```python
import torch

def _softmax(x, axis=-1):
    return torch.softmax(x, dim=axis)

def _gelu(x):
    return torch.nn.functional.gelu(x, approximate='tanh')

def _silu(x):
    return torch.nn.functional.silu(x)

def _sigmoid(x):
    return torch.sigmoid(x)

def _layernorm(x, axis=-1, eps=1e-05):
    m = x.mean(dim=axis, keepdim=True)
    v = x.var(dim=axis, keepdim=True, unbiased=False)
    return (x - m) / torch.sqrt(v + eps)

def _scatter_add(tgt, idx, src, axis=0):
    return tgt.clone().index_add_(axis, idx, src)

def _segment_sum(src, seg, n):
    out = torch.zeros((n,) + src.shape[1:], dtype=src.dtype)
    return out.index_add_(0, seg, src)

def _pad(x, pw):
    flat = tuple((v for pair in reversed(pw) for v in pair))
    return torch.nn.functional.pad(x, flat)
kernel_name = 'adaLN_cond__softmax_full_mha__glu_gated_glu__prompt'

def setup_inputs():

    _w = lambda a: (lambda t: t.to(torch.bfloat16) if t.is_floating_point() else t)(torch.as_tensor(a))

    def _A_setup():
        B, S, D = (1, 2048, 576)
        return {'x': _w((lambda *s: torch.randn(*s, dtype=torch.bfloat16) * 0.05)(B, S, D)), 'wqkv': _w((lambda *s: torch.randn(*s, dtype=torch.bfloat16) * 0.05)(D, 3 * D)), 'wo': _w((lambda *s: torch.randn(*s, dtype=torch.bfloat16) * 0.05)(D, D))}
    _A_in = _A_setup()

    def _B_setup():
        B, S, D, F = (1, 2048, 576, 4608)
        return {'x': _w((lambda *s: torch.randn(*s, dtype=torch.bfloat16) * 0.05)(B, S, D)), 'w_gate': _w((lambda *s: torch.randn(*s, dtype=torch.bfloat16) * 0.05)(D, F)), 'w_up': _w((lambda *s: torch.randn(*s, dtype=torch.bfloat16) * 0.05)(D, F)), 'w_down': _w((lambda *s: torch.randn(*s, dtype=torch.bfloat16) * 0.05)(F, D))}
    _B_in = _B_setup()
    return {'A_x': _A_in['x'], 'A_wqkv': _A_in['wqkv'], 'A_wo': _A_in['wo'], 'B_x': _B_in['x'], 'B_w_gate': _B_in['w_gate'], 'B_w_up': _B_in['w_up'], 'B_w_down': _B_in['w_down'], 'c': _w((lambda *s: torch.randn(*s, dtype=torch.bfloat16) * 0.1)(1, 576) * 8.0), 'w_mod': _w((lambda *s: torch.randn(*s, dtype=torch.bfloat16) * 0.1)(576, 6 * 576) * 576 ** (-0.5) * 8.0)}

def reference(A_x, A_wqkv, A_wo, B_x, B_w_gate, B_w_up, B_w_down, c, w_mod):

    def _A_ref(x, wqkv, wo):
        B, S, D = x.shape
        H = 32
        Dh = D // H
        qkv = (lambda x, *d: x.permute(*d))((x @ wqkv).reshape(B, S, 3, H, Dh), 2, 0, 3, 1, 4)
        q, k, v = (qkv[0], qkv[1], qkv[2])
        scale = Dh ** (-0.5)
        scores = torch.einsum('bhqd,bhkd->bhqk', q, k) * scale
        p = _softmax(scores, axis=-1)
        o = torch.einsum('bhqk,bhkd->bhqd', p, v)
        return (lambda x, *d: x.permute(*d))(o, 0, 2, 1, 3).reshape(B, S, D) @ wo

    def _B_ref(x, w_gate, w_up, w_down):
        g = torch.einsum('bsd,df->bsf', x, w_gate)
        u = torch.einsum('bsd,df->bsf', x, w_up)
        h = _sigmoid(g) * u
        return torch.einsum('bsf,fd->bsd', h, w_down)
    x = A_x
    mod = (_silu(c) @ w_mod).reshape(c.shape[0], 6, 1, -1)
    sa, ca, ga, sb, cb, gb = (mod[:, 0].clone(), mod[:, 1].clone(), mod[:, 2].clone(), mod[:, 3].clone(), mod[:, 4].clone(), mod[:, 5].clone())
    h = _layernorm(x, axis=-1) * (1 + ca) + sa
    x = x + ga * _A_ref(h, A_wqkv, A_wo)
    h = _layernorm(x, axis=-1) * (1 + cb) + sb
    x = x + gb * _B_ref(h, B_w_gate, B_w_up, B_w_down)
    return x
```

```cpp
#include <cuda_runtime.h>
#include <cuda_bf16.h>
#include <cuda.h>
#include <stdint.h>

#define SEQ 2048
#define DM 576
#define NH 32
#define FF 4608

__device__ uint4 g_tab1[36 * 4];
__device__ uint4 g_tab2[36 * 4];
__device__ float g_ga[DM];
__device__ float g_gb[DM];
__device__ uint4 g_stat1[SEQ];
__device__ float2 g_stat2[SEQ * 8];
__device__ __align__(1024) uint8_t g_qkv[96 * 98304];
__device__ float g_kmax[NH * 16];
__device__ __align__(1024) __nv_bfloat16 g_o[SEQ * DM];
__device__ __align__(1024) __nv_bfloat16 g_x1[SEQ * DM];
__device__ __align__(1024) uint8_t g_part[8 * 16 * 5 * 2 * 16384];
__device__ unsigned int g_cnt[16 * 5];

__device__ __forceinline__ uint32_t s2u(const void* p) { return (uint32_t)__cvta_generic_to_shared(p); }
__device__ __forceinline__ void mbar_init(uint32_t b, int c) { asm volatile("mbarrier.init.shared::cta.b64 [%0],%1;" ::"r"(b), "r"(c)); }
__device__ __forceinline__ void mbar_expect(uint32_t b, uint32_t n) { asm volatile("mbarrier.arrive.expect_tx.shared::cta.b64 _,[%0],%1;" ::"r"(b), "r"(n) : "memory"); }
__device__ __forceinline__ void mbar_arrive(uint32_t b) { asm volatile("mbarrier.arrive.shared::cta.b64 _,[%0];" ::"r"(b) : "memory"); }
__device__ __forceinline__ void mbar_wait(uint32_t b, uint32_t ph) {
  asm volatile(
      "{.reg .pred p; .reg .u32 n; mov.u32 n,0;\n"
      "W: mbarrier.try_wait.parity.shared::cta.b64 p,[%0],%1;\n"
      "@p bra D;\n"
      "add.u32 n,n,1; setp.lt.u32 p,n,4000000; @p bra W;\n"
      "trap;\n"
      "D: }" ::"r"(b), "r"(ph) : "memory");
}
__device__ __forceinline__ void tma2d(uint32_t dst, const CUtensorMap* m, int c0, int c1, uint32_t bar) {
  asm volatile("cp.async.bulk.tensor.2d.shared::cluster.global.mbarrier::complete_tx::bytes [%0],[%1,{%3,%4}],[%2];"
               ::"r"(dst), "l"(m), "r"(bar), "r"(c0), "r"(c1) : "memory");
}
__device__ __forceinline__ void bulk_g2s(uint32_t dst, const void* src, uint32_t bytes, uint32_t bar) {
  asm volatile("cp.async.bulk.shared::cluster.global.mbarrier::complete_tx::bytes [%0],[%1],%2,[%3];"
               ::"r"(dst), "l"(src), "r"(bytes), "r"(bar) : "memory");
}
__device__ __forceinline__ void bulk_s2g(void* dst, uint32_t src, uint32_t bytes) {
  asm volatile("cp.async.bulk.global.shared::cta.bulk_group [%0],[%1],%2;" ::"l"(dst), "r"(src), "r"(bytes) : "memory");
}
__device__ __forceinline__ void bulk_commit() { asm volatile("cp.async.bulk.commit_group;" ::: "memory"); }
__device__ __forceinline__ void bulk_wait0() { asm volatile("cp.async.bulk.wait_group 0;" ::: "memory"); }
__device__ __forceinline__ void prefetch_map(const CUtensorMap* m) { asm volatile("prefetch.tensormap [%0];" ::"l"(m) : "memory"); }
__device__ __forceinline__ void fence_async_smem() { asm volatile("fence.proxy.async.shared::cta;" ::: "memory"); }
__device__ __forceinline__ void fence_bar_init() { asm volatile("fence.mbarrier_init.release.cluster;" ::: "memory"); }
__device__ __forceinline__ void pdl_wait() { asm volatile("griddepcontrol.wait;" ::: "memory"); }
__device__ __forceinline__ void pdl_launch() { asm volatile("griddepcontrol.launch_dependents;" ::: "memory"); }
__device__ __forceinline__ void bar_sync(int id, int n) { asm volatile("bar.sync %0,%1;" ::"r"(id), "r"(n) : "memory"); }
__device__ __forceinline__ void bar_arrive(int id, int n) { asm volatile("bar.arrive %0,%1;" ::"r"(id), "r"(n) : "memory"); }
#define WG_FENCE() asm volatile("wgmma.fence.sync.aligned;" ::: "memory")
#define WG_COMMIT() asm volatile("wgmma.commit_group.sync.aligned;" ::: "memory")
#define WG_WAIT(n) asm volatile("wgmma.wait_group.sync.aligned " #n ";" ::: "memory")
#define REG_INC(n) asm volatile("setmaxnreg.inc.sync.aligned.u32 " #n ";")
#define REG_DEC(n) asm volatile("setmaxnreg.dec.sync.aligned.u32 " #n ";")
__device__ __forceinline__ uint64_t mkdesc(uint32_t addr, uint32_t lbo, uint32_t sbo, int sw) {
  return (uint64_t)((addr & 0x3FFFF) >> 4) | ((uint64_t)(lbo >> 4) << 16) | ((uint64_t)(sbo >> 4) << 32) | ((uint64_t)sw << 62);
}
__device__ __forceinline__ void ldsm4(uint32_t* r, uint32_t addr) {
  asm volatile("ldmatrix.sync.aligned.m8n8.x4.shared.b16 {%0,%1,%2,%3},[%4];" : "=r"(r[0]), "=r"(r[1]), "=r"(r[2]), "=r"(r[3]) : "r"(addr) : "memory");
}
__device__ __forceinline__ void stsm4(uint32_t addr, uint32_t r0, uint32_t r1, uint32_t r2, uint32_t r3) {
  asm volatile("stmatrix.sync.aligned.m8n8.x4.shared.b16 [%0],{%1,%2,%3,%4};" ::"r"(addr), "r"(r0), "r"(r1), "r"(r2), "r"(r3) : "memory");
}
__device__ __forceinline__ uint32_t pack_bf16(float lo, float hi) {
  uint32_t r;
  asm("cvt.rn.bf16x2.f32 %0,%1,%2;" : "=r"(r) : "f"(hi), "f"(lo));
  return r;
}
__device__ __forceinline__ float bf_lo(uint32_t v) { return __uint_as_float(v << 16); }
__device__ __forceinline__ float bf_hi(uint32_t v) { return __uint_as_float(v & 0xFFFF0000u); }
__device__ __forceinline__ float rbf(float x) { return __bfloat162float(__float2bfloat16_rn(x)); }
__device__ __forceinline__ uint32_t hfma2(uint32_t a, uint32_t b, uint32_t c) {
  uint32_t r;
  asm("fma.rn.bf16x2 %0,%1,%2,%3;" : "=r"(r) : "r"(a), "r"(b), "r"(c));
  return r;
}
__device__ __forceinline__ uint32_t hadd2(uint32_t a, uint32_t b) {
  uint32_t r;
  asm("add.rn.bf16x2 %0,%1,%2;" : "=r"(r) : "r"(a), "r"(b));
  return r;
}
__device__ __forceinline__ uint32_t hmul2(uint32_t a, uint32_t b) {
  uint32_t r;
  asm("mul.rn.bf16x2 %0,%1,%2;" : "=r"(r) : "r"(a), "r"(b));
  return r;
}
__device__ __forceinline__ uint32_t hneg2(uint32_t a) {
  uint32_t r;
  asm("neg.bf16x2 %0,%1;" : "=r"(r) : "r"(a));
  return r;
}
__device__ __forceinline__ float ex2f(float x) {
  float r;
  asm("ex2.approx.ftz.f32 %0,%1;" : "=f"(r) : "f"(x));
  return r;
}
__device__ __forceinline__ float tanhf_fast(float x) {
  float r;
  asm("tanh.approx.f32 %0,%1;" : "=f"(r) : "f"(x));
  return r;
}
__device__ __forceinline__ uint4 ln_consts(float mean, float var) {
  float m = rbf(mean), v = rbf(var);
  float s = rbf(sqrtf(rbf(v + 1e-5f)));
  float r = 1.0f / s;
  float rh = rbf(r), rl = r - rh;
  return make_uint4(pack_bf16(-m, -m), pack_bf16(rh, rh), pack_bf16(rl, rl), 0u);
}
__device__ __forceinline__ uint32_t ln_apply(uint32_t x, const uint4& st, uint32_t a, uint32_t s) {
  uint32_t d = hadd2(x, st.x);
  uint32_t n = hfma2(d, st.y, hmul2(d, st.z));
  return hfma2(n, a, s);
}

__device__ __forceinline__ void wg_rs_n128_t1(float* d, uint32_t a0, uint32_t a1, uint32_t a2, uint32_t a3, uint64_t db, int sc) {
  asm volatile("{.reg .pred p; setp.ne.b32 p,%69,0; wgmma.mma_async.sync.aligned.m64n128k16.f32.bf16.bf16 {%0,%1,%2,%3,%4,%5,%6,%7,%8,%9,%10,%11,%12,%13,%14,%15,%16,%17,%18,%19,%20,%21,%22,%23,%24,%25,%26,%27,%28,%29,%30,%31,%32,%33,%34,%35,%36,%37,%38,%39,%40,%41,%42,%43,%44,%45,%46,%47,%48,%49,%50,%51,%52,%53,%54,%55,%56,%57,%58,%59,%60,%61,%62,%63}, {%64,%65,%66,%67}, %68, p,1,1,1;}"
  : "+f"(d[0]),"+f"(d[1]),"+f"(d[2]),"+f"(d[3]),"+f"(d[4]),"+f"(d[5]),"+f"(d[6]),"+f"(d[7]),"+f"(d[8]),"+f"(d[9]),"+f"(d[10]),"+f"(d[11]),"+f"(d[12]),"+f"(d[13]),"+f"(d[14]),"+f"(d[15]),"+f"(d[16]),"+f"(d[17]),"+f"(d[18]),"+f"(d[19]),"+f"(d[20]),"+f"(d[21]),"+f"(d[22]),"+f"(d[23]),"+f"(d[24]),"+f"(d[25]),"+f"(d[26]),"+f"(d[27]),"+f"(d[28]),"+f"(d[29]),"+f"(d[30]),"+f"(d[31]),"+f"(d[32]),"+f"(d[33]),"+f"(d[34]),"+f"(d[35]),"+f"(d[36]),"+f"(d[37]),"+f"(d[38]),"+f"(d[39]),"+f"(d[40]),"+f"(d[41]),"+f"(d[42]),"+f"(d[43]),"+f"(d[44]),"+f"(d[45]),"+f"(d[46]),"+f"(d[47]),"+f"(d[48]),"+f"(d[49]),"+f"(d[50]),"+f"(d[51]),"+f"(d[52]),"+f"(d[53]),"+f"(d[54]),"+f"(d[55]),"+f"(d[56]),"+f"(d[57]),"+f"(d[58]),"+f"(d[59]),"+f"(d[60]),"+f"(d[61]),"+f"(d[62]),"+f"(d[63]) : "r"(a0),"r"(a1),"r"(a2),"r"(a3),"l"(db),"r"(sc));
}
__device__ __forceinline__ void wg_rs_n24_t1(float* d, uint32_t a0, uint32_t a1, uint32_t a2, uint32_t a3, uint64_t db, int sc) {
  asm volatile("{.reg .pred p; setp.ne.b32 p,%17,0; wgmma.mma_async.sync.aligned.m64n24k16.f32.bf16.bf16 {%0,%1,%2,%3,%4,%5,%6,%7,%8,%9,%10,%11}, {%12,%13,%14,%15}, %16, p,1,1,1;}"
  : "+f"(d[0]),"+f"(d[1]),"+f"(d[2]),"+f"(d[3]),"+f"(d[4]),"+f"(d[5]),"+f"(d[6]),"+f"(d[7]),"+f"(d[8]),"+f"(d[9]),"+f"(d[10]),"+f"(d[11]) : "r"(a0),"r"(a1),"r"(a2),"r"(a3),"l"(db),"r"(sc));
}
__device__ __forceinline__ void wg_rs_n64_t0(float* d, uint32_t a0, uint32_t a1, uint32_t a2, uint32_t a3, uint64_t db, int sc) {
  asm volatile("{.reg .pred p; setp.ne.b32 p,%37,0; wgmma.mma_async.sync.aligned.m64n64k16.f32.bf16.bf16 {%0,%1,%2,%3,%4,%5,%6,%7,%8,%9,%10,%11,%12,%13,%14,%15,%16,%17,%18,%19,%20,%21,%22,%23,%24,%25,%26,%27,%28,%29,%30,%31}, {%32,%33,%34,%35}, %36, p,1,1,0;}"
  : "+f"(d[0]),"+f"(d[1]),"+f"(d[2]),"+f"(d[3]),"+f"(d[4]),"+f"(d[5]),"+f"(d[6]),"+f"(d[7]),"+f"(d[8]),"+f"(d[9]),"+f"(d[10]),"+f"(d[11]),"+f"(d[12]),"+f"(d[13]),"+f"(d[14]),"+f"(d[15]),"+f"(d[16]),"+f"(d[17]),"+f"(d[18]),"+f"(d[19]),"+f"(d[20]),"+f"(d[21]),"+f"(d[22]),"+f"(d[23]),"+f"(d[24]),"+f"(d[25]),"+f"(d[26]),"+f"(d[27]),"+f"(d[28]),"+f"(d[29]),"+f"(d[30]),"+f"(d[31]) : "r"(a0),"r"(a1),"r"(a2),"r"(a3),"l"(db),"r"(sc));
}
__device__ __forceinline__ void wg_rs_n64_t1(float* d, uint32_t a0, uint32_t a1, uint32_t a2, uint32_t a3, uint64_t db, int sc) {
  asm volatile("{.reg .pred p; setp.ne.b32 p,%37,0; wgmma.mma_async.sync.aligned.m64n64k16.f32.bf16.bf16 {%0,%1,%2,%3,%4,%5,%6,%7,%8,%9,%10,%11,%12,%13,%14,%15,%16,%17,%18,%19,%20,%21,%22,%23,%24,%25,%26,%27,%28,%29,%30,%31}, {%32,%33,%34,%35}, %36, p,1,1,1;}"
  : "+f"(d[0]),"+f"(d[1]),"+f"(d[2]),"+f"(d[3]),"+f"(d[4]),"+f"(d[5]),"+f"(d[6]),"+f"(d[7]),"+f"(d[8]),"+f"(d[9]),"+f"(d[10]),"+f"(d[11]),"+f"(d[12]),"+f"(d[13]),"+f"(d[14]),"+f"(d[15]),"+f"(d[16]),"+f"(d[17]),"+f"(d[18]),"+f"(d[19]),"+f"(d[20]),"+f"(d[21]),"+f"(d[22]),"+f"(d[23]),"+f"(d[24]),"+f"(d[25]),"+f"(d[26]),"+f"(d[27]),"+f"(d[28]),"+f"(d[29]),"+f"(d[30]),"+f"(d[31]) : "r"(a0),"r"(a1),"r"(a2),"r"(a3),"l"(db),"r"(sc));
}
__device__ __forceinline__ void wg_rs_n88_t1(float* d, uint32_t a0, uint32_t a1, uint32_t a2, uint32_t a3, uint64_t db, int sc) {
  asm volatile("{.reg .pred p; setp.ne.b32 p,%49,0; wgmma.mma_async.sync.aligned.m64n88k16.f32.bf16.bf16 {%0,%1,%2,%3,%4,%5,%6,%7,%8,%9,%10,%11,%12,%13,%14,%15,%16,%17,%18,%19,%20,%21,%22,%23,%24,%25,%26,%27,%28,%29,%30,%31,%32,%33,%34,%35,%36,%37,%38,%39,%40,%41,%42,%43}, {%44,%45,%46,%47}, %48, p,1,1,1;}"
  : "+f"(d[0]),"+f"(d[1]),"+f"(d[2]),"+f"(d[3]),"+f"(d[4]),"+f"(d[5]),"+f"(d[6]),"+f"(d[7]),"+f"(d[8]),"+f"(d[9]),"+f"(d[10]),"+f"(d[11]),"+f"(d[12]),"+f"(d[13]),"+f"(d[14]),"+f"(d[15]),"+f"(d[16]),"+f"(d[17]),"+f"(d[18]),"+f"(d[19]),"+f"(d[20]),"+f"(d[21]),"+f"(d[22]),"+f"(d[23]),"+f"(d[24]),"+f"(d[25]),"+f"(d[26]),"+f"(d[27]),"+f"(d[28]),"+f"(d[29]),"+f"(d[30]),"+f"(d[31]),"+f"(d[32]),"+f"(d[33]),"+f"(d[34]),"+f"(d[35]),"+f"(d[36]),"+f"(d[37]),"+f"(d[38]),"+f"(d[39]),"+f"(d[40]),"+f"(d[41]),"+f"(d[42]),"+f"(d[43]) : "r"(a0),"r"(a1),"r"(a2),"r"(a3),"l"(db),"r"(sc));
}
__device__ __forceinline__ void wg_ss_n72_t1(float* d, uint64_t da, uint64_t db, int sc) {
  asm volatile("{.reg .pred p; setp.ne.b32 p,%38,0; wgmma.mma_async.sync.aligned.m64n72k16.f32.bf16.bf16 {%0,%1,%2,%3,%4,%5,%6,%7,%8,%9,%10,%11,%12,%13,%14,%15,%16,%17,%18,%19,%20,%21,%22,%23,%24,%25,%26,%27,%28,%29,%30,%31,%32,%33,%34,%35}, %36, %37, p,1,1,0,1;}"
  : "+f"(d[0]),"+f"(d[1]),"+f"(d[2]),"+f"(d[3]),"+f"(d[4]),"+f"(d[5]),"+f"(d[6]),"+f"(d[7]),"+f"(d[8]),"+f"(d[9]),"+f"(d[10]),"+f"(d[11]),"+f"(d[12]),"+f"(d[13]),"+f"(d[14]),"+f"(d[15]),"+f"(d[16]),"+f"(d[17]),"+f"(d[18]),"+f"(d[19]),"+f"(d[20]),"+f"(d[21]),"+f"(d[22]),"+f"(d[23]),"+f"(d[24]),"+f"(d[25]),"+f"(d[26]),"+f"(d[27]),"+f"(d[28]),"+f"(d[29]),"+f"(d[30]),"+f"(d[31]),"+f"(d[32]),"+f"(d[33]),"+f"(d[34]),"+f"(d[35]) : "l"(da),"l"(db),"r"(sc));
}


#define POLY_MASK 0xB5u
#define QSCALE (0.23570226039551584f * 1.4426950408889634f)

__global__ void __launch_bounds__(256) k0_kernel(const __nv_bfloat16* __restrict__ x, const __nv_bfloat16* __restrict__ c,
                                                 const __nv_bfloat16* __restrict__ wmod) {
  pdl_launch();
  const int tid = threadIdx.x, lane = tid & 31, warp = tid >> 5;
  if (blockIdx.x < 108) {
    __shared__ float red[8][32];
    const int col0 = blockIdx.x * 32 + (tid & 3) * 8, r0 = tid >> 2;
    uint4 w[9];
#pragma unroll
    for (int i = 0; i < 9; i++) w[i] = __ldg((const uint4*)(wmod + (size_t)(r0 + 64 * i) * 3456 + col0));
    float acc[8] = {0, 0, 0, 0, 0, 0, 0, 0};
#pragma unroll
    for (int i = 0; i < 9; i++) {
      float cv = __bfloat162float(c[r0 + 64 * i]);
      float sv = rbf(cv / (1.0f + __expf(-cv)));
      acc[0] += sv * bf_lo(w[i].x); acc[1] += sv * bf_hi(w[i].x);
      acc[2] += sv * bf_lo(w[i].y); acc[3] += sv * bf_hi(w[i].y);
      acc[4] += sv * bf_lo(w[i].z); acc[5] += sv * bf_hi(w[i].z);
      acc[6] += sv * bf_lo(w[i].w); acc[7] += sv * bf_hi(w[i].w);
    }
#pragma unroll
    for (int j = 0; j < 8; j++) {
      acc[j] += __shfl_xor_sync(~0u, acc[j], 4);
      acc[j] += __shfl_xor_sync(~0u, acc[j], 8);
      acc[j] += __shfl_xor_sync(~0u, acc[j], 16);
    }
    if (lane < 4) {
#pragma unroll
      for (int j = 0; j < 8; j++) red[warp][lane * 8 + j] = acc[j];
    }
    __syncthreads();
    if (tid < 32) {
      float s = 0;
#pragma unroll
      for (int j = 0; j < 8; j++) s += red[j][tid];
      s = rbf(s);
      int n = blockIdx.x * 32 + tid, part = n / DM, col = n % DM;
      if (part == 2) g_ga[col] = s;
      else if (part == 5) g_gb[col] = s;
      else {
        __nv_bfloat16* tab = (__nv_bfloat16*)(part < 2 ? g_tab1 : g_tab2);
        bool shift = (part == 0 || part == 3);
        int kk = col >> 4, half = (col >> 3) & 1, cq = (col & 7) >> 1, e = col & 1;
        tab[((kk * 4 + cq) * 4 + half * 2 + (shift ? 1 : 0)) * 2 + e] = __float2bfloat16_rn(shift ? s : 1.0f + s);
      }
    }
    if (blockIdx.x == 0 && tid >= 64 && tid < 64 + 80) g_cnt[tid - 64] = 0;
  } else {
    const int row0 = (blockIdx.x - 108) * 16 + warp * 2;
    uint32_t v[2][9];
#pragma unroll
    for (int r = 0; r < 2; r++)
#pragma unroll
      for (int i = 0; i < 9; i++) v[r][i] = __ldg((const uint32_t*)(x + (size_t)(row0 + r) * DM) + lane + 32 * i);
#pragma unroll
    for (int r = 0; r < 2; r++) {
      float s = 0;
#pragma unroll
      for (int i = 0; i < 9; i++) s += bf_lo(v[r][i]) + bf_hi(v[r][i]);
#pragma unroll
      for (int o = 16; o; o >>= 1) s += __shfl_xor_sync(~0u, s, o);
      float mean = s * (1.0f / DM), q = 0;
#pragma unroll
      for (int i = 0; i < 9; i++) {
        float a = bf_lo(v[r][i]) - mean, b = bf_hi(v[r][i]) - mean;
        q += a * a + b * b;
      }
#pragma unroll
      for (int o = 16; o; o >>= 1) q += __shfl_xor_sync(~0u, q, o);
      if (lane == 0) g_stat1[row0 + r] = ln_consts(mean, q * (1.0f / DM));
    }
  }
}

#define NSTG 6
#define STG_BYTES 16384
#define R_BYTES (8 * 16384)
#define GEMM_SMEM (R_BYTES + NSTG * STG_BYTES + 1024 + 256)

struct Ring {
  uint32_t base, full, empty;
  int st;
  uint32_t ph;
  __device__ __forceinline__ void next() { if (++st == NSTG) { st = 0; ph ^= 1; } }
};

__device__ __forceinline__ void load_a_chunk(uint32_t (*a)[4], uint32_t chunk_base, int row_in_tile, int lane) {
  const int r = row_in_tile + (lane & 7) + ((lane >> 3) & 1) * 8;
  const uint32_t rb = chunk_base + r * 128;
#pragma unroll
  for (int k = 0; k < 4; k++) ldsm4(a[k], rb + (((k * 2 + (lane >> 4)) ^ (r & 7)) << 4));
}

#define MMA_TILE(FN, acc, a, ring, lane)                                        \
  {                                                                             \
    uint32_t prev_empty = 0;                                                    \
    _Pragma("unroll") for (int s = 0; s < 9; s++) {                             \
      mbar_wait(ring.full + ring.st * 8, ring.ph);                              \
      WG_FENCE();                                                               \
      uint64_t db = mkdesc(ring.base + ring.st * STG_BYTES, 8192, 1024, 1);     \
      _Pragma("unroll") for (int k = 0; k < 4; k++)                             \
          FN(acc, a[s * 4 + k][0], a[s * 4 + k][1], a[s * 4 + k][2], a[s * 4 + k][3], db + k * 128, (s | k) != 0); \
      WG_COMMIT();                                                              \
      if (s > 0) { WG_WAIT(1); if (lane == 0) mbar_arrive(prev_empty); }        \
      prev_empty = ring.empty + ring.st * 8;                                    \
      ring.next();                                                              \
    }                                                                           \
    WG_WAIT(0);                                                                 \
    if (lane == 0) mbar_arrive(prev_empty);                                     \
  }

template <int NG, int G0>
__device__ __forceinline__ void qkv_stage(const float* acc, uint32_t stg, int rowl, int cq, int col_base) {
#pragma unroll
  for (int i = 0; i < NG; i++) {
    const int cc = (G0 + i) * 8 + cq * 2;
    const int slot = (cc * 3641) >> 16, d = cc - slot * 18;
    const float sc = (col_base + cc < DM) ? QSCALE : 1.0f;
    const uint32_t ad = stg + slot * 6144 + (d >> 3) * 128 + (d & 7) * 2 + (rowl >> 3) * 384 + (rowl & 7) * 16;
    asm volatile("st.shared.b32 [%0],%1;" ::"r"(ad), "r"(pack_bf16(acc[4 * i] * sc, acc[4 * i + 1] * sc)) : "memory");
    asm volatile("st.shared.b32 [%0],%1;" ::"r"(ad + 384), "r"(pack_bf16(acc[4 * i + 2] * sc, acc[4 * i + 3] * sc)) : "memory");
  }
}

__global__ void __launch_bounds__(384, 1) k1_kernel(const __grid_constant__ CUtensorMap mx, const __grid_constant__ CUtensorMap mw) {
  extern __shared__ uint8_t smem_raw[];
  const uint32_t sb = (s2u(smem_raw) + 1023) & ~1023u;
  const uint32_t R = sb, RING = sb + R_BYTES, BAR = RING + NSTG * STG_BYTES;
  const uint32_t full = BAR, empty = BAR + 64, xfull = BAR + 128;
  const int tid = threadIdx.x, lane = tid & 31, warp = tid >> 5;
  const int mb = blockIdx.x >> 3, nb = blockIdx.x & 7;
  if (tid == 0) {
    for (int i = 0; i < NSTG; i++) { mbar_init(full + i * 8, 1); mbar_init(empty + i * 8, 8); }
    for (int i = 0; i < 8; i++) mbar_init(xfull + i * 8, 1);
    fence_bar_init();
  }
  __syncthreads();
  pdl_launch();
  if (warp >= 8) {
    REG_DEC(40);
    if (warp == 8) {
      if (lane == 0) {
        for (int c = 0; c < 8; c++) { mbar_expect(xfull + c * 8, 16384); tma2d(R + c * 16384, &mx, c * 64, mb * 128, xfull + c * 8); }
        mbar_expect(full, 16384);
        tma2d(RING, &mx, 512, mb * 128, full);
        int st = 1; uint32_t ph = 0;
        for (int it = 0; it < 18; it++) {
          const int t = it / 9, s = it - t * 9;
          mbar_wait(empty + st * 8, ph ^ 1);
          mbar_expect(full + st * 8, 16384);
          tma2d(RING + st * STG_BYTES, &mw, nb * 216 + t * 128, s * 64, full + st * 8);
          tma2d(RING + st * STG_BYTES + 8192, &mw, nb * 216 + t * 128 + 64, s * 64, full + st * 8);
          if (++st == NSTG) { st = 0; ph ^= 1; }
        }
      }
      pdl_wait();
    } else {
      const int ht = tid - 288;
      bar_sync(1, 352);
      for (int i = ht; i < 12 * 128; i += 96) {
        const int slot = i >> 7, row = i & 127, type = (nb * 12 + slot) >> 5;
        uint32_t v = 0;
        if (type == 1) v = 0x3F80u | (((POLY_MASK >> ((row >> 3) & 7)) & 1) ? 0x43C00000u : 0x3F800000u);
        if (type == 2) v = 0x3F80u;
        const uint32_t ad = R + slot * 6144 + (row >> 3) * 384 + 256 + (row & 7) * 16;
        asm volatile("st.shared.b32 [%0],%1;" ::"r"(ad + 4), "r"(v) : "memory");
        asm volatile("st.shared.v2.b32 [%0],{%1,%1};" ::"r"(ad + 8), "r"(0) : "memory");
      }
      fence_async_smem();
      pdl_wait();
#pragma unroll 1
      for (int t = 0; t < 2; t++) {
        bar_sync(2 + t, 352);
        const int s0 = t ? 7 : 0, s1 = t ? 12 : 7;
        if (ht == 0) {
          for (int s = s0; s < s1; s++) bulk_s2g(g_qkv + (size_t)(nb * 12 + s) * 98304 + mb * 6144, R + s * 6144, 6144);
          bulk_commit();
        }
        for (int s = s0 + (warp - 9); s < s1; s += 3) {
          const int gs = nb * 12 + s;
          if ((gs >> 5) != 1) continue;
          float mx2 = 0;
#pragma unroll 1
          for (int row = lane; row < 128; row += 32) {
            const uint32_t ad = R + s * 6144 + (row >> 3) * 384 + (row & 7) * 16;
            uint32_t u[9];
            asm volatile("ld.shared.v4.b32 {%0,%1,%2,%3},[%4];" : "=r"(u[0]), "=r"(u[1]), "=r"(u[2]), "=r"(u[3]) : "r"(ad));
            asm volatile("ld.shared.v4.b32 {%0,%1,%2,%3},[%4];" : "=r"(u[4]), "=r"(u[5]), "=r"(u[6]), "=r"(u[7]) : "r"(ad + 128));
            asm volatile("ld.shared.b32 %0,[%1];" : "=r"(u[8]) : "r"(ad + 256));
            float q = 0;
#pragma unroll
            for (int j = 0; j < 9; j++) q += bf_lo(u[j]) * bf_lo(u[j]) + bf_hi(u[j]) * bf_hi(u[j]);
            mx2 = (q > mx2 || q != q) ? q : mx2;
            if (mx2 != mx2) mx2 = __int_as_float(0x7f800000);
          }
#pragma unroll
          for (int o = 16; o; o >>= 1) mx2 = fmaxf(mx2, __shfl_xor_sync(~0u, mx2, o));
          if (lane == 0) g_kmax[(gs & 31) * 16 + mb] = mx2;
        }
      }
      if (ht == 0) bulk_wait0();
    }
  } else {
    REG_INC(232);
    uint32_t a[36][4];
    const int rowl = warp * 16;
#pragma unroll
    for (int c = 0; c < 8; c++) { mbar_wait(xfull + c * 8, 0); load_a_chunk(&a[c * 4], R + c * 16384, rowl, lane); }
    mbar_wait(full, 0);
    load_a_chunk(&a[32], RING, rowl, lane);
    __syncwarp();
    if (lane == 0) mbar_arrive(empty);
    bar_arrive(1, 352);
    pdl_wait();
    {
      const int g = lane >> 2, cq = lane & 3;
      const uint4 s0 = g_stat1[mb * 128 + rowl + g], s1 = g_stat1[mb * 128 + rowl + g + 8];
#pragma unroll
      for (int k = 0; k < 36; k++) {
        const uint4 t = g_tab1[k * 4 + cq];
        a[k][0] = ln_apply(a[k][0], s0, t.x, t.y);
        a[k][1] = ln_apply(a[k][1], s1, t.x, t.y);
        a[k][2] = ln_apply(a[k][2], s0, t.z, t.w);
        a[k][3] = ln_apply(a[k][3], s1, t.z, t.w);
      }
    }
    bar_sync(4, 256);
    Ring ring{RING, full, empty, 1, 0};
    float acc[64];
    MMA_TILE(wg_rs_n128_t1, acc, a, ring, lane);
    qkv_stage<16, 0>(acc, R, rowl + (lane >> 2), lane & 3, nb * 216);
    fence_async_smem();
    bar_arrive(2, 352);
    MMA_TILE(wg_rs_n88_t1, acc, a, ring, lane);
    qkv_stage<11, 16>(acc, R, rowl + (lane >> 2), lane & 3, nb * 216);
    fence_async_smem();
    bar_arrive(3, 352);
  }
}

#define ATT_SMEM (2 * 98304 + 1024 + 256)

__device__ __forceinline__ uint32_t exp2_pair_fma(float t0, float t1) {
  uint32_t y, m;
  asm("prmt.b32 %0,%1,%2,0x6521;" : "=r"(y) : "r"(__float_as_uint(t0)), "r"(__float_as_uint(t1)));
  m = (y & 0x007F007Fu) | 0x3F803F80u;
  const uint32_t w = hfma2(m, 0x3EF73EF7u, 0xBF37BF37u);
  const uint32_t h = hfma2(w, w, 0xBD63BD63u);
  const uint32_t ny = hneg2(y);
  return hfma2(ny, h, ny);
}

__device__ __forceinline__ void softmax_fast(const float* s, uint32_t* p) {
#pragma unroll
  for (int i = 0; i < 8; i++) {
    if ((POLY_MASK >> i) & 1) {
      p[2 * i] = exp2_pair_fma(s[4 * i], s[4 * i + 1]);
      p[2 * i + 1] = exp2_pair_fma(s[4 * i + 2], s[4 * i + 3]);
    } else {
      p[2 * i] = pack_bf16(ex2f(s[4 * i]), ex2f(s[4 * i + 1]));
      p[2 * i + 1] = pack_bf16(ex2f(s[4 * i + 2]), ex2f(s[4 * i + 3]));
    }
  }
}
#define QK_MMA(S, kaddr)                                                        \
  wg_rs_n64_t0(S, q[0], q[1], q[2], q[3], mkdesc(kaddr, 128, 384, 0), 0);       \
  wg_rs_n64_t0(S, q[4], q[5], 0u, 0u, mkdesc((kaddr) + 256, 0, 384, 0), 1);
#define PV_MMA(P, vaddr)                                                        \
  _Pragma("unroll") for (int t = 0; t < 4; t++)                                 \
      wg_rs_n24_t1(o, P[4 * t], P[4 * t + 1], P[4 * t + 2], P[4 * t + 3], mkdesc((vaddr) + t * 768, 384, 128, 0), 1);

__global__ void __launch_bounds__(512, 1) k2_kernel() {
  extern __shared__ uint8_t smem_raw[];
  const uint32_t sb = (s2u(smem_raw) + 1023) & ~1023u;
  const uint32_t KS = sb, VS = sb + 98304, BAR = sb + 2 * 98304;
  const int tid = threadIdx.x, lane = tid & 31, warp = tid >> 5, wg = tid >> 7;
  const int head = blockIdx.x >> 2, qb = blockIdx.x & 3;
  if (tid == 0) {
    for (int i = 0; i < 16; i++) mbar_init(BAR + i * 8, 1);
    fence_bar_init();
  }
  __syncthreads();
  pdl_launch();
  pdl_wait();
  if (tid == 0) {
    const uint8_t* kg = g_qkv + (size_t)(32 + head) * 98304;
    const uint8_t* vg = g_qkv + (size_t)(64 + head) * 98304;
    for (int c = 0; c < 16; c++) {
      mbar_expect(BAR + c * 8, 12288);
      bulk_g2s(KS + c * 6144, kg + c * 6144, 6144, BAR + c * 8);
      bulk_g2s(VS + c * 6144, vg + c * 6144, 6144, BAR + c * 8);
    }
  }
  const int g = lane >> 2, cq = lane & 3;
  float kmax2 = g_kmax[head * 16 + (lane & 15)];
#pragma unroll
  for (int o = 8; o; o >>= 1) kmax2 = fmaxf(kmax2, __shfl_xor_sync(~0u, kmax2, o));

#pragma unroll 1
  for (int tile = 0; tile < 2; tile++) {
    const int row0 = qb * 512 + wg * 128 + tile * 64 + (warp & 3) * 16 + g;
    uint32_t q[6];
    {
      const uint8_t* qg = g_qkv + (size_t)head * 98304 + (row0 >> 3) * 384 + (row0 & 7) * 16 + cq * 4;
      q[0] = *(const uint32_t*)(qg);       q[1] = *(const uint32_t*)(qg + 384);
      q[2] = *(const uint32_t*)(qg + 128); q[3] = *(const uint32_t*)(qg + 384 + 128);
      q[4] = *(const uint32_t*)(qg + 256); q[5] = *(const uint32_t*)(qg + 384 + 256);
    }
    float n0 = bf_lo(q[0]) * bf_lo(q[0]) + bf_hi(q[0]) * bf_hi(q[0]) + bf_lo(q[2]) * bf_lo(q[2]) + bf_hi(q[2]) * bf_hi(q[2]) +
               bf_lo(q[4]) * bf_lo(q[4]) + bf_hi(q[4]) * bf_hi(q[4]);
    float n1 = bf_lo(q[1]) * bf_lo(q[1]) + bf_hi(q[1]) * bf_hi(q[1]) + bf_lo(q[3]) * bf_lo(q[3]) + bf_hi(q[3]) * bf_hi(q[3]) +
               bf_lo(q[5]) * bf_lo(q[5]) + bf_hi(q[5]) * bf_hi(q[5]);
    n0 += __shfl_xor_sync(~0u, n0, 1); n0 += __shfl_xor_sync(~0u, n0, 2);
    n1 += __shfl_xor_sync(~0u, n1, 1); n1 += __shfl_xor_sync(~0u, n1, 2);
    const float b0 = sqrtf(n0 * kmax2) * 1.01f + 1.0f, b1 = sqrtf(n1 * kmax2) * 1.01f + 1.0f;
    int ok = (b0 <= 62.0f) && (b1 <= 62.0f);
    {
      uint32_t all;
      asm volatile("{.reg .pred p,q; setp.ne.b32 p,%1,0; barrier.red.and.pred q,%2,128,p; selp.u32 %0,1,0,q;}"
                   : "=r"(all) : "r"(ok), "r"(1 + wg) : "memory");
      ok = all;
    }
    float o[12];
#pragma unroll
    for (int i = 0; i < 12; i++) o[i] = 0.f;

    if (ok) {
      if (cq == 1) { q[4] = pack_bf16(-b0, 1.0f); q[5] = pack_bf16(-b1, 1.0f); }
      float sa[32], sbb[32];
      uint32_t pa[16], pb[16];
      mbar_wait(BAR, 0);
      WG_FENCE();
      QK_MMA(sa, KS);
      WG_COMMIT();
      QK_MMA(sbb, KS + 3072);
      WG_COMMIT();
#pragma unroll 1
      for (int j = 0; j < 16; j++) {
        const int jn = (j < 15) ? j + 1 : j;
        WG_WAIT(1);
        softmax_fast(sa, pa);
        mbar_wait(BAR + jn * 8, 0);
        WG_FENCE();
        PV_MMA(pa, VS + j * 6144);
        QK_MMA(sa, KS + jn * 6144);
        WG_COMMIT();
        WG_WAIT(1);
        softmax_fast(sbb, pb);
        WG_FENCE();
        PV_MMA(pb, VS + j * 6144 + 3072);
        QK_MMA(sbb, KS + jn * 6144 + 3072);
        WG_COMMIT();
      }
      WG_WAIT(0);
    } else {
      float m0 = -INFINITY, m1 = -INFINITY;
#pragma unroll 1
      for (int j = 0; j < 32; j++) {
        float s[32];
        uint32_t p[16];
        mbar_wait(BAR + (j >> 1) * 8, 0);
        WG_FENCE();
        QK_MMA(s, KS + j * 3072);
        WG_COMMIT();
        WG_WAIT(0);
        float x0 = m0, x1 = m1;
#pragma unroll
        for (int i = 0; i < 8; i++) {
          x0 = fmaxf(x0, fmaxf(s[4 * i], s[4 * i + 1]));
          x1 = fmaxf(x1, fmaxf(s[4 * i + 2], s[4 * i + 3]));
        }
        x0 = fmaxf(x0, __shfl_xor_sync(~0u, x0, 1)); x0 = fmaxf(x0, __shfl_xor_sync(~0u, x0, 2));
        x1 = fmaxf(x1, __shfl_xor_sync(~0u, x1, 1)); x1 = fmaxf(x1, __shfl_xor_sync(~0u, x1, 2));
        const float c0 = ex2f(m0 - x0), c1 = ex2f(m1 - x1);
        m0 = x0; m1 = x1;
#pragma unroll
        for (int i = 0; i < 3; i++) { o[4 * i] *= c0; o[4 * i + 1] *= c0; o[4 * i + 2] *= c1; o[4 * i + 3] *= c1; }
#pragma unroll
        for (int i = 0; i < 8; i++) {
          p[2 * i] = pack_bf16(ex2f(s[4 * i] - x0), ex2f(s[4 * i + 1] - x0));
          p[2 * i + 1] = pack_bf16(ex2f(s[4 * i + 2] - x1), ex2f(s[4 * i + 3] - x1));
        }
        WG_FENCE();
        PV_MMA(p, VS + j * 3072);
        WG_COMMIT();
        WG_WAIT(0);
      }
    }
    const float l0 = __shfl_sync(~0u, o[8], (lane & ~3) | 1), l1 = __shfl_sync(~0u, o[10], (lane & ~3) | 1);
    const float i0 = 1.0f / l0, i1 = 1.0f / l1;
    uint32_t* og = (uint32_t*)(g_o + (size_t)row0 * DM + head * 18 + cq * 2);
    og[0] = pack_bf16(o[0] * i0, o[1] * i0);
    og[4] = pack_bf16(o[4] * i0, o[5] * i0);
    og[8 * DM / 2] = pack_bf16(o[2] * i1, o[3] * i1);
    og[8 * DM / 2 + 4] = pack_bf16(o[6] * i1, o[7] * i1);
    if (cq == 0) {
      og[8] = pack_bf16(o[8] * i0, o[9] * i0);
      og[8 * DM / 2 + 8] = pack_bf16(o[10] * i1, o[11] * i1);
    }
  }
}

#define K3_NSTG 4
#define K3_SMEM (9 * 16384 + K3_NSTG * 16384 + 1024 + 256)
__global__ void __launch_bounds__(288, 1) k3_kernel(const __grid_constant__ CUtensorMap mo, const __grid_constant__ CUtensorMap mw,
                                                    const __nv_bfloat16* __restrict__ x) {
  extern __shared__ uint8_t smem_raw[];
  const uint32_t sb = (s2u(smem_raw) + 1023) & ~1023u;
  const uint32_t A = sb, RING = sb + 9 * 16384, BAR = RING + K3_NSTG * 16384;
  const uint32_t full = BAR, empty = BAR + 64, afull = BAR + 128;
  const int tid = threadIdx.x, lane = tid & 31, warp = tid >> 5;
  const int mb = blockIdx.x >> 3, nb = blockIdx.x & 7;
  if (tid == 0) {
    for (int i = 0; i < K3_NSTG; i++) { mbar_init(full + i * 8, 1); mbar_init(empty + i * 8, 8); }
    for (int i = 0; i < 9; i++) mbar_init(afull + i * 8, 1);
    fence_bar_init();
  }
  __syncthreads();
  pdl_launch();
  if (warp == 8) {
    if (lane == 0) {
      for (int s = 0; s < K3_NSTG; s++) {
        mbar_expect(full + s * 8, 16384);
        tma2d(RING + s * 16384, &mw, nb * 72, s * 64, full + s * 8);
        tma2d(RING + s * 16384 + 8192, &mw, nb * 72 + 64, s * 64, full + s * 8);
      }
      pdl_wait();
      for (int c = 0; c < 9; c++) { mbar_expect(afull + c * 8, 16384); tma2d(A + c * 16384, &mo, c * 64, mb * 128, afull + c * 8); }
      for (int s = K3_NSTG; s < 9; s++) {
        const int st = s % K3_NSTG;
        mbar_wait(empty + st * 8, ((s / K3_NSTG) & 1) ^ 1);
        mbar_expect(full + st * 8, 16384);
        tma2d(RING + st * 16384, &mw, nb * 72, s * 64, full + st * 8);
        tma2d(RING + st * 16384 + 8192, &mw, nb * 72 + 64, s * 64, full + st * 8);
      }
    }
  } else {
    const int g = lane >> 2, cq = lane & 3;
    const int row = mb * 128 + warp * 16 + g, col = nb * 72 + cq * 2;
    uint32_t xv[18];
#pragma unroll
    for (int i = 0; i < 9; i++) {
      xv[2 * i] = __ldg((const uint32_t*)(x + (size_t)row * DM + col + 8 * i));
      xv[2 * i + 1] = __ldg((const uint32_t*)(x + (size_t)(row + 8) * DM + col + 8 * i));
    }
    pdl_wait();
    float2 ga[9];
#pragma unroll
    for (int i = 0; i < 9; i++) ga[i] = *(const float2*)(g_ga + col + 8 * i);
    float acc[36];
    const uint32_t abase = A + (warp >> 2) * 8192;
#pragma unroll
    for (int s = 0; s < 9; s++) {
      const int st = s % K3_NSTG;
      mbar_wait(afull + s * 8, 0);
      mbar_wait(full + st * 8, (s / K3_NSTG) & 1);
      WG_FENCE();
#pragma unroll
      for (int k = 0; k < 4; k++)
        wg_ss_n72_t1(acc, mkdesc(abase + s * 16384 + k * 32, 16, 1024, 1), mkdesc(RING + st * 16384 + k * 2048, 8192, 1024, 1), (s | k) != 0);
      WG_COMMIT();
      if (s > 0) { WG_WAIT(1); if (lane == 0) mbar_arrive(empty + ((s - 1) % K3_NSTG) * 8); }
    }
    WG_WAIT(0);
    float s0 = 0, s1 = 0;
#pragma unroll
    for (int i = 0; i < 9; i++) {
      acc[4 * i] = rbf(bf_lo(xv[2 * i]) + rbf(ga[i].x * rbf(acc[4 * i])));
      acc[4 * i + 1] = rbf(bf_hi(xv[2 * i]) + rbf(ga[i].y * rbf(acc[4 * i + 1])));
      acc[4 * i + 2] = rbf(bf_lo(xv[2 * i + 1]) + rbf(ga[i].x * rbf(acc[4 * i + 2])));
      acc[4 * i + 3] = rbf(bf_hi(xv[2 * i + 1]) + rbf(ga[i].y * rbf(acc[4 * i + 3])));
      *(uint32_t*)(g_x1 + (size_t)row * DM + col + 8 * i) = pack_bf16(acc[4 * i], acc[4 * i + 1]);
      *(uint32_t*)(g_x1 + (size_t)(row + 8) * DM + col + 8 * i) = pack_bf16(acc[4 * i + 2], acc[4 * i + 3]);
      s0 += acc[4 * i] + acc[4 * i + 1];
      s1 += acc[4 * i + 2] + acc[4 * i + 3];
    }
    s0 += __shfl_xor_sync(~0u, s0, 1); s0 += __shfl_xor_sync(~0u, s0, 2);
    s1 += __shfl_xor_sync(~0u, s1, 1); s1 += __shfl_xor_sync(~0u, s1, 2);
    const float m0 = s0 * (1.0f / 72), m1 = s1 * (1.0f / 72);
    float q0 = 0, q1 = 0;
#pragma unroll
    for (int i = 0; i < 9; i++) {
      q0 += (acc[4 * i] - m0) * (acc[4 * i] - m0) + (acc[4 * i + 1] - m0) * (acc[4 * i + 1] - m0);
      q1 += (acc[4 * i + 2] - m1) * (acc[4 * i + 2] - m1) + (acc[4 * i + 3] - m1) * (acc[4 * i + 3] - m1);
    }
    q0 += __shfl_xor_sync(~0u, q0, 1); q0 += __shfl_xor_sync(~0u, q0, 2);
    q1 += __shfl_xor_sync(~0u, q1, 1); q1 += __shfl_xor_sync(~0u, q1, 2);
    if (cq == 0) {
      g_stat2[row * 8 + nb] = make_float2(m0, q0);
      g_stat2[(row + 8) * 8 + nb] = make_float2(m1, q1);
    }
  }
}

__device__ __forceinline__ uint4 ln2_consts(int row, int cq) {
  const float4 p = *(const float4*)(g_stat2 + row * 8 + cq * 2);
  float s = p.x + p.z;
  s += __shfl_xor_sync(~0u, s, 1); s += __shfl_xor_sync(~0u, s, 2);
  const float mean = s * 0.125f;
  float q = p.y + p.w + 72.0f * ((p.x - mean) * (p.x - mean) + (p.z - mean) * (p.z - mean));
  q += __shfl_xor_sync(~0u, q, 1); q += __shfl_xor_sync(~0u, q, 2);
  return ln_consts(mean, q * (1.0f / DM));
}
__device__ __forceinline__ uint32_t glu_pair(float g0, float g1, float u0, float u1) {
  const float s0 = fmaf(tanhf_fast(0.5f * g0), 0.5f, 0.5f), s1 = fmaf(tanhf_fast(0.5f * g1), 0.5f, 0.5f);
  return pack_bf16(s0 * u0, s1 * u1);
}
template <int NG>
__device__ __forceinline__ void stage_part(const float* acc, uint32_t stg, int wrow, int lane) {
  const int r = wrow + (lane & 7) + ((lane >> 3) & 1) * 8;
#pragma unroll
  for (int i = 0; i < NG; i += 2) {
    const int ch = i + (lane >> 4);
    stsm4(stg + r * 256 + ((ch ^ (r & 7)) << 4), pack_bf16(acc[4 * i], acc[4 * i + 1]), pack_bf16(acc[4 * i + 2], acc[4 * i + 3]),
          pack_bf16(acc[4 * i + 4], acc[4 * i + 5]), pack_bf16(acc[4 * i + 6], acc[4 * i + 7]));
  }
}

__global__ void __launch_bounds__(384, 1) k4_kernel(const __grid_constant__ CUtensorMap mx, const __grid_constant__ CUtensorMap mg,
                                                    const __grid_constant__ CUtensorMap mu, const __grid_constant__ CUtensorMap md,
                                                    __nv_bfloat16* __restrict__ out) {
  extern __shared__ uint8_t smem_raw[];
  const uint32_t sb = (s2u(smem_raw) + 1023) & ~1023u;
  const uint32_t R = sb, RING = sb + R_BYTES, BAR = RING + NSTG * STG_BYTES;
  const uint32_t full = BAR, empty = BAR + 64, xfull = BAR + 128;
  const int tid = threadIdx.x, lane = tid & 31, warp = tid >> 5;
  const int mb = blockIdx.x >> 3, fb = blockIdx.x & 7;
  if (tid == 0) {
    for (int i = 0; i < NSTG; i++) { mbar_init(full + i * 8, 1); mbar_init(empty + i * 8, 8); }
    for (int i = 0; i < 8; i++) mbar_init(xfull + i * 8, 1);
    fence_bar_init();
  }
  __syncthreads();
  if (warp >= 8) {
    REG_DEC(40);
    if (warp == 8) {
      if (lane == 0) {
        int st = 1; uint32_t ph = 0;
        for (int it = 0; it < 126; it++) {
          if (it == NSTG - 1) {
            pdl_wait();
            for (int c = 0; c < 8; c++) { mbar_expect(xfull + c * 8, 16384); tma2d(R + c * 16384, &mx, c * 64, mb * 128, xfull + c * 8); }
            mbar_expect(full, 16384);
            tma2d(RING, &mx, 512, mb * 128, full);
          }
          const int t = it / 9, s = it - t * 9;
          const uint32_t dst = RING + st * STG_BYTES, fb_ = full + st * 8;
          mbar_wait(empty + st * 8, ph ^ 1);
          if (t < 9) {
            mbar_expect(fb_, 16384);
            tma2d(dst, &mg, fb * 576 + t * 64, s * 64, fb_);
            tma2d(dst + 8192, &mu, fb * 576 + t * 64, s * 64, fb_);
          } else {
            mbar_expect(fb_, t < 13 ? 16384 : 8192);
            tma2d(dst, &md, (t - 9) * 128, fb * 576 + s * 64, fb_);
            if (t < 13) tma2d(dst + 8192, &md, (t - 9) * 128 + 64, fb * 576 + s * 64, fb_);
          }
          if (++st == NSTG) { st = 0; ph ^= 1; }
        }
      }
    } else {
      const int ht = tid - 288;
      pdl_wait();
#pragma unroll 1
      for (int p = 0; p < 5; p++) {
        if (lane == 0) {
          unsigned int v; int n = 0;
          do {
            asm volatile("ld.acquire.gpu.global.u32 %0,[%1];" : "=r"(v) : "l"(g_cnt + mb * 5 + p) : "memory");
            if (v >= 16) break;
            __nanosleep(100);
          } while (++n < 20000000);
          if (v < 16) __trap();
        }
        __syncwarp();
        const int nch = p < 4 ? 16 : 8;
#pragma unroll 1
        for (int i = ht; i < 16 * nch; i += 96) {
          const int rl = fb * 16 + i / nch, ch = i % nch;
          const uint8_t* src = g_part + ((size_t)(mb * 5 + p) * 2 + (rl >> 6)) * 16384 + (rl & 63) * 256 + ((ch ^ (rl & 7)) << 4);
          float acc[8] = {0, 0, 0, 0, 0, 0, 0, 0};
#pragma unroll
          for (int h = 0; h < 2; h++) {
            uint4 v[4];
#pragma unroll
            for (int f = 0; f < 4; f++) v[f] = __ldcg((const uint4*)(src + (size_t)(h * 4 + f) * (16 * 5 * 2 * 16384)));
#pragma unroll
            for (int f = 0; f < 4; f++) {
              acc[0] += bf_lo(v[f].x); acc[1] += bf_hi(v[f].x); acc[2] += bf_lo(v[f].y); acc[3] += bf_hi(v[f].y);
              acc[4] += bf_lo(v[f].z); acc[5] += bf_hi(v[f].z); acc[6] += bf_lo(v[f].w); acc[7] += bf_hi(v[f].w);
            }
          }
          const int col = p * 128 + ch * 8;
          const size_t off = (size_t)(mb * 128 + rl) * DM + col;
          const uint4 xv = *(const uint4*)(g_x1 + off);
          const float4 g0 = *(const float4*)(g_gb + col), g1 = *(const float4*)(g_gb + col + 4);
          uint4 r;
          r.x = pack_bf16(bf_lo(xv.x) + rbf(g0.x * rbf(acc[0])), bf_hi(xv.x) + rbf(g0.y * rbf(acc[1])));
          r.y = pack_bf16(bf_lo(xv.y) + rbf(g0.z * rbf(acc[2])), bf_hi(xv.y) + rbf(g0.w * rbf(acc[3])));
          r.z = pack_bf16(bf_lo(xv.z) + rbf(g1.x * rbf(acc[4])), bf_hi(xv.z) + rbf(g1.y * rbf(acc[5])));
          r.w = pack_bf16(bf_lo(xv.w) + rbf(g1.z * rbf(acc[6])), bf_hi(xv.w) + rbf(g1.w * rbf(acc[7])));
          *(uint4*)(out + off) = r;
        }
      }
    }
  } else {
    REG_INC(232);
    uint32_t a[36][4];
    const int rowl = warp * 16, wg = warp >> 2;
    pdl_wait();
    {
      const int g = lane >> 2, cq = lane & 3;
      const uint4 s0 = ln2_consts(mb * 128 + rowl + g, cq), s1 = ln2_consts(mb * 128 + rowl + g + 8, cq);
#pragma unroll
      for (int c = 0; c < 9; c++) {
        if (c < 8) { mbar_wait(xfull + c * 8, 0); load_a_chunk(&a[c * 4], R + c * 16384, rowl, lane); }
        else { mbar_wait(full, 0); load_a_chunk(&a[32], RING, rowl, lane); __syncwarp(); if (lane == 0) mbar_arrive(empty); }
#pragma unroll
        for (int k = c * 4; k < c * 4 + 4; k++) {
          const uint4 t = g_tab2[k * 4 + cq];
          a[k][0] = ln_apply(a[k][0], s0, t.x, t.y);
          a[k][1] = ln_apply(a[k][1], s1, t.x, t.y);
          a[k][2] = ln_apply(a[k][2], s0, t.z, t.w);
          a[k][3] = ln_apply(a[k][3], s1, t.z, t.w);
        }
      }
    }
    bar_sync(4, 256);
    Ring ring{RING, full, empty, 1, 0};
    float acc[64];
    const uint32_t hsp = R + tid * 16;
#pragma unroll 1
    for (int t = 0; t < 8; t++) {
      MMA_TILE(wg_rs_n128_t1, acc, a, ring, lane);
#pragma unroll
      for (int j = 0; j < 4; j++) {
        uint32_t h[4];
#pragma unroll
        for (int e = 0; e < 4; e++) h[e] = glu_pair(acc[8 * j + 2 * e], acc[8 * j + 2 * e + 1], acc[32 + 8 * j + 2 * e], acc[32 + 8 * j + 2 * e + 1]);
        asm volatile("st.shared.v4.b32 [%0],{%1,%2,%3,%4};" ::"r"(hsp + t * 16384 + j * 4096), "r"(h[0]), "r"(h[1]), "r"(h[2]), "r"(h[3]) : "memory");
      }
    }
    MMA_TILE(wg_rs_n128_t1, acc, a, ring, lane);
#pragma unroll
    for (int j = 0; j < 4; j++)
#pragma unroll
      for (int e = 0; e < 4; e++)
        a[32 + j][e] = glu_pair(acc[8 * j + 2 * e], acc[8 * j + 2 * e + 1], acc[32 + 8 * j + 2 * e], acc[32 + 8 * j + 2 * e + 1]);
#pragma unroll
    for (int k = 0; k < 32; k++)
      asm volatile("ld.shared.v4.b32 {%0,%1,%2,%3},[%4];" : "=r"(a[k][0]), "=r"(a[k][1]), "=r"(a[k][2]), "=r"(a[k][3]) : "r"(hsp + k * 4096) : "memory");
    bar_sync(4, 256);
#pragma unroll 1
    for (int p = 0; p < 5; p++) {
      const uint32_t stg = R + ((p & 3) * 2 + wg) * 16384;
      if (p < 4) {
        MMA_TILE(wg_rs_n128_t1, acc, a, ring, lane);
        stage_part<16>(acc, stg, (warp & 3) * 16, lane);
      } else {
        MMA_TILE(wg_rs_n64_t1, acc, a, ring, lane);
        bar_sync(5 + wg, 128);
        stage_part<8>(acc, stg, (warp & 3) * 16, lane);
      }
      fence_async_smem();
      bar_sync(5 + wg, 128);
      if ((tid & 127) == 0) {
        bulk_s2g(g_part + ((size_t)((fb * 16 + mb) * 5 + p) * 2 + wg) * 16384, stg, 16384);
        bulk_commit();
        bulk_wait0();
        asm volatile("fence.proxy.async;" ::: "memory");
        asm volatile("red.release.gpu.global.add.u32 [%0],1;" ::"l"(g_cnt + mb * 5 + p) : "memory");
      }
    }
  }
}

typedef CUresult (*EncodeFn)(CUtensorMap*, CUtensorMapDataType, cuuint32_t, void*, const cuuint64_t*, const cuuint64_t*,
                             const cuuint32_t*, const cuuint32_t*, CUtensorMapInterleave, CUtensorMapSwizzle,
                             CUtensorMapL2promotion, CUtensorMapFloatOOBfill);
static void make_map(EncodeFn fn, CUtensorMap* m, const void* p, int rows, int cols, int box_rows) {
  cuuint64_t dims[2] = {(cuuint64_t)cols, (cuuint64_t)rows};
  cuuint64_t strides[1] = {(cuuint64_t)cols * 2};
  cuuint32_t box[2] = {64, (cuuint32_t)box_rows};
  cuuint32_t es[2] = {1, 1};
  fn(m, CU_TENSOR_MAP_DATA_TYPE_BFLOAT16, 2, (void*)p, dims, strides, box, es, CU_TENSOR_MAP_INTERLEAVE_NONE,
     CU_TENSOR_MAP_SWIZZLE_128B, CU_TENSOR_MAP_L2_PROMOTION_L2_256B, CU_TENSOR_MAP_FLOAT_OOB_FILL_NONE);
}
template <typename... KA, typename... A>
static void launch(void (*k)(KA...), int grid, int block, int smem, bool pdl, A... args) {
  cudaLaunchConfig_t cfg = {};
  cfg.gridDim = dim3(grid); cfg.blockDim = dim3(block); cfg.dynamicSmemBytes = smem; cfg.stream = cudaStreamPerThread;
  cudaLaunchAttribute at;
  at.id = cudaLaunchAttributeProgrammaticStreamSerialization;
  at.val.programmaticStreamSerializationAllowed = 1;
  cfg.attrs = &at; cfg.numAttrs = pdl ? 1 : 0;
  cudaLaunchKernelEx(&cfg, k, KA(args)...);
}

extern "C" void kernel_launch(void* const* d_in, const int* in_sizes, int n_in, void* d_out, int out_size) {
  const __nv_bfloat16* x = (const __nv_bfloat16*)d_in[0];
  void* fnp = nullptr;
  cudaDriverEntryPointQueryResult qr;
  cudaGetDriverEntryPoint("cuTensorMapEncodeTiled", &fnp, cudaEnableDefault, &qr);
  EncodeFn fn = (EncodeFn)fnp;
  void *po, *px1;
  cudaGetSymbolAddress(&po, g_o);
  cudaGetSymbolAddress(&px1, g_x1);
  CUtensorMap mx, mqkv, mo, mwo, mx1, mg, mu, md;
  make_map(fn, &mx, x, SEQ, DM, 128);
  make_map(fn, &mqkv, d_in[1], DM, 3 * DM, 64);
  make_map(fn, &mo, po, SEQ, DM, 128);
  make_map(fn, &mwo, d_in[2], DM, DM, 64);
  make_map(fn, &mx1, px1, SEQ, DM, 128);
  make_map(fn, &mg, d_in[4], DM, FF, 64);
  make_map(fn, &mu, d_in[5], DM, FF, 64);
  make_map(fn, &md, d_in[6], FF, DM, 64);
  cudaFuncSetAttribute(k1_kernel, cudaFuncAttributeMaxDynamicSharedMemorySize, GEMM_SMEM);
  cudaFuncSetAttribute(k2_kernel, cudaFuncAttributeMaxDynamicSharedMemorySize, ATT_SMEM);
  cudaFuncSetAttribute(k3_kernel, cudaFuncAttributeMaxDynamicSharedMemorySize, K3_SMEM);
  cudaFuncSetAttribute(k4_kernel, cudaFuncAttributeMaxDynamicSharedMemorySize, GEMM_SMEM);
  launch(k0_kernel, 108 + 128, 256, 0, false, x, (const __nv_bfloat16*)d_in[7], (const __nv_bfloat16*)d_in[8]);
  launch(k1_kernel, 128, 384, GEMM_SMEM, true, mx, mqkv);
  launch(k2_kernel, 128, 512, ATT_SMEM, true);
  launch(k3_kernel, 128, 288, K3_SMEM, true, mo, mwo, x);
  launch(k4_kernel, 128, 384, GEMM_SMEM, true, mx1, mg, mu, md, (__nv_bfloat16*)d_out);
}
```

```cpp
#include <cuda_runtime.h>
#include <cuda_bf16.h>
#include <cuda.h>
#include <stdint.h>

#define SEQ 2048
#define DM 576
#define NH 32
#define FF 4608

__device__ uint4 g_tab1[36 * 4];
__device__ uint4 g_tab2[36 * 4];
__device__ float g_ga[DM];
__device__ float g_gb[DM];
__device__ uint4 g_stat1[SEQ];
__device__ float2 g_stat2[SEQ * 8];
__device__ __align__(1024) uint8_t g_qkv[96 * 98304];
__device__ float g_kmax[NH * 16];
__device__ __align__(1024) __nv_bfloat16 g_o[SEQ * DM];
__device__ __align__(1024) __nv_bfloat16 g_x1[SEQ * DM];
__device__ __align__(1024) uint8_t g_part[8 * 16 * 5 * 2 * 16384];
__device__ unsigned int g_cnt[16 * 5];

__device__ __forceinline__ uint32_t s2u(const void* p) { return (uint32_t)__cvta_generic_to_shared(p); }
__device__ __forceinline__ void mbar_init(uint32_t b, int c) { asm volatile("mbarrier.init.shared::cta.b64 [%0],%1;" ::"r"(b), "r"(c)); }
__device__ __forceinline__ void mbar_expect(uint32_t b, uint32_t n) { asm volatile("mbarrier.arrive.expect_tx.shared::cta.b64 _,[%0],%1;" ::"r"(b), "r"(n) : "memory"); }
__device__ __forceinline__ void mbar_arrive(uint32_t b) { asm volatile("mbarrier.arrive.shared::cta.b64 _,[%0];" ::"r"(b) : "memory"); }
__device__ __forceinline__ void mbar_wait(uint32_t b, uint32_t ph) {
  asm volatile(
      "{.reg .pred p; .reg .u32 n; mov.u32 n,0;\n"
      "W: mbarrier.try_wait.parity.shared::cta.b64 p,[%0],%1;\n"
      "@p bra D;\n"
      "add.u32 n,n,1; setp.lt.u32 p,n,4000000; @p bra W;\n"
      "trap;\n"
      "D: }" ::"r"(b), "r"(ph) : "memory");
}
__device__ __forceinline__ void tma2d(uint32_t dst, const CUtensorMap* m, int c0, int c1, uint32_t bar) {
  asm volatile("cp.async.bulk.tensor.2d.shared::cluster.global.mbarrier::complete_tx::bytes [%0],[%1,{%3,%4}],[%2];"
               ::"r"(dst), "l"(m), "r"(bar), "r"(c0), "r"(c1) : "memory");
}
__device__ __forceinline__ void bulk_g2s(uint32_t dst, const void* src, uint32_t bytes, uint32_t bar) {
  asm volatile("cp.async.bulk.shared::cluster.global.mbarrier::complete_tx::bytes [%0],[%1],%2,[%3];"
               ::"r"(dst), "l"(src), "r"(bytes), "r"(bar) : "memory");
}
__device__ __forceinline__ void bulk_s2g(void* dst, uint32_t src, uint32_t bytes) {
  asm volatile("cp.async.bulk.global.shared::cta.bulk_group [%0],[%1],%2;" ::"l"(dst), "r"(src), "r"(bytes) : "memory");
}
__device__ __forceinline__ void bulk_commit() { asm volatile("cp.async.bulk.commit_group;" ::: "memory"); }
__device__ __forceinline__ void bulk_wait0() { asm volatile("cp.async.bulk.wait_group 0;" ::: "memory"); }
__device__ __forceinline__ void prefetch_map(const CUtensorMap* m) { asm volatile("prefetch.tensormap [%0];" ::"l"(m) : "memory"); }
__device__ __forceinline__ void fence_async_smem() { asm volatile("fence.proxy.async.shared::cta;" ::: "memory"); }
__device__ __forceinline__ void fence_bar_init() { asm volatile("fence.mbarrier_init.release.cluster;" ::: "memory"); }
__device__ __forceinline__ void pdl_wait() { asm volatile("griddepcontrol.wait;" ::: "memory"); }
__device__ __forceinline__ void pdl_launch() { asm volatile("griddepcontrol.launch_dependents;" ::: "memory"); }
__device__ __forceinline__ void bar_sync(int id, int n) { asm volatile("bar.sync %0,%1;" ::"r"(id), "r"(n) : "memory"); }
__device__ __forceinline__ void bar_arrive(int id, int n) { asm volatile("bar.arrive %0,%1;" ::"r"(id), "r"(n) : "memory"); }
#define WG_FENCE() asm volatile("wgmma.fence.sync.aligned;" ::: "memory")
#define WG_COMMIT() asm volatile("wgmma.commit_group.sync.aligned;" ::: "memory")
#define WG_WAIT(n) asm volatile("wgmma.wait_group.sync.aligned " #n ";" ::: "memory")
#define REG_INC(n) asm volatile("setmaxnreg.inc.sync.aligned.u32 " #n ";")
#define REG_DEC(n) asm volatile("setmaxnreg.dec.sync.aligned.u32 " #n ";")
__device__ __forceinline__ uint64_t mkdesc(uint32_t addr, uint32_t lbo, uint32_t sbo, int sw) {
  return (uint64_t)((addr & 0x3FFFF) >> 4) | ((uint64_t)(lbo >> 4) << 16) | ((uint64_t)(sbo >> 4) << 32) | ((uint64_t)sw << 62);
}
__device__ __forceinline__ void ldsm4(uint32_t* r, uint32_t addr) {
  asm volatile("ldmatrix.sync.aligned.m8n8.x4.shared.b16 {%0,%1,%2,%3},[%4];" : "=r"(r[0]), "=r"(r[1]), "=r"(r[2]), "=r"(r[3]) : "r"(addr) : "memory");
}
__device__ __forceinline__ void stsm4(uint32_t addr, uint32_t r0, uint32_t r1, uint32_t r2, uint32_t r3) {
  asm volatile("stmatrix.sync.aligned.m8n8.x4.shared.b16 [%0],{%1,%2,%3,%4};" ::"r"(addr), "r"(r0), "r"(r1), "r"(r2), "r"(r3) : "memory");
}
__device__ __forceinline__ uint32_t pack_bf16(float lo, float hi) {
  uint32_t r;
  asm("cvt.rn.bf16x2.f32 %0,%1,%2;" : "=r"(r) : "f"(hi), "f"(lo));
  return r;
}
__device__ __forceinline__ float bf_lo(uint32_t v) { return __uint_as_float(v << 16); }
__device__ __forceinline__ float bf_hi(uint32_t v) { return __uint_as_float(v & 0xFFFF0000u); }
__device__ __forceinline__ float rbf(float x) { return __bfloat162float(__float2bfloat16_rn(x)); }
__device__ __forceinline__ uint32_t hfma2(uint32_t a, uint32_t b, uint32_t c) {
  uint32_t r;
  asm("fma.rn.bf16x2 %0,%1,%2,%3;" : "=r"(r) : "r"(a), "r"(b), "r"(c));
  return r;
}
__device__ __forceinline__ uint32_t hadd2(uint32_t a, uint32_t b) {
  uint32_t r;
  asm("add.rn.bf16x2 %0,%1,%2;" : "=r"(r) : "r"(a), "r"(b));
  return r;
}
__device__ __forceinline__ uint32_t hmul2(uint32_t a, uint32_t b) {
  uint32_t r;
  asm("mul.rn.bf16x2 %0,%1,%2;" : "=r"(r) : "r"(a), "r"(b));
  return r;
}
__device__ __forceinline__ uint32_t hneg2(uint32_t a) {
  uint32_t r;
  asm("neg.bf16x2 %0,%1;" : "=r"(r) : "r"(a));
  return r;
}
__device__ __forceinline__ float ex2f(float x) {
  float r;
  asm("ex2.approx.ftz.f32 %0,%1;" : "=f"(r) : "f"(x));
  return r;
}
__device__ __forceinline__ float tanhf_fast(float x) {
  float r;
  asm("tanh.approx.f32 %0,%1;" : "=f"(r) : "f"(x));
  return r;
}
__device__ __forceinline__ uint4 ln_consts(float mean, float var) {
  float m = rbf(mean), v = rbf(var);
  float s = rbf(sqrtf(rbf(v + 1e-5f)));
  float r = 1.0f / s;
  float rh = rbf(r), rl = r - rh;
  return make_uint4(pack_bf16(-m, -m), pack_bf16(rh, rh), pack_bf16(rl, rl), 0u);
}
__device__ __forceinline__ uint32_t ln_apply(uint32_t x, const uint4& st, uint32_t a, uint32_t s) {
  uint32_t d = hadd2(x, st.x);
  uint32_t n = hfma2(d, st.y, hmul2(d, st.z));
  return hfma2(n, a, s);
}

__device__ __forceinline__ void wg_rs_n128_t0(float* d, uint32_t a0, uint32_t a1, uint32_t a2, uint32_t a3, uint64_t db, int sc) {
  asm volatile("{.reg .pred p; setp.ne.b32 p,%69,0; wgmma.mma_async.sync.aligned.m64n128k16.f32.bf16.bf16 {%0,%1,%2,%3,%4,%5,%6,%7,%8,%9,%10,%11,%12,%13,%14,%15,%16,%17,%18,%19,%20,%21,%22,%23,%24,%25,%26,%27,%28,%29,%30,%31,%32,%33,%34,%35,%36,%37,%38,%39,%40,%41,%42,%43,%44,%45,%46,%47,%48,%49,%50,%51,%52,%53,%54,%55,%56,%57,%58,%59,%60,%61,%62,%63}, {%64,%65,%66,%67}, %68, p,1,1,0;}"
  : "+f"(d[0]),"+f"(d[1]),"+f"(d[2]),"+f"(d[3]),"+f"(d[4]),"+f"(d[5]),"+f"(d[6]),"+f"(d[7]),"+f"(d[8]),"+f"(d[9]),"+f"(d[10]),"+f"(d[11]),"+f"(d[12]),"+f"(d[13]),"+f"(d[14]),"+f"(d[15]),"+f"(d[16]),"+f"(d[17]),"+f"(d[18]),"+f"(d[19]),"+f"(d[20]),"+f"(d[21]),"+f"(d[22]),"+f"(d[23]),"+f"(d[24]),"+f"(d[25]),"+f"(d[26]),"+f"(d[27]),"+f"(d[28]),"+f"(d[29]),"+f"(d[30]),"+f"(d[31]),"+f"(d[32]),"+f"(d[33]),"+f"(d[34]),"+f"(d[35]),"+f"(d[36]),"+f"(d[37]),"+f"(d[38]),"+f"(d[39]),"+f"(d[40]),"+f"(d[41]),"+f"(d[42]),"+f"(d[43]),"+f"(d[44]),"+f"(d[45]),"+f"(d[46]),"+f"(d[47]),"+f"(d[48]),"+f"(d[49]),"+f"(d[50]),"+f"(d[51]),"+f"(d[52]),"+f"(d[53]),"+f"(d[54]),"+f"(d[55]),"+f"(d[56]),"+f"(d[57]),"+f"(d[58]),"+f"(d[59]),"+f"(d[60]),"+f"(d[61]),"+f"(d[62]),"+f"(d[63]) : "r"(a0),"r"(a1),"r"(a2),"r"(a3),"l"(db),"r"(sc));
}
__device__ __forceinline__ void wg_rs_n128_t1(float* d, uint32_t a0, uint32_t a1, uint32_t a2, uint32_t a3, uint64_t db, int sc) {
  asm volatile("{.reg .pred p; setp.ne.b32 p,%69,0; wgmma.mma_async.sync.aligned.m64n128k16.f32.bf16.bf16 {%0,%1,%2,%3,%4,%5,%6,%7,%8,%9,%10,%11,%12,%13,%14,%15,%16,%17,%18,%19,%20,%21,%22,%23,%24,%25,%26,%27,%28,%29,%30,%31,%32,%33,%34,%35,%36,%37,%38,%39,%40,%41,%42,%43,%44,%45,%46,%47,%48,%49,%50,%51,%52,%53,%54,%55,%56,%57,%58,%59,%60,%61,%62,%63}, {%64,%65,%66,%67}, %68, p,1,1,1;}"
  : "+f"(d[0]),"+f"(d[1]),"+f"(d[2]),"+f"(d[3]),"+f"(d[4]),"+f"(d[5]),"+f"(d[6]),"+f"(d[7]),"+f"(d[8]),"+f"(d[9]),"+f"(d[10]),"+f"(d[11]),"+f"(d[12]),"+f"(d[13]),"+f"(d[14]),"+f"(d[15]),"+f"(d[16]),"+f"(d[17]),"+f"(d[18]),"+f"(d[19]),"+f"(d[20]),"+f"(d[21]),"+f"(d[22]),"+f"(d[23]),"+f"(d[24]),"+f"(d[25]),"+f"(d[26]),"+f"(d[27]),"+f"(d[28]),"+f"(d[29]),"+f"(d[30]),"+f"(d[31]),"+f"(d[32]),"+f"(d[33]),"+f"(d[34]),"+f"(d[35]),"+f"(d[36]),"+f"(d[37]),"+f"(d[38]),"+f"(d[39]),"+f"(d[40]),"+f"(d[41]),"+f"(d[42]),"+f"(d[43]),"+f"(d[44]),"+f"(d[45]),"+f"(d[46]),"+f"(d[47]),"+f"(d[48]),"+f"(d[49]),"+f"(d[50]),"+f"(d[51]),"+f"(d[52]),"+f"(d[53]),"+f"(d[54]),"+f"(d[55]),"+f"(d[56]),"+f"(d[57]),"+f"(d[58]),"+f"(d[59]),"+f"(d[60]),"+f"(d[61]),"+f"(d[62]),"+f"(d[63]) : "r"(a0),"r"(a1),"r"(a2),"r"(a3),"l"(db),"r"(sc));
}
__device__ __forceinline__ void wg_rs_n24_t1(float* d, uint32_t a0, uint32_t a1, uint32_t a2, uint32_t a3, uint64_t db, int sc) {
  asm volatile("{.reg .pred p; setp.ne.b32 p,%17,0; wgmma.mma_async.sync.aligned.m64n24k16.f32.bf16.bf16 {%0,%1,%2,%3,%4,%5,%6,%7,%8,%9,%10,%11}, {%12,%13,%14,%15}, %16, p,1,1,1;}"
  : "+f"(d[0]),"+f"(d[1]),"+f"(d[2]),"+f"(d[3]),"+f"(d[4]),"+f"(d[5]),"+f"(d[6]),"+f"(d[7]),"+f"(d[8]),"+f"(d[9]),"+f"(d[10]),"+f"(d[11]) : "r"(a0),"r"(a1),"r"(a2),"r"(a3),"l"(db),"r"(sc));
}
__device__ __forceinline__ void wg_rs_n64_t0(float* d, uint32_t a0, uint32_t a1, uint32_t a2, uint32_t a3, uint64_t db, int sc) {
  asm volatile("{.reg .pred p; setp.ne.b32 p,%37,0; wgmma.mma_async.sync.aligned.m64n64k16.f32.bf16.bf16 {%0,%1,%2,%3,%4,%5,%6,%7,%8,%9,%10,%11,%12,%13,%14,%15,%16,%17,%18,%19,%20,%21,%22,%23,%24,%25,%26,%27,%28,%29,%30,%31}, {%32,%33,%34,%35}, %36, p,1,1,0;}"
  : "+f"(d[0]),"+f"(d[1]),"+f"(d[2]),"+f"(d[3]),"+f"(d[4]),"+f"(d[5]),"+f"(d[6]),"+f"(d[7]),"+f"(d[8]),"+f"(d[9]),"+f"(d[10]),"+f"(d[11]),"+f"(d[12]),"+f"(d[13]),"+f"(d[14]),"+f"(d[15]),"+f"(d[16]),"+f"(d[17]),"+f"(d[18]),"+f"(d[19]),"+f"(d[20]),"+f"(d[21]),"+f"(d[22]),"+f"(d[23]),"+f"(d[24]),"+f"(d[25]),"+f"(d[26]),"+f"(d[27]),"+f"(d[28]),"+f"(d[29]),"+f"(d[30]),"+f"(d[31]) : "r"(a0),"r"(a1),"r"(a2),"r"(a3),"l"(db),"r"(sc));
}
__device__ __forceinline__ void wg_rs_n64_t1(float* d, uint32_t a0, uint32_t a1, uint32_t a2, uint32_t a3, uint64_t db, int sc) {
  asm volatile("{.reg .pred p; setp.ne.b32 p,%37,0; wgmma.mma_async.sync.aligned.m64n64k16.f32.bf16.bf16 {%0,%1,%2,%3,%4,%5,%6,%7,%8,%9,%10,%11,%12,%13,%14,%15,%16,%17,%18,%19,%20,%21,%22,%23,%24,%25,%26,%27,%28,%29,%30,%31}, {%32,%33,%34,%35}, %36, p,1,1,1;}"
  : "+f"(d[0]),"+f"(d[1]),"+f"(d[2]),"+f"(d[3]),"+f"(d[4]),"+f"(d[5]),"+f"(d[6]),"+f"(d[7]),"+f"(d[8]),"+f"(d[9]),"+f"(d[10]),"+f"(d[11]),"+f"(d[12]),"+f"(d[13]),"+f"(d[14]),"+f"(d[15]),"+f"(d[16]),"+f"(d[17]),"+f"(d[18]),"+f"(d[19]),"+f"(d[20]),"+f"(d[21]),"+f"(d[22]),"+f"(d[23]),"+f"(d[24]),"+f"(d[25]),"+f"(d[26]),"+f"(d[27]),"+f"(d[28]),"+f"(d[29]),"+f"(d[30]),"+f"(d[31]) : "r"(a0),"r"(a1),"r"(a2),"r"(a3),"l"(db),"r"(sc));
}
__device__ __forceinline__ void wg_rs_n88_t1(float* d, uint32_t a0, uint32_t a1, uint32_t a2, uint32_t a3, uint64_t db, int sc) {
  asm volatile("{.reg .pred p; setp.ne.b32 p,%49,0; wgmma.mma_async.sync.aligned.m64n88k16.f32.bf16.bf16 {%0,%1,%2,%3,%4,%5,%6,%7,%8,%9,%10,%11,%12,%13,%14,%15,%16,%17,%18,%19,%20,%21,%22,%23,%24,%25,%26,%27,%28,%29,%30,%31,%32,%33,%34,%35,%36,%37,%38,%39,%40,%41,%42,%43}, {%44,%45,%46,%47}, %48, p,1,1,1;}"
  : "+f"(d[0]),"+f"(d[1]),"+f"(d[2]),"+f"(d[3]),"+f"(d[4]),"+f"(d[5]),"+f"(d[6]),"+f"(d[7]),"+f"(d[8]),"+f"(d[9]),"+f"(d[10]),"+f"(d[11]),"+f"(d[12]),"+f"(d[13]),"+f"(d[14]),"+f"(d[15]),"+f"(d[16]),"+f"(d[17]),"+f"(d[18]),"+f"(d[19]),"+f"(d[20]),"+f"(d[21]),"+f"(d[22]),"+f"(d[23]),"+f"(d[24]),"+f"(d[25]),"+f"(d[26]),"+f"(d[27]),"+f"(d[28]),"+f"(d[29]),"+f"(d[30]),"+f"(d[31]),"+f"(d[32]),"+f"(d[33]),"+f"(d[34]),"+f"(d[35]),"+f"(d[36]),"+f"(d[37]),"+f"(d[38]),"+f"(d[39]),"+f"(d[40]),"+f"(d[41]),"+f"(d[42]),"+f"(d[43]) : "r"(a0),"r"(a1),"r"(a2),"r"(a3),"l"(db),"r"(sc));
}
__device__ __forceinline__ void wg_ss_n72_t1(float* d, uint64_t da, uint64_t db, int sc) {
  asm volatile("{.reg .pred p; setp.ne.b32 p,%38,0; wgmma.mma_async.sync.aligned.m64n72k16.f32.bf16.bf16 {%0,%1,%2,%3,%4,%5,%6,%7,%8,%9,%10,%11,%12,%13,%14,%15,%16,%17,%18,%19,%20,%21,%22,%23,%24,%25,%26,%27,%28,%29,%30,%31,%32,%33,%34,%35}, %36, %37, p,1,1,0,1;}"
  : "+f"(d[0]),"+f"(d[1]),"+f"(d[2]),"+f"(d[3]),"+f"(d[4]),"+f"(d[5]),"+f"(d[6]),"+f"(d[7]),"+f"(d[8]),"+f"(d[9]),"+f"(d[10]),"+f"(d[11]),"+f"(d[12]),"+f"(d[13]),"+f"(d[14]),"+f"(d[15]),"+f"(d[16]),"+f"(d[17]),"+f"(d[18]),"+f"(d[19]),"+f"(d[20]),"+f"(d[21]),"+f"(d[22]),"+f"(d[23]),"+f"(d[24]),"+f"(d[25]),"+f"(d[26]),"+f"(d[27]),"+f"(d[28]),"+f"(d[29]),"+f"(d[30]),"+f"(d[31]),"+f"(d[32]),"+f"(d[33]),"+f"(d[34]),"+f"(d[35]) : "l"(da),"l"(db),"r"(sc));
}


#define POLY_MASK 0xB5u
#define QSCALE (0.23570226039551584f * 1.4426950408889634f)

__global__ void __launch_bounds__(256) k0_kernel(const __nv_bfloat16* __restrict__ x, const __nv_bfloat16* __restrict__ c,
                                                 const __nv_bfloat16* __restrict__ wmod) {
  pdl_launch();
  const int tid = threadIdx.x, lane = tid & 31, warp = tid >> 5;
  if (blockIdx.x < 108) {
    __shared__ float red[8][32];
    const int col0 = blockIdx.x * 32 + (tid & 3) * 8, r0 = tid >> 2;
    uint4 w[9];
#pragma unroll
    for (int i = 0; i < 9; i++) w[i] = __ldg((const uint4*)(wmod + (size_t)(r0 + 64 * i) * 3456 + col0));
    float acc[8] = {0, 0, 0, 0, 0, 0, 0, 0};
#pragma unroll
    for (int i = 0; i < 9; i++) {
      float cv = __bfloat162float(c[r0 + 64 * i]);
      float sv = rbf(cv / (1.0f + __expf(-cv)));
      acc[0] += sv * bf_lo(w[i].x); acc[1] += sv * bf_hi(w[i].x);
      acc[2] += sv * bf_lo(w[i].y); acc[3] += sv * bf_hi(w[i].y);
      acc[4] += sv * bf_lo(w[i].z); acc[5] += sv * bf_hi(w[i].z);
      acc[6] += sv * bf_lo(w[i].w); acc[7] += sv * bf_hi(w[i].w);
    }
#pragma unroll
    for (int j = 0; j < 8; j++) {
      acc[j] += __shfl_xor_sync(~0u, acc[j], 4);
      acc[j] += __shfl_xor_sync(~0u, acc[j], 8);
      acc[j] += __shfl_xor_sync(~0u, acc[j], 16);
    }
    if (lane < 4) {
#pragma unroll
      for (int j = 0; j < 8; j++) red[warp][lane * 8 + j] = acc[j];
    }
    __syncthreads();
    if (tid < 32) {
      float s = 0;
#pragma unroll
      for (int j = 0; j < 8; j++) s += red[j][tid];
      s = rbf(s);
      int n = blockIdx.x * 32 + tid, part = n / DM, col = n % DM;
      if (part == 2) g_ga[col] = s;
      else if (part == 5) g_gb[col] = s;
      else {
        __nv_bfloat16* tab = (__nv_bfloat16*)(part < 2 ? g_tab1 : g_tab2);
        bool shift = (part == 0 || part == 3);
        int kk = col >> 4, half = (col >> 3) & 1, cq = (col & 7) >> 1, e = col & 1;
        tab[((kk * 4 + cq) * 4 + half * 2 + (shift ? 1 : 0)) * 2 + e] = __float2bfloat16_rn(shift ? s : 1.0f + s);
      }
    }
    if (blockIdx.x == 0 && tid >= 64 && tid < 64 + 80) g_cnt[tid - 64] = 0;
  } else {
    const int row0 = (blockIdx.x - 108) * 16 + warp * 2;
    uint32_t v[2][9];
#pragma unroll
    for (int r = 0; r < 2; r++)
#pragma unroll
      for (int i = 0; i < 9; i++) v[r][i] = __ldg((const uint32_t*)(x + (size_t)(row0 + r) * DM) + lane + 32 * i);
#pragma unroll
    for (int r = 0; r < 2; r++) {
      float s = 0;
#pragma unroll
      for (int i = 0; i < 9; i++) s += bf_lo(v[r][i]) + bf_hi(v[r][i]);
#pragma unroll
      for (int o = 16; o; o >>= 1) s += __shfl_xor_sync(~0u, s, o);
      float mean = s * (1.0f / DM), q = 0;
#pragma unroll
      for (int i = 0; i < 9; i++) {
        float a = bf_lo(v[r][i]) - mean, b = bf_hi(v[r][i]) - mean;
        q += a * a + b * b;
      }
#pragma unroll
      for (int o = 16; o; o >>= 1) q += __shfl_xor_sync(~0u, q, o);
      if (lane == 0) g_stat1[row0 + r] = ln_consts(mean, q * (1.0f / DM));
    }
  }
}

#define NSTG 6
#define STG_BYTES 16384
#define R_BYTES (8 * 16384)
#define GEMM_SMEM (R_BYTES + NSTG * STG_BYTES + 1024 + 256)

struct Ring {
  uint32_t base, full, empty;
  int st;
  uint32_t ph;
  __device__ __forceinline__ void next() { if (++st == NSTG) { st = 0; ph ^= 1; } }
};

__device__ __forceinline__ void load_a_chunk(uint32_t (*a)[4], uint32_t chunk_base, int row_in_tile, int lane) {
  const int r = row_in_tile + (lane & 7) + ((lane >> 3) & 1) * 8;
  const uint32_t rb = chunk_base + r * 128;
#pragma unroll
  for (int k = 0; k < 4; k++) ldsm4(a[k], rb + (((k * 2 + (lane >> 4)) ^ (r & 7)) << 4));
}

#define MMA_TILE(FN, acc, a, ring, lane)                                        \
  {                                                                             \
    uint32_t prev_empty = 0;                                                    \
    _Pragma("unroll") for (int s = 0; s < 9; s++) {                             \
      mbar_wait(ring.full + ring.st * 8, ring.ph);                              \
      WG_FENCE();                                                               \
      uint32_t sa_ = ring.base + ring.st * STG_BYTES;                           \
      asm volatile("" : "+r"(sa_));                                             \
      uint64_t db = mkdesc(sa_, 8192, 1024, 1);                                 \
      _Pragma("unroll") for (int k = 0; k < 4; k++)                             \
          FN(acc, a[s * 4 + k][0], a[s * 4 + k][1], a[s * 4 + k][2], a[s * 4 + k][3], db + k * 128, (s | k) != 0); \
      WG_COMMIT();                                                              \
      if (s > 0) { WG_WAIT(1); if (lane == 0) mbar_arrive(prev_empty); }        \
      prev_empty = ring.empty + ring.st * 8;                                    \
      ring.next();                                                              \
    }                                                                           \
    WG_WAIT(0);                                                                 \
    if (lane == 0) mbar_arrive(prev_empty);                                     \
  }

template <int NG, int G0>
__device__ __forceinline__ void qkv_stage(const float* acc, uint32_t stg, int rowl, int cq, int col_base) {
  const float vs0 = ((POLY_MASK >> ((rowl >> 3) & 7)) & 1) ? -1.0f : 1.0f, vs1 = ((POLY_MASK >> (((rowl >> 3) + 1) & 7)) & 1) ? -1.0f : 1.0f;
#pragma unroll
  for (int i = 0; i < NG; i++) {
    const int cc = (G0 + i) * 8 + cq * 2;
    const int slot = (cc * 3641) >> 16, d = cc - slot * 18;
    const int gc = col_base + cc;
    const float sc0 = gc < DM ? QSCALE : (gc >= 2 * DM ? vs0 : 1.0f), sc1 = gc < DM ? QSCALE : (gc >= 2 * DM ? vs1 : 1.0f);
    const uint32_t ad = stg + slot * 6144 + (d >> 3) * 128 + (d & 7) * 2 + (rowl >> 3) * 384 + (rowl & 7) * 16;
    asm volatile("st.shared.b32 [%0],%1;" ::"r"(ad), "r"(pack_bf16(acc[4 * i] * sc0, acc[4 * i + 1] * sc0)) : "memory");
    asm volatile("st.shared.b32 [%0],%1;" ::"r"(ad + 384), "r"(pack_bf16(acc[4 * i + 2] * sc1, acc[4 * i + 3] * sc1)) : "memory");
  }
}

__global__ void __launch_bounds__(384, 1) k1_kernel(const __grid_constant__ CUtensorMap mx, const __grid_constant__ CUtensorMap mw) {
  extern __shared__ uint8_t smem_raw[];
  const uint32_t sb = (s2u(smem_raw) + 1023) & ~1023u;
  const uint32_t R = sb, RING = sb + R_BYTES, BAR = RING + NSTG * STG_BYTES;
  const uint32_t full = BAR, empty = BAR + 64, xfull = BAR + 128;
  const int tid = threadIdx.x, lane = tid & 31, warp = tid >> 5;
  const int mb = blockIdx.x >> 3, nb = blockIdx.x & 7;
  if (tid == 0) {
    for (int i = 0; i < NSTG; i++) { mbar_init(full + i * 8, 1); mbar_init(empty + i * 8, 8); }
    for (int i = 0; i < 8; i++) mbar_init(xfull + i * 8, 1);
    fence_bar_init();
  }
  __syncthreads();
  pdl_launch();
  if (warp >= 8) {
    REG_DEC(24);
    if (warp == 8) {
      if (lane == 0) {
        for (int c = 0; c < 8; c++) { mbar_expect(xfull + c * 8, 16384); tma2d(R + c * 16384, &mx, c * 64, mb * 128, xfull + c * 8); }
        mbar_expect(full, 16384);
        tma2d(RING, &mx, 512, mb * 128, full);
        int st = 1; uint32_t ph = 0;
        for (int it = 0; it < 18; it++) {
          const int t = it / 9, s = it - t * 9;
          mbar_wait(empty + st * 8, ph ^ 1);
          mbar_expect(full + st * 8, 16384);
          tma2d(RING + st * STG_BYTES, &mw, nb * 216 + t * 128, s * 64, full + st * 8);
          tma2d(RING + st * STG_BYTES + 8192, &mw, nb * 216 + t * 128 + 64, s * 64, full + st * 8);
          if (++st == NSTG) { st = 0; ph ^= 1; }
        }
      }
      pdl_wait();
    } else {
      const int ht = tid - 288;
      bar_sync(1, 352);
      for (int i = ht; i < 12 * 128; i += 96) {
        const int slot = i >> 7, row = i & 127, type = (nb * 12 + slot) >> 5;
        uint32_t v = 0;
        if (type == 1) v = 0x3F80u | (((POLY_MASK >> ((row >> 3) & 7)) & 1) ? 0x43C00000u : 0x3F800000u);
        if (type == 2) v = ((POLY_MASK >> ((row >> 3) & 7)) & 1) ? 0xBF80u : 0x3F80u;
        const uint32_t ad = R + slot * 6144 + (row >> 3) * 384 + 256 + (row & 7) * 16;
        asm volatile("st.shared.b32 [%0],%1;" ::"r"(ad + 4), "r"(v) : "memory");
        asm volatile("st.shared.v2.b32 [%0],{%1,%1};" ::"r"(ad + 8), "r"(0) : "memory");
      }
      fence_async_smem();
      pdl_wait();
#pragma unroll 1
      for (int t = 0; t < 2; t++) {
        bar_sync(2 + t, 352);
        const int s0 = t ? 7 : 0, s1 = t ? 12 : 7;
        if (ht == 0) {
          for (int s = s0; s < s1; s++) bulk_s2g(g_qkv + (size_t)(nb * 12 + s) * 98304 + mb * 6144, R + s * 6144, 6144);
          bulk_commit();
        }
        for (int s = s0 + (warp - 9); s < s1; s += 3) {
          const int gs = nb * 12 + s;
          if ((gs >> 5) != 1) continue;
          float mx2 = 0;
#pragma unroll 1
          for (int row = lane; row < 128; row += 32) {
            const uint32_t ad = R + s * 6144 + (row >> 3) * 384 + (row & 7) * 16;
            float q = 0;
#pragma unroll 1
            for (int ch = 0; ch < 3; ch++) {
              uint32_t u0, u1, u2, u3;
              asm volatile("ld.shared.v4.b32 {%0,%1,%2,%3},[%4];" : "=r"(u0), "=r"(u1), "=r"(u2), "=r"(u3) : "r"(ad + ch * 128));
              if (ch == 2) u1 = 0;
              q += bf_lo(u0) * bf_lo(u0) + bf_hi(u0) * bf_hi(u0) + bf_lo(u1) * bf_lo(u1) + bf_hi(u1) * bf_hi(u1);
              q += bf_lo(u2) * bf_lo(u2) + bf_hi(u2) * bf_hi(u2) + bf_lo(u3) * bf_lo(u3) + bf_hi(u3) * bf_hi(u3);
            }
            mx2 = (q > mx2 || q != q) ? q : mx2;
            if (mx2 != mx2) mx2 = __int_as_float(0x7f800000);
          }
#pragma unroll
          for (int o = 16; o; o >>= 1) mx2 = fmaxf(mx2, __shfl_xor_sync(~0u, mx2, o));
          if (lane == 0) g_kmax[(gs & 31) * 16 + mb] = mx2;
        }
      }
      if (ht == 0) bulk_wait0();
    }
  } else {
    REG_INC(240);
    uint32_t a[36][4];
    const int rowl = warp * 16;
#pragma unroll
    for (int c = 0; c < 8; c++) { mbar_wait(xfull + c * 8, 0); load_a_chunk(&a[c * 4], R + c * 16384, rowl, lane); }
    mbar_wait(full, 0);
    load_a_chunk(&a[32], RING, rowl, lane);
    __syncwarp();
    if (lane == 0) mbar_arrive(empty);
    bar_arrive(1, 352);
    pdl_wait();
    {
      const int g = lane >> 2, cq = lane & 3;
      const uint4 s0 = g_stat1[mb * 128 + rowl + g], s1 = g_stat1[mb * 128 + rowl + g + 8];
#pragma unroll
      for (int k = 0; k < 36; k++) {
        if ((k & 3) == 0) asm volatile("" ::: "memory");
        const uint4 t = g_tab1[k * 4 + cq];
        a[k][0] = ln_apply(a[k][0], s0, t.x, t.y);
        a[k][1] = ln_apply(a[k][1], s1, t.x, t.y);
        a[k][2] = ln_apply(a[k][2], s0, t.z, t.w);
        a[k][3] = ln_apply(a[k][3], s1, t.z, t.w);
      }
    }
    bar_sync(4, 256);
    Ring ring{RING, full, empty, 1, 0};
    float acc[64];
    MMA_TILE(wg_rs_n128_t1, acc, a, ring, lane);
    qkv_stage<16, 0>(acc, R, rowl + (lane >> 2), lane & 3, nb * 216);
    fence_async_smem();
    bar_arrive(2, 352);
    MMA_TILE(wg_rs_n88_t1, acc, a, ring, lane);
    qkv_stage<11, 16>(acc, R, rowl + (lane >> 2), lane & 3, nb * 216);
    fence_async_smem();
    bar_arrive(3, 352);
  }
}

#define ATT_SMEM (2 * 98304 + 1024 + 256)

__device__ __forceinline__ uint32_t exp2_pair_fma(float t0, float t1, uint32_t one2) {
  uint32_t y, m;
  asm("prmt.b32 %0,%1,%2,0x6521;" : "=r"(y) : "r"(__float_as_uint(t0)), "r"(__float_as_uint(t1)));
  asm("lop3.b32 %0,%1,0x007F007F,%2,0xEA;" : "=r"(m) : "r"(y), "r"(one2));
  const uint32_t w = hfma2(m, 0x3EF73EF7u, 0xBF37BF37u);
  const uint32_t h = hfma2(w, w, 0xBD63BD63u);
  return hfma2(y, h, y);
}

__device__ __forceinline__ void softmax_fast(const float* s, uint32_t* p, uint32_t one2) {
#pragma unroll
  for (int i = 0; i < 8; i++) {
    if ((POLY_MASK >> i) & 1) {
      p[2 * i] = exp2_pair_fma(s[4 * i], s[4 * i + 1], one2);
      p[2 * i + 1] = exp2_pair_fma(s[4 * i + 2], s[4 * i + 3], one2);
    } else {
      p[2 * i] = pack_bf16(ex2f(s[4 * i]), ex2f(s[4 * i + 1]));
      p[2 * i + 1] = pack_bf16(ex2f(s[4 * i + 2]), ex2f(s[4 * i + 3]));
    }
  }
}
#define QK_MMA(S, kaddr)                                                        \
  wg_rs_n64_t0(S, q[0], q[1], q[2], q[3], dk0 + (uint64_t)(kaddr), 0);       \
  wg_rs_n64_t0(S, q[4], q[5], q[6], q[7], dk1 + (uint64_t)(kaddr), 1);
#define QK_MMA128(S, kaddr)                                                     \
  wg_rs_n128_t0(S, q[0], q[1], q[2], q[3], dk0 + (uint64_t)(kaddr), 0);      \
  wg_rs_n128_t0(S, q[4], q[5], q[6], q[7], dk1 + (uint64_t)(kaddr), 1);
#define PV_MMA(P, vaddr)                                                        \
  _Pragma("unroll") for (int t = 0; t < 4; t++)                                 \
      wg_rs_n24_t1(o, P[4 * t], P[4 * t + 1], P[4 * t + 2], P[4 * t + 3], dv + (uint64_t)(vaddr) + t * 48, 1);

__global__ void __launch_bounds__(256, 1) k2_kernel() {
  extern __shared__ uint8_t smem_raw[];
  const uint32_t sb = (s2u(smem_raw) + 1023) & ~1023u;
  const uint32_t KS = sb, VS = sb + 98304, BAR = sb + 2 * 98304;
  const int tid = threadIdx.x, lane = tid & 31, warp = tid >> 5, wg = tid >> 7;
  const int head = blockIdx.x >> 2, qb = blockIdx.x & 3;
  if (tid == 0) {
    for (int i = 0; i < 16; i++) mbar_init(BAR + i * 8, 1);
    fence_bar_init();
  }
  __syncthreads();
  pdl_launch();
  pdl_wait();
  if (tid == 0) {
    const uint8_t* kg = g_qkv + (size_t)(32 + head) * 98304;
    const uint8_t* vg = g_qkv + (size_t)(64 + head) * 98304;
#pragma unroll 1
    for (int c = 0; c < 16; c++) {
      mbar_expect(BAR + c * 8, 12288);
      bulk_g2s(KS + c * 6144, kg + c * 6144, 6144, BAR + c * 8);
      bulk_g2s(VS + c * 6144, vg + c * 6144, 6144, BAR + c * 8);
    }
  }
  const uint64_t dk0 = mkdesc(KS, 128, 384, 0), dk1 = mkdesc(KS + 256, 0, 384, 0), dv = mkdesc(VS, 384, 128, 0);
  const int g = lane >> 2, cq = lane & 3;
  float kmax2 = g_kmax[head * 16 + (lane & 15)];
#pragma unroll
  for (int o = 8; o; o >>= 1) kmax2 = fmaxf(kmax2, __shfl_xor_sync(~0u, kmax2, o));

#pragma unroll 1
  for (int tile = 0; tile < 4; tile++) {
    const int row0 = qb * 512 + wg * 256 + tile * 64 + (warp & 3) * 16 + g;
    uint32_t q[8];

    {
      const uint8_t* qg = g_qkv + (size_t)head * 98304 + (row0 >> 3) * 384 + (row0 & 7) * 16 + cq * 4;
      q[0] = *(const uint32_t*)(qg);       q[1] = *(const uint32_t*)(qg + 384);
      q[2] = *(const uint32_t*)(qg + 128); q[3] = *(const uint32_t*)(qg + 384 + 128);
      q[4] = *(const uint32_t*)(qg + 256); q[5] = *(const uint32_t*)(qg + 384 + 256);
      q[6] = *(const uint32_t*)(qg + 256 + 12 - cq * 4); q[7] = *(const uint32_t*)(qg + 256 + 8 - cq * 4);
    }
    float n0 = bf_lo(q[0]) * bf_lo(q[0]) + bf_hi(q[0]) * bf_hi(q[0]) + bf_lo(q[2]) * bf_lo(q[2]) + bf_hi(q[2]) * bf_hi(q[2]) +
               bf_lo(q[4]) * bf_lo(q[4]) + bf_hi(q[4]) * bf_hi(q[4]);
    float n1 = bf_lo(q[1]) * bf_lo(q[1]) + bf_hi(q[1]) * bf_hi(q[1]) + bf_lo(q[3]) * bf_lo(q[3]) + bf_hi(q[3]) * bf_hi(q[3]) +
               bf_lo(q[5]) * bf_lo(q[5]) + bf_hi(q[5]) * bf_hi(q[5]);
    n0 += __shfl_xor_sync(~0u, n0, 1); n0 += __shfl_xor_sync(~0u, n0, 2);
    n1 += __shfl_xor_sync(~0u, n1, 1); n1 += __shfl_xor_sync(~0u, n1, 2);
    const float b0 = sqrtf(n0 * kmax2) * 1.01f + 1.0f, b1 = sqrtf(n1 * kmax2) * 1.01f + 1.0f;
    int ok = (b0 <= 62.0f) && (b1 <= 62.0f);
    {
      uint32_t all;
      asm volatile("{.reg .pred p,q; setp.ne.b32 p,%1,0; barrier.red.and.pred q,%2,128,p; selp.u32 %0,1,0,q;}"
                   : "=r"(all) : "r"(ok), "r"(1 + wg) : "memory");
      ok = __all_sync(~0u, all);
    }
    float o[12];
#pragma unroll
    for (int i = 0; i < 12; i++) { o[i] = 0.f; asm volatile("" : "+f"(o[i])); }

    if (ok) {
      if (cq == 1) { q[4] = pack_bf16(-b0, 1.0f); q[5] = pack_bf16(-b1, 1.0f); }
      uint32_t one2 = 0x3F803F80u;
      asm volatile("" : "+r"(one2));
      float sa[64], sbb[64];
      uint32_t pa[32], pb[32];
      mbar_wait(BAR, 0);
      mbar_wait(BAR + 8, 0);
      WG_FENCE();
      QK_MMA128(sa, 0u);
      WG_COMMIT();
      QK_MMA128(sbb, 384u);
      WG_COMMIT();
#pragma unroll 1
      for (int j = 0; j < 16; j += 2) {
        const int jn = (j < 14) ? j + 2 : j;
        WG_WAIT(1);
        softmax_fast(sa, pa, one2);
        softmax_fast(sa + 32, pa + 16, one2);
        mbar_wait(BAR + jn * 8, 0);
        WG_FENCE();
        PV_MMA(pa, (uint32_t)j * 384);
        PV_MMA((pa + 16), (uint32_t)j * 384 + 192);
        QK_MMA128(sa, (uint32_t)jn * 384);
        WG_COMMIT();
        WG_WAIT(1);
        softmax_fast(sbb, pb, one2);
        softmax_fast(sbb + 32, pb + 16, one2);
        mbar_wait(BAR + jn * 8 + 8, 0);
        WG_FENCE();
        PV_MMA(pb, (uint32_t)j * 384 + 384);
        PV_MMA((pb + 16), (uint32_t)j * 384 + 384 + 192);
        QK_MMA128(sbb, (uint32_t)jn * 384 + 384);
        WG_COMMIT();
      }
      WG_WAIT(0);
    } else {
      float m0 = -INFINITY, m1 = -INFINITY;
#pragma unroll 1
      for (int j = 0; j < 32; j++) {
        float s[32];
        uint32_t p[16];
        mbar_wait(BAR + (j >> 1) * 8, 0);
        WG_FENCE();
        QK_MMA(s, (uint32_t)j * 192);
        WG_COMMIT();
        WG_WAIT(0);
        float x0 = m0, x1 = m1;
#pragma unroll
        for (int i = 0; i < 8; i++) {
          x0 = fmaxf(x0, fmaxf(s[4 * i], s[4 * i + 1]));
          x1 = fmaxf(x1, fmaxf(s[4 * i + 2], s[4 * i + 3]));
        }
        x0 = fmaxf(x0, __shfl_xor_sync(~0u, x0, 1)); x0 = fmaxf(x0, __shfl_xor_sync(~0u, x0, 2));
        x1 = fmaxf(x1, __shfl_xor_sync(~0u, x1, 1)); x1 = fmaxf(x1, __shfl_xor_sync(~0u, x1, 2));
        const float c0 = ex2f(m0 - x0), c1 = ex2f(m1 - x1);
        m0 = x0; m1 = x1;
#pragma unroll
        for (int i = 0; i < 3; i++) { o[4 * i] *= c0; o[4 * i + 1] *= c0; o[4 * i + 2] *= c1; o[4 * i + 3] *= c1; }
#pragma unroll
        for (int i = 0; i < 8; i++) {
          const uint32_t sg = ((POLY_MASK >> i) & 1) ? 0x80008000u : 0u;
          p[2 * i] = pack_bf16(ex2f(s[4 * i] - x0), ex2f(s[4 * i + 1] - x0)) ^ sg;
          p[2 * i + 1] = pack_bf16(ex2f(s[4 * i + 2] - x1), ex2f(s[4 * i + 3] - x1)) ^ sg;
        }
        WG_FENCE();
        PV_MMA(p, (uint32_t)j * 192);
        WG_COMMIT();
        WG_WAIT(0);
      }
    }
    const float l0 = __shfl_sync(~0u, o[8], (lane & ~3) | 1), l1 = __shfl_sync(~0u, o[10], (lane & ~3) | 1);
    const float i0 = 1.0f / l0, i1 = 1.0f / l1;
    uint32_t* og = (uint32_t*)(g_o + (size_t)row0 * DM + head * 18 + cq * 2);
    og[0] = pack_bf16(o[0] * i0, o[1] * i0);
    og[4] = pack_bf16(o[4] * i0, o[5] * i0);
    og[8 * DM / 2] = pack_bf16(o[2] * i1, o[3] * i1);
    og[8 * DM / 2 + 4] = pack_bf16(o[6] * i1, o[7] * i1);
    if (cq == 0) {
      og[8] = pack_bf16(o[8] * i0, o[9] * i0);
      og[8 * DM / 2 + 8] = pack_bf16(o[10] * i1, o[11] * i1);
    }
  }
}

#define K3_NSTG 4
#define K3_SMEM (9 * 16384 + K3_NSTG * 16384 + 1024 + 256)
__global__ void __launch_bounds__(288, 1) k3_kernel(const __grid_constant__ CUtensorMap mo, const __grid_constant__ CUtensorMap mw,
                                                    const __nv_bfloat16* __restrict__ x) {
  extern __shared__ uint8_t smem_raw[];
  const uint32_t sb = (s2u(smem_raw) + 1023) & ~1023u;
  const uint32_t A = sb, RING = sb + 9 * 16384, BAR = RING + K3_NSTG * 16384;
  const uint32_t full = BAR, empty = BAR + 64, afull = BAR + 128;
  const int tid = threadIdx.x, lane = tid & 31, warp = tid >> 5;
  const int mb = blockIdx.x >> 3, nb = blockIdx.x & 7;
  if (tid == 0) {
    for (int i = 0; i < K3_NSTG; i++) { mbar_init(full + i * 8, 1); mbar_init(empty + i * 8, 8); }
    for (int i = 0; i < 9; i++) mbar_init(afull + i * 8, 1);
    fence_bar_init();
  }
  __syncthreads();
  pdl_launch();
  if (warp == 8) {
    if (lane == 0) {
      for (int s = 0; s < K3_NSTG; s++) {
        mbar_expect(full + s * 8, 16384);
        tma2d(RING + s * 16384, &mw, nb * 72, s * 64, full + s * 8);
        tma2d(RING + s * 16384 + 8192, &mw, nb * 72 + 64, s * 64, full + s * 8);
      }
      pdl_wait();
      for (int c = 0; c < 9; c++) { mbar_expect(afull + c * 8, 16384); tma2d(A + c * 16384, &mo, c * 64, mb * 128, afull + c * 8); }
      for (int s = K3_NSTG; s < 9; s++) {
        const int st = s % K3_NSTG;
        mbar_wait(empty + st * 8, ((s / K3_NSTG) & 1) ^ 1);
        mbar_expect(full + st * 8, 16384);
        tma2d(RING + st * 16384, &mw, nb * 72, s * 64, full + st * 8);
        tma2d(RING + st * 16384 + 8192, &mw, nb * 72 + 64, s * 64, full + st * 8);
      }
    }
  } else {
    const int g = lane >> 2, cq = lane & 3;
    const int row = mb * 128 + warp * 16 + g, col = nb * 72 + cq * 2;
    uint32_t xv[18];
#pragma unroll
    for (int i = 0; i < 9; i++) {
      xv[2 * i] = __ldg((const uint32_t*)(x + (size_t)row * DM + col + 8 * i));
      xv[2 * i + 1] = __ldg((const uint32_t*)(x + (size_t)(row + 8) * DM + col + 8 * i));
    }
    pdl_wait();
    float2 ga[9];
#pragma unroll
    for (int i = 0; i < 9; i++) ga[i] = *(const float2*)(g_ga + col + 8 * i);
    float acc[36];
    const uint32_t abase = A + (warp >> 2) * 8192;
#pragma unroll
    for (int s = 0; s < 9; s++) {
      const int st = s % K3_NSTG;
      mbar_wait(afull + s * 8, 0);
      mbar_wait(full + st * 8, (s / K3_NSTG) & 1);
      WG_FENCE();
#pragma unroll
      for (int k = 0; k < 4; k++)
        wg_ss_n72_t1(acc, mkdesc(abase + s * 16384 + k * 32, 16, 1024, 1), mkdesc(RING + st * 16384 + k * 2048, 8192, 1024, 1), (s | k) != 0);
      WG_COMMIT();
      if (s > 0) { WG_WAIT(1); if (lane == 0) mbar_arrive(empty + ((s - 1) % K3_NSTG) * 8); }
    }
    WG_WAIT(0);
    float s0 = 0, s1 = 0;
#pragma unroll
    for (int i = 0; i < 9; i++) {
      acc[4 * i] = rbf(bf_lo(xv[2 * i]) + rbf(ga[i].x * rbf(acc[4 * i])));
      acc[4 * i + 1] = rbf(bf_hi(xv[2 * i]) + rbf(ga[i].y * rbf(acc[4 * i + 1])));
      acc[4 * i + 2] = rbf(bf_lo(xv[2 * i + 1]) + rbf(ga[i].x * rbf(acc[4 * i + 2])));
      acc[4 * i + 3] = rbf(bf_hi(xv[2 * i + 1]) + rbf(ga[i].y * rbf(acc[4 * i + 3])));
      *(uint32_t*)(g_x1 + (size_t)row * DM + col + 8 * i) = pack_bf16(acc[4 * i], acc[4 * i + 1]);
      *(uint32_t*)(g_x1 + (size_t)(row + 8) * DM + col + 8 * i) = pack_bf16(acc[4 * i + 2], acc[4 * i + 3]);
      s0 += acc[4 * i] + acc[4 * i + 1];
      s1 += acc[4 * i + 2] + acc[4 * i + 3];
    }
    s0 += __shfl_xor_sync(~0u, s0, 1); s0 += __shfl_xor_sync(~0u, s0, 2);
    s1 += __shfl_xor_sync(~0u, s1, 1); s1 += __shfl_xor_sync(~0u, s1, 2);
    const float m0 = s0 * (1.0f / 72), m1 = s1 * (1.0f / 72);
    float q0 = 0, q1 = 0;
#pragma unroll
    for (int i = 0; i < 9; i++) {
      q0 += (acc[4 * i] - m0) * (acc[4 * i] - m0) + (acc[4 * i + 1] - m0) * (acc[4 * i + 1] - m0);
      q1 += (acc[4 * i + 2] - m1) * (acc[4 * i + 2] - m1) + (acc[4 * i + 3] - m1) * (acc[4 * i + 3] - m1);
    }
    q0 += __shfl_xor_sync(~0u, q0, 1); q0 += __shfl_xor_sync(~0u, q0, 2);
    q1 += __shfl_xor_sync(~0u, q1, 1); q1 += __shfl_xor_sync(~0u, q1, 2);
    if (cq == 0) {
      g_stat2[row * 8 + nb] = make_float2(m0, q0);
      g_stat2[(row + 8) * 8 + nb] = make_float2(m1, q1);
    }
  }
}

__device__ __forceinline__ uint4 ln2_consts(int row, int cq) {
  const float4 p = *(const float4*)(g_stat2 + row * 8 + cq * 2);
  float s = p.x + p.z;
  s += __shfl_xor_sync(~0u, s, 1); s += __shfl_xor_sync(~0u, s, 2);
  const float mean = s * 0.125f;
  float q = p.y + p.w + 72.0f * ((p.x - mean) * (p.x - mean) + (p.z - mean) * (p.z - mean));
  q += __shfl_xor_sync(~0u, q, 1); q += __shfl_xor_sync(~0u, q, 2);
  return ln_consts(mean, q * (1.0f / DM));
}
__device__ __forceinline__ uint32_t glu_pair(float g0, float g1, float u0, float u1) {
  const float s0 = fmaf(tanhf_fast(0.5f * g0), 0.5f, 0.5f), s1 = fmaf(tanhf_fast(0.5f * g1), 0.5f, 0.5f);
  return pack_bf16(s0 * u0, s1 * u1);
}
template <int NG>
__device__ __forceinline__ void stage_part(const float* acc, uint32_t stg, int wrow, int lane) {
  const int r = wrow + (lane & 7) + ((lane >> 3) & 1) * 8;
#pragma unroll
  for (int i = 0; i < NG; i += 2) {
    const int ch = i + (lane >> 4);
    stsm4(stg + r * 256 + ((ch ^ (r & 7)) << 4), pack_bf16(acc[4 * i], acc[4 * i + 1]), pack_bf16(acc[4 * i + 2], acc[4 * i + 3]),
          pack_bf16(acc[4 * i + 4], acc[4 * i + 5]), pack_bf16(acc[4 * i + 6], acc[4 * i + 7]));
  }
}

__global__ void __launch_bounds__(384, 1) k4_kernel(const __grid_constant__ CUtensorMap mx, const __grid_constant__ CUtensorMap mg,
                                                    const __grid_constant__ CUtensorMap mu, const __grid_constant__ CUtensorMap md,
                                                    __nv_bfloat16* __restrict__ out) {
  extern __shared__ uint8_t smem_raw[];
  const uint32_t sb = (s2u(smem_raw) + 1023) & ~1023u;
  const uint32_t R = sb, RING = sb + R_BYTES, BAR = RING + NSTG * STG_BYTES;
  const uint32_t full = BAR, empty = BAR + 64, xfull = BAR + 128, sfull = BAR + 192, sfree = BAR + 208;
  const int tid = threadIdx.x, lane = tid & 31, warp = tid >> 5;
  const int mb = blockIdx.x >> 3, fb = blockIdx.x & 7;
  if (tid == 0) {
    for (int i = 0; i < 2; i++) { mbar_init(sfull + i * 8, 4); mbar_init(sfree + i * 8, 1); }
    for (int i = 0; i < NSTG; i++) { mbar_init(full + i * 8, 1); mbar_init(empty + i * 8, 8); }
    for (int i = 0; i < 8; i++) mbar_init(xfull + i * 8, 1);
    fence_bar_init();
  }
  __syncthreads();
  if (warp >= 8) {
    REG_DEC(24);
    if (warp == 8) {
      if (lane == 0) {
        int st = 1; uint32_t ph = 0;
        for (int it = 0; it < 126; it++) {
          if (it == NSTG - 1) {
            pdl_wait();
            for (int c = 0; c < 8; c++) { mbar_expect(xfull + c * 8, 16384); tma2d(R + c * 16384, &mx, c * 64, mb * 128, xfull + c * 8); }
            mbar_expect(full, 16384);
            tma2d(RING, &mx, 512, mb * 128, full);
          }
          const int t = it / 9, s = it - t * 9;
          const uint32_t dst = RING + st * STG_BYTES, fb_ = full + st * 8;
          mbar_wait(empty + st * 8, ph ^ 1);
          if (t < 9) {
            mbar_expect(fb_, 16384);
            tma2d(dst, &mg, fb * 576 + t * 64, s * 64, fb_);
            tma2d(dst + 8192, &mu, fb * 576 + t * 64, s * 64, fb_);
          } else {
            mbar_expect(fb_, t < 13 ? 16384 : 8192);
            tma2d(dst, &md, (t - 9) * 128, fb * 576 + s * 64, fb_);
            if (t < 13) tma2d(dst + 8192, &md, (t - 9) * 128 + 64, fb * 576 + s * 64, fb_);
          }
          if (++st == NSTG) { st = 0; ph ^= 1; }
        }
      }
    } else {
      if (warp < 11 && lane == 0) {
        const int wg = warp - 9;
#pragma unroll 1
        for (int p = 0; p < 5; p++) {
          mbar_wait(sfull + wg * 8, p & 1);
          bulk_s2g(g_part + ((size_t)((fb * 16 + mb) * 5 + p) * 2 + wg) * 16384, R + ((p & 3) * 2 + wg) * 16384, 16384);
          bulk_commit();
          bulk_wait0();
          asm volatile("fence.proxy.async;" ::: "memory");
          asm volatile("red.release.gpu.global.add.u32 [%0],1;" ::"l"(g_cnt + mb * 5 + p) : "memory");
          if (p == 0) mbar_arrive(sfree + wg * 8);
        }
      }
    }
  } else {
    REG_INC(240);
    uint32_t a[36][4];
    const int rowl = warp * 16, wg = warp >> 2;
    pdl_wait();
    {
      const int g = lane >> 2, cq = lane & 3;
      const uint4 s0 = ln2_consts(mb * 128 + rowl + g, cq), s1 = ln2_consts(mb * 128 + rowl + g + 8, cq);
#pragma unroll
      for (int c = 0; c < 9; c++) {
        if (c < 8) { mbar_wait(xfull + c * 8, 0); load_a_chunk(&a[c * 4], R + c * 16384, rowl, lane); }
        else { mbar_wait(full, 0); load_a_chunk(&a[32], RING, rowl, lane); __syncwarp(); if (lane == 0) mbar_arrive(empty); }
#pragma unroll
        for (int k = c * 4; k < c * 4 + 4; k++) {
          const uint4 t = g_tab2[k * 4 + cq];
          a[k][0] = ln_apply(a[k][0], s0, t.x, t.y);
          a[k][1] = ln_apply(a[k][1], s1, t.x, t.y);
          a[k][2] = ln_apply(a[k][2], s0, t.z, t.w);
          a[k][3] = ln_apply(a[k][3], s1, t.z, t.w);
        }
      }
    }
    bar_sync(4, 256);
    Ring ring{RING, full, empty, 1, 0};
    float acc[64];
    const uint32_t hsp = R + tid * 16;
#pragma unroll 1
    for (int t = 0; t < 8; t++) {
      MMA_TILE(wg_rs_n128_t1, acc, a, ring, lane);
#pragma unroll
      for (int j = 0; j < 4; j++) {
        uint32_t h[4];
#pragma unroll
        for (int e = 0; e < 4; e++) h[e] = glu_pair(acc[8 * j + 2 * e], acc[8 * j + 2 * e + 1], acc[32 + 8 * j + 2 * e], acc[32 + 8 * j + 2 * e + 1]);
        asm volatile("st.shared.v4.b32 [%0],{%1,%2,%3,%4};" ::"r"(hsp + t * 16384 + j * 4096), "r"(h[0]), "r"(h[1]), "r"(h[2]), "r"(h[3]) : "memory");
      }
    }
    MMA_TILE(wg_rs_n128_t1, acc, a, ring, lane);
#pragma unroll
    for (int j = 0; j < 4; j++)
#pragma unroll
      for (int e = 0; e < 4; e++)
        a[32 + j][e] = glu_pair(acc[8 * j + 2 * e], acc[8 * j + 2 * e + 1], acc[32 + 8 * j + 2 * e], acc[32 + 8 * j + 2 * e + 1]);
#pragma unroll
    for (int k = 0; k < 32; k++)
      asm volatile("ld.shared.v4.b32 {%0,%1,%2,%3},[%4];" : "=r"(a[k][0]), "=r"(a[k][1]), "=r"(a[k][2]), "=r"(a[k][3]) : "r"(hsp + k * 4096) : "memory");
    bar_sync(4, 256);
#pragma unroll 1
    for (int p = 0; p < 4; p++) {
      MMA_TILE(wg_rs_n128_t1, acc, a, ring, lane);
      stage_part<16>(acc, R + (p * 2 + wg) * 16384, (warp & 3) * 16, lane);
      fence_async_smem();
      __syncwarp();
      if (lane == 0) mbar_arrive(sfull + wg * 8);
    }
    MMA_TILE(wg_rs_n64_t1, acc, a, ring, lane);
    mbar_wait(sfree + wg * 8, 0);
    stage_part<8>(acc, R + wg * 16384, (warp & 3) * 16, lane);
    fence_async_smem();
    __syncwarp();
    if (lane == 0) mbar_arrive(sfull + wg * 8);
    const int rl = fb * 16 + (tid >> 4), ch = tid & 15;
    const uint8_t* src = g_part + ((size_t)(mb * 5) * 2 + (rl >> 6)) * 16384 + (rl & 63) * 256 + ((ch ^ (rl & 7)) << 4);
    const size_t off = (size_t)(mb * 128 + rl) * DM + ch * 8;
#pragma unroll
    for (int p = 0; p < 5; p++) {
      if (p == 4 && ch >= 8) break;
      const uint4 xv = *(const uint4*)(g_x1 + off + p * 128);
      const float4 g0 = *(const float4*)(g_gb + p * 128 + ch * 8), g1 = *(const float4*)(g_gb + p * 128 + ch * 8 + 4);
      if (p == 0 || p == 4) {
        const int pl = p == 0 ? 3 : 4;
        for (int pp = p; pp <= pl; pp++) {
          unsigned int v; int n = 0;
          do {
            asm volatile("ld.acquire.gpu.global.u32 %0,[%1];" : "=r"(v) : "l"(g_cnt + mb * 5 + pp) : "memory");
          } while (v < 16 && ++n < 20000000);
          if (v < 16) __trap();
        }
      }
      uint4 v[8];
#pragma unroll
      for (int f = 0; f < 8; f++) v[f] = __ldcg((const uint4*)(src + p * 32768 + (size_t)f * (16 * 5 * 2 * 16384)));
      float r8[8] = {0, 0, 0, 0, 0, 0, 0, 0};
#pragma unroll
      for (int f = 0; f < 8; f++) {
        r8[0] += bf_lo(v[f].x); r8[1] += bf_hi(v[f].x); r8[2] += bf_lo(v[f].y); r8[3] += bf_hi(v[f].y);
        r8[4] += bf_lo(v[f].z); r8[5] += bf_hi(v[f].z); r8[6] += bf_lo(v[f].w); r8[7] += bf_hi(v[f].w);
      }
      uint4 r;
      r.x = pack_bf16(bf_lo(xv.x) + rbf(g0.x * rbf(r8[0])), bf_hi(xv.x) + rbf(g0.y * rbf(r8[1])));
      r.y = pack_bf16(bf_lo(xv.y) + rbf(g0.z * rbf(r8[2])), bf_hi(xv.y) + rbf(g0.w * rbf(r8[3])));
      r.z = pack_bf16(bf_lo(xv.z) + rbf(g1.x * rbf(r8[4])), bf_hi(xv.z) + rbf(g1.y * rbf(r8[5])));
      r.w = pack_bf16(bf_lo(xv.w) + rbf(g1.z * rbf(r8[6])), bf_hi(xv.w) + rbf(g1.w * rbf(r8[7])));
      *(uint4*)(out + off + p * 128) = r;
    }
  }
}

typedef CUresult (*EncodeFn)(CUtensorMap*, CUtensorMapDataType, cuuint32_t, void*, const cuuint64_t*, const cuuint64_t*,
                             const cuuint32_t*, const cuuint32_t*, CUtensorMapInterleave, CUtensorMapSwizzle,
                             CUtensorMapL2promotion, CUtensorMapFloatOOBfill);
static void make_map(EncodeFn fn, CUtensorMap* m, const void* p, int rows, int cols, int box_rows) {
  cuuint64_t dims[2] = {(cuuint64_t)cols, (cuuint64_t)rows};
  cuuint64_t strides[1] = {(cuuint64_t)cols * 2};
  cuuint32_t box[2] = {64, (cuuint32_t)box_rows};
  cuuint32_t es[2] = {1, 1};
  fn(m, CU_TENSOR_MAP_DATA_TYPE_BFLOAT16, 2, (void*)p, dims, strides, box, es, CU_TENSOR_MAP_INTERLEAVE_NONE,
     CU_TENSOR_MAP_SWIZZLE_128B, CU_TENSOR_MAP_L2_PROMOTION_L2_256B, CU_TENSOR_MAP_FLOAT_OOB_FILL_NONE);
}
template <typename... KA, typename... A>
static void launch(void (*k)(KA...), int grid, int block, int smem, bool pdl, A... args) {
  cudaLaunchConfig_t cfg = {};
  cfg.gridDim = dim3(grid); cfg.blockDim = dim3(block); cfg.dynamicSmemBytes = smem; cfg.stream = cudaStreamPerThread;
  cudaLaunchAttribute at;
  at.id = cudaLaunchAttributeProgrammaticStreamSerialization;
  at.val.programmaticStreamSerializationAllowed = 1;
  cfg.attrs = &at; cfg.numAttrs = pdl ? 1 : 0;
  cudaLaunchKernelEx(&cfg, k, KA(args)...);
}

extern "C" void kernel_launch(void* const* d_in, const int* in_sizes, int n_in, void* d_out, int out_size) {
  const __nv_bfloat16* x = (const __nv_bfloat16*)d_in[0];
  void* fnp = nullptr;
  cudaDriverEntryPointQueryResult qr;
  cudaGetDriverEntryPoint("cuTensorMapEncodeTiled", &fnp, cudaEnableDefault, &qr);
  EncodeFn fn = (EncodeFn)fnp;
  void *po, *px1;
  cudaGetSymbolAddress(&po, g_o);
  cudaGetSymbolAddress(&px1, g_x1);
  CUtensorMap mx, mqkv, mo, mwo, mx1, mg, mu, md;
  make_map(fn, &mx, x, SEQ, DM, 128);
  make_map(fn, &mqkv, d_in[1], DM, 3 * DM, 64);
  make_map(fn, &mo, po, SEQ, DM, 128);
  make_map(fn, &mwo, d_in[2], DM, DM, 64);
  make_map(fn, &mx1, px1, SEQ, DM, 128);
  make_map(fn, &mg, d_in[4], DM, FF, 64);
  make_map(fn, &mu, d_in[5], DM, FF, 64);
  make_map(fn, &md, d_in[6], FF, DM, 64);
  cudaFuncSetAttribute(k1_kernel, cudaFuncAttributeMaxDynamicSharedMemorySize, GEMM_SMEM);
  cudaFuncSetAttribute(k2_kernel, cudaFuncAttributeMaxDynamicSharedMemorySize, ATT_SMEM);
  cudaFuncSetAttribute(k3_kernel, cudaFuncAttributeMaxDynamicSharedMemorySize, K3_SMEM);
  cudaFuncSetAttribute(k4_kernel, cudaFuncAttributeMaxDynamicSharedMemorySize, GEMM_SMEM);
  launch(k0_kernel, 108 + 128, 256, 0, false, x, (const __nv_bfloat16*)d_in[7], (const __nv_bfloat16*)d_in[8]);
  launch(k1_kernel, 128, 384, GEMM_SMEM, true, mx, mqkv);
  launch(k2_kernel, 128, 256, ATT_SMEM, true);
  launch(k3_kernel, 128, 288, K3_SMEM, true, mo, mwo, x);
  launch(k4_kernel, 128, 384, GEMM_SMEM, true, mx1, mg, mu, md, (__nv_bfloat16*)d_out);
}
```

```cpp
#include <cuda_runtime.h>
#include <cuda_bf16.h>
#include <cuda.h>
#include <stdint.h>

#define SEQ 2048
#define DM 576
#define NH 32
#define FF 4608

__device__ uint4 g_tab1[36 * 4];
__device__ uint4 g_tab2[36 * 4];
__device__ float g_ga[DM];
__device__ float g_gb[DM];
__device__ uint4 g_stat1[SEQ];
__device__ float2 g_stat2[SEQ * 8];
__device__ __align__(1024) uint8_t g_qkv[96 * 98304];
__device__ float g_kmax[NH * 16];
__device__ __align__(1024) __nv_bfloat16 g_o[SEQ * DM];
__device__ __align__(1024) __nv_bfloat16 g_x1[SEQ * DM];
__device__ __align__(1024) uint8_t g_part[8 * 16 * 5 * 2 * 16384];
__device__ unsigned int g_cnt[16 * 5];

#define TS(k, i)
__device__ __forceinline__ uint32_t s2u(const void* p) { return (uint32_t)__cvta_generic_to_shared(p); }
__device__ __forceinline__ void mbar_init(uint32_t b, int c) { asm volatile("mbarrier.init.shared::cta.b64 [%0],%1;" ::"r"(b), "r"(c)); }
__device__ __forceinline__ void mbar_expect(uint32_t b, uint32_t n) { asm volatile("mbarrier.arrive.expect_tx.shared::cta.b64 _,[%0],%1;" ::"r"(b), "r"(n) : "memory"); }
__device__ __forceinline__ void mbar_arrive(uint32_t b) { asm volatile("mbarrier.arrive.shared::cta.b64 _,[%0];" ::"r"(b) : "memory"); }
__device__ __forceinline__ void mbar_wait(uint32_t b, uint32_t ph) {
  asm volatile(
      "{.reg .pred p; .reg .u32 n; mov.u32 n,0;\n"
      "W: mbarrier.try_wait.parity.shared::cta.b64 p,[%0],%1;\n"
      "@p bra D;\n"
      "add.u32 n,n,1; setp.lt.u32 p,n,4000000; @p bra W;\n"
      "trap;\n"
      "D: }" ::"r"(b), "r"(ph) : "memory");
}
__device__ __forceinline__ void tma2d(uint32_t dst, const CUtensorMap* m, int c0, int c1, uint32_t bar) {
  asm volatile("cp.async.bulk.tensor.2d.shared::cluster.global.mbarrier::complete_tx::bytes [%0],[%1,{%3,%4}],[%2];"
               ::"r"(dst), "l"(m), "r"(bar), "r"(c0), "r"(c1) : "memory");
}
__device__ __forceinline__ void bulk_g2s(uint32_t dst, const void* src, uint32_t bytes, uint32_t bar) {
  asm volatile("cp.async.bulk.shared::cluster.global.mbarrier::complete_tx::bytes [%0],[%1],%2,[%3];"
               ::"r"(dst), "l"(src), "r"(bytes), "r"(bar) : "memory");
}
__device__ __forceinline__ void bulk_s2g(void* dst, uint32_t src, uint32_t bytes) {
  asm volatile("cp.async.bulk.global.shared::cta.bulk_group [%0],[%1],%2;" ::"l"(dst), "r"(src), "r"(bytes) : "memory");
}
__device__ __forceinline__ void bulk_commit() { asm volatile("cp.async.bulk.commit_group;" ::: "memory"); }
__device__ __forceinline__ void bulk_wait0() { asm volatile("cp.async.bulk.wait_group 0;" ::: "memory"); }
__device__ __forceinline__ void prefetch_map(const CUtensorMap* m) { asm volatile("prefetch.tensormap [%0];" ::"l"(m) : "memory"); }
__device__ __forceinline__ void fence_async_smem() { asm volatile("fence.proxy.async.shared::cta;" ::: "memory"); }
__device__ __forceinline__ void fence_bar_init() { asm volatile("fence.mbarrier_init.release.cluster;" ::: "memory"); }
__device__ __forceinline__ void pdl_wait() { asm volatile("griddepcontrol.wait;" ::: "memory"); }
__device__ __forceinline__ void pdl_launch() { asm volatile("griddepcontrol.launch_dependents;" ::: "memory"); }
__device__ __forceinline__ void bar_sync(int id, int n) { asm volatile("bar.sync %0,%1;" ::"r"(id), "r"(n) : "memory"); }
__device__ __forceinline__ void bar_arrive(int id, int n) { asm volatile("bar.arrive %0,%1;" ::"r"(id), "r"(n) : "memory"); }
#define WG_FENCE() asm volatile("wgmma.fence.sync.aligned;" ::: "memory")
#define WG_COMMIT() asm volatile("wgmma.commit_group.sync.aligned;" ::: "memory")
#define WG_WAIT(n) asm volatile("wgmma.wait_group.sync.aligned " #n ";" ::: "memory")
template <int N> __device__ __forceinline__ void fence_regs(float* r) {
#pragma unroll
  for (int i = 0; i < N; i++) asm volatile("" : "+f"(r[i])::"memory");
}
#define REG_INC(n) asm volatile("setmaxnreg.inc.sync.aligned.u32 " #n ";")
#define REG_DEC(n) asm volatile("setmaxnreg.dec.sync.aligned.u32 " #n ";")
__device__ __forceinline__ uint64_t mkdesc(uint32_t addr, uint32_t lbo, uint32_t sbo, int sw) {
  return (uint64_t)((addr & 0x3FFFF) >> 4) | ((uint64_t)(lbo >> 4) << 16) | ((uint64_t)(sbo >> 4) << 32) | ((uint64_t)sw << 62);
}
__device__ __forceinline__ void ldsm4(uint32_t* r, uint32_t addr) {
  asm volatile("ldmatrix.sync.aligned.m8n8.x4.shared.b16 {%0,%1,%2,%3},[%4];" : "=r"(r[0]), "=r"(r[1]), "=r"(r[2]), "=r"(r[3]) : "r"(addr) : "memory");
}
__device__ __forceinline__ void stsm4(uint32_t addr, uint32_t r0, uint32_t r1, uint32_t r2, uint32_t r3) {
  asm volatile("stmatrix.sync.aligned.m8n8.x4.shared.b16 [%0],{%1,%2,%3,%4};" ::"r"(addr), "r"(r0), "r"(r1), "r"(r2), "r"(r3) : "memory");
}
__device__ __forceinline__ uint32_t pack_bf16(float lo, float hi) {
  uint32_t r;
  asm("cvt.rn.bf16x2.f32 %0,%1,%2;" : "=r"(r) : "f"(hi), "f"(lo));
  return r;
}
__device__ __forceinline__ float bf_lo(uint32_t v) { return __uint_as_float(v << 16); }
__device__ __forceinline__ float bf_hi(uint32_t v) { return __uint_as_float(v & 0xFFFF0000u); }
__device__ __forceinline__ float rbf(float x) { return __bfloat162float(__float2bfloat16_rn(x)); }
__device__ __forceinline__ uint32_t hfma2(uint32_t a, uint32_t b, uint32_t c) {
  uint32_t r;
  asm("fma.rn.bf16x2 %0,%1,%2,%3;" : "=r"(r) : "r"(a), "r"(b), "r"(c));
  return r;
}
__device__ __forceinline__ uint32_t hadd2(uint32_t a, uint32_t b) {
  uint32_t r;
  asm("add.rn.bf16x2 %0,%1,%2;" : "=r"(r) : "r"(a), "r"(b));
  return r;
}
__device__ __forceinline__ uint32_t hmul2(uint32_t a, uint32_t b) {
  uint32_t r;
  asm("mul.rn.bf16x2 %0,%1,%2;" : "=r"(r) : "r"(a), "r"(b));
  return r;
}
__device__ __forceinline__ uint32_t hneg2(uint32_t a) {
  uint32_t r;
  asm("neg.bf16x2 %0,%1;" : "=r"(r) : "r"(a));
  return r;
}
__device__ __forceinline__ float ex2f(float x) {
  float r;
  asm("ex2.approx.ftz.f32 %0,%1;" : "=f"(r) : "f"(x));
  return r;
}
__device__ __forceinline__ float tanhf_fast(float x) {
  float r;
  asm("tanh.approx.f32 %0,%1;" : "=f"(r) : "f"(x));
  return r;
}
__device__ __forceinline__ uint4 ln_consts(float mean, float var) {
  float m = rbf(mean), v = rbf(var);
  float s = rbf(sqrtf(rbf(v + 1e-5f)));
  float r = 1.0f / s;
  float rh = rbf(r), rl = r - rh;
  return make_uint4(pack_bf16(-m, -m), pack_bf16(rh, rh), pack_bf16(rl, rl), 0u);
}
__device__ __forceinline__ uint32_t ln_apply(uint32_t x, const uint4& st, uint32_t a, uint32_t s) {
  uint32_t d = hadd2(x, st.x);
  uint32_t n = hfma2(d, st.y, hmul2(d, st.z));
  return hfma2(n, a, s);
}

__device__ __forceinline__ void wg_rs_n128_t1(float* d, uint32_t a0, uint32_t a1, uint32_t a2, uint32_t a3, uint64_t db, int sc) {
  asm volatile("{.reg .pred p; setp.ne.b32 p,%69,0; wgmma.mma_async.sync.aligned.m64n128k16.f32.bf16.bf16 {%0,%1,%2,%3,%4,%5,%6,%7,%8,%9,%10,%11,%12,%13,%14,%15,%16,%17,%18,%19,%20,%21,%22,%23,%24,%25,%26,%27,%28,%29,%30,%31,%32,%33,%34,%35,%36,%37,%38,%39,%40,%41,%42,%43,%44,%45,%46,%47,%48,%49,%50,%51,%52,%53,%54,%55,%56,%57,%58,%59,%60,%61,%62,%63}, {%64,%65,%66,%67}, %68, p,1,1,1;}"
  : "+f"(d[0]),"+f"(d[1]),"+f"(d[2]),"+f"(d[3]),"+f"(d[4]),"+f"(d[5]),"+f"(d[6]),"+f"(d[7]),"+f"(d[8]),"+f"(d[9]),"+f"(d[10]),"+f"(d[11]),"+f"(d[12]),"+f"(d[13]),"+f"(d[14]),"+f"(d[15]),"+f"(d[16]),"+f"(d[17]),"+f"(d[18]),"+f"(d[19]),"+f"(d[20]),"+f"(d[21]),"+f"(d[22]),"+f"(d[23]),"+f"(d[24]),"+f"(d[25]),"+f"(d[26]),"+f"(d[27]),"+f"(d[28]),"+f"(d[29]),"+f"(d[30]),"+f"(d[31]),"+f"(d[32]),"+f"(d[33]),"+f"(d[34]),"+f"(d[35]),"+f"(d[36]),"+f"(d[37]),"+f"(d[38]),"+f"(d[39]),"+f"(d[40]),"+f"(d[41]),"+f"(d[42]),"+f"(d[43]),"+f"(d[44]),"+f"(d[45]),"+f"(d[46]),"+f"(d[47]),"+f"(d[48]),"+f"(d[49]),"+f"(d[50]),"+f"(d[51]),"+f"(d[52]),"+f"(d[53]),"+f"(d[54]),"+f"(d[55]),"+f"(d[56]),"+f"(d[57]),"+f"(d[58]),"+f"(d[59]),"+f"(d[60]),"+f"(d[61]),"+f"(d[62]),"+f"(d[63]) : "r"(a0),"r"(a1),"r"(a2),"r"(a3),"l"(db),"r"(sc));
}
__device__ __forceinline__ void wg_rs_n24_t1(float* d, uint32_t a0, uint32_t a1, uint32_t a2, uint32_t a3, uint64_t db, int sc) {
  asm volatile("{.reg .pred p; setp.ne.b32 p,%17,0; wgmma.mma_async.sync.aligned.m64n24k16.f32.bf16.bf16 {%0,%1,%2,%3,%4,%5,%6,%7,%8,%9,%10,%11}, {%12,%13,%14,%15}, %16, p,1,1,1;}"
  : "+f"(d[0]),"+f"(d[1]),"+f"(d[2]),"+f"(d[3]),"+f"(d[4]),"+f"(d[5]),"+f"(d[6]),"+f"(d[7]),"+f"(d[8]),"+f"(d[9]),"+f"(d[10]),"+f"(d[11]) : "r"(a0),"r"(a1),"r"(a2),"r"(a3),"l"(db),"r"(sc));
}
__device__ __forceinline__ void wg_rs_n64_t0(float* d, uint32_t a0, uint32_t a1, uint32_t a2, uint32_t a3, uint64_t db, int sc) {
  asm volatile("{.reg .pred p; setp.ne.b32 p,%37,0; wgmma.mma_async.sync.aligned.m64n64k16.f32.bf16.bf16 {%0,%1,%2,%3,%4,%5,%6,%7,%8,%9,%10,%11,%12,%13,%14,%15,%16,%17,%18,%19,%20,%21,%22,%23,%24,%25,%26,%27,%28,%29,%30,%31}, {%32,%33,%34,%35}, %36, p,1,1,0;}"
  : "+f"(d[0]),"+f"(d[1]),"+f"(d[2]),"+f"(d[3]),"+f"(d[4]),"+f"(d[5]),"+f"(d[6]),"+f"(d[7]),"+f"(d[8]),"+f"(d[9]),"+f"(d[10]),"+f"(d[11]),"+f"(d[12]),"+f"(d[13]),"+f"(d[14]),"+f"(d[15]),"+f"(d[16]),"+f"(d[17]),"+f"(d[18]),"+f"(d[19]),"+f"(d[20]),"+f"(d[21]),"+f"(d[22]),"+f"(d[23]),"+f"(d[24]),"+f"(d[25]),"+f"(d[26]),"+f"(d[27]),"+f"(d[28]),"+f"(d[29]),"+f"(d[30]),"+f"(d[31]) : "r"(a0),"r"(a1),"r"(a2),"r"(a3),"l"(db),"r"(sc));
}
__device__ __forceinline__ void wg_rs_n64_t1(float* d, uint32_t a0, uint32_t a1, uint32_t a2, uint32_t a3, uint64_t db, int sc) {
  asm volatile("{.reg .pred p; setp.ne.b32 p,%37,0; wgmma.mma_async.sync.aligned.m64n64k16.f32.bf16.bf16 {%0,%1,%2,%3,%4,%5,%6,%7,%8,%9,%10,%11,%12,%13,%14,%15,%16,%17,%18,%19,%20,%21,%22,%23,%24,%25,%26,%27,%28,%29,%30,%31}, {%32,%33,%34,%35}, %36, p,1,1,1;}"
  : "+f"(d[0]),"+f"(d[1]),"+f"(d[2]),"+f"(d[3]),"+f"(d[4]),"+f"(d[5]),"+f"(d[6]),"+f"(d[7]),"+f"(d[8]),"+f"(d[9]),"+f"(d[10]),"+f"(d[11]),"+f"(d[12]),"+f"(d[13]),"+f"(d[14]),"+f"(d[15]),"+f"(d[16]),"+f"(d[17]),"+f"(d[18]),"+f"(d[19]),"+f"(d[20]),"+f"(d[21]),"+f"(d[22]),"+f"(d[23]),"+f"(d[24]),"+f"(d[25]),"+f"(d[26]),"+f"(d[27]),"+f"(d[28]),"+f"(d[29]),"+f"(d[30]),"+f"(d[31]) : "r"(a0),"r"(a1),"r"(a2),"r"(a3),"l"(db),"r"(sc));
}
__device__ __forceinline__ void wg_rs_n88_t1(float* d, uint32_t a0, uint32_t a1, uint32_t a2, uint32_t a3, uint64_t db, int sc) {
  asm volatile("{.reg .pred p; setp.ne.b32 p,%49,0; wgmma.mma_async.sync.aligned.m64n88k16.f32.bf16.bf16 {%0,%1,%2,%3,%4,%5,%6,%7,%8,%9,%10,%11,%12,%13,%14,%15,%16,%17,%18,%19,%20,%21,%22,%23,%24,%25,%26,%27,%28,%29,%30,%31,%32,%33,%34,%35,%36,%37,%38,%39,%40,%41,%42,%43}, {%44,%45,%46,%47}, %48, p,1,1,1;}"
  : "+f"(d[0]),"+f"(d[1]),"+f"(d[2]),"+f"(d[3]),"+f"(d[4]),"+f"(d[5]),"+f"(d[6]),"+f"(d[7]),"+f"(d[8]),"+f"(d[9]),"+f"(d[10]),"+f"(d[11]),"+f"(d[12]),"+f"(d[13]),"+f"(d[14]),"+f"(d[15]),"+f"(d[16]),"+f"(d[17]),"+f"(d[18]),"+f"(d[19]),"+f"(d[20]),"+f"(d[21]),"+f"(d[22]),"+f"(d[23]),"+f"(d[24]),"+f"(d[25]),"+f"(d[26]),"+f"(d[27]),"+f"(d[28]),"+f"(d[29]),"+f"(d[30]),"+f"(d[31]),"+f"(d[32]),"+f"(d[33]),"+f"(d[34]),"+f"(d[35]),"+f"(d[36]),"+f"(d[37]),"+f"(d[38]),"+f"(d[39]),"+f"(d[40]),"+f"(d[41]),"+f"(d[42]),"+f"(d[43]) : "r"(a0),"r"(a1),"r"(a2),"r"(a3),"l"(db),"r"(sc));
}
__device__ __forceinline__ void wg_ss_n72_t1(float* d, uint64_t da, uint64_t db, int sc) {
  asm volatile("{.reg .pred p; setp.ne.b32 p,%38,0; wgmma.mma_async.sync.aligned.m64n72k16.f32.bf16.bf16 {%0,%1,%2,%3,%4,%5,%6,%7,%8,%9,%10,%11,%12,%13,%14,%15,%16,%17,%18,%19,%20,%21,%22,%23,%24,%25,%26,%27,%28,%29,%30,%31,%32,%33,%34,%35}, %36, %37, p,1,1,0,1;}"
  : "+f"(d[0]),"+f"(d[1]),"+f"(d[2]),"+f"(d[3]),"+f"(d[4]),"+f"(d[5]),"+f"(d[6]),"+f"(d[7]),"+f"(d[8]),"+f"(d[9]),"+f"(d[10]),"+f"(d[11]),"+f"(d[12]),"+f"(d[13]),"+f"(d[14]),"+f"(d[15]),"+f"(d[16]),"+f"(d[17]),"+f"(d[18]),"+f"(d[19]),"+f"(d[20]),"+f"(d[21]),"+f"(d[22]),"+f"(d[23]),"+f"(d[24]),"+f"(d[25]),"+f"(d[26]),"+f"(d[27]),"+f"(d[28]),"+f"(d[29]),"+f"(d[30]),"+f"(d[31]),"+f"(d[32]),"+f"(d[33]),"+f"(d[34]),"+f"(d[35]) : "l"(da),"l"(db),"r"(sc));
}

#define POLY_MASK 0xB5u
#define QSCALE (0.23570226039551584f * 1.4426950408889634f)

__global__ void __launch_bounds__(256) k0_kernel(const __nv_bfloat16* __restrict__ x, const __nv_bfloat16* __restrict__ c,
                                                 const __nv_bfloat16* __restrict__ wmod) {
  if (threadIdx.x == 0) TS(0, 0);
  pdl_launch();
  const int tid = threadIdx.x, lane = tid & 31, warp = tid >> 5;
  if (blockIdx.x < 108) {
    __shared__ float red[8][32];
    const int col0 = blockIdx.x * 32 + (tid & 3) * 8, r0 = tid >> 2;
    uint4 w[9];
#pragma unroll
    for (int i = 0; i < 9; i++) w[i] = __ldg((const uint4*)(wmod + (size_t)(r0 + 64 * i) * 3456 + col0));
    float acc[8] = {0, 0, 0, 0, 0, 0, 0, 0};
#pragma unroll
    for (int i = 0; i < 9; i++) {
      float cv = __bfloat162float(c[r0 + 64 * i]);
      float sv = rbf(cv / (1.0f + __expf(-cv)));
      acc[0] += sv * bf_lo(w[i].x); acc[1] += sv * bf_hi(w[i].x);
      acc[2] += sv * bf_lo(w[i].y); acc[3] += sv * bf_hi(w[i].y);
      acc[4] += sv * bf_lo(w[i].z); acc[5] += sv * bf_hi(w[i].z);
      acc[6] += sv * bf_lo(w[i].w); acc[7] += sv * bf_hi(w[i].w);
    }
#pragma unroll
    for (int j = 0; j < 8; j++) {
      acc[j] += __shfl_xor_sync(~0u, acc[j], 4);
      acc[j] += __shfl_xor_sync(~0u, acc[j], 8);
      acc[j] += __shfl_xor_sync(~0u, acc[j], 16);
    }
    if (lane < 4) {
#pragma unroll
      for (int j = 0; j < 8; j++) red[warp][lane * 8 + j] = acc[j];
    }
    __syncthreads();
    if (tid < 32) {
      float s = 0;
#pragma unroll
      for (int j = 0; j < 8; j++) s += red[j][tid];
      s = rbf(s);
      int n = blockIdx.x * 32 + tid, part = n / DM, col = n % DM;
      if (part == 2) g_ga[col] = s;
      else if (part == 5) g_gb[col] = s;
      else {
        __nv_bfloat16* tab = (__nv_bfloat16*)(part < 2 ? g_tab1 : g_tab2);
        bool shift = (part == 0 || part == 3);
        int kk = col >> 4, half = (col >> 3) & 1, cq = (col & 7) >> 1, e = col & 1;
        tab[((kk * 4 + cq) * 4 + half * 2 + (shift ? 1 : 0)) * 2 + e] = __float2bfloat16_rn(shift ? s : 1.0f + s);
      }
    }
    if (blockIdx.x == 0 && tid >= 64 && tid < 64 + 80) g_cnt[tid - 64] = 0;
  } else {
    const int row0 = (blockIdx.x - 108) * 16 + warp * 2;
    uint32_t v[2][9];
#pragma unroll
    for (int r = 0; r < 2; r++)
#pragma unroll
      for (int i = 0; i < 9; i++) v[r][i] = __ldg((const uint32_t*)(x + (size_t)(row0 + r) * DM) + lane + 32 * i);
#pragma unroll
    for (int r = 0; r < 2; r++) {
      float s = 0;
#pragma unroll
      for (int i = 0; i < 9; i++) s += bf_lo(v[r][i]) + bf_hi(v[r][i]);
#pragma unroll
      for (int o = 16; o; o >>= 1) s += __shfl_xor_sync(~0u, s, o);
      float mean = s * (1.0f / DM), q = 0;
#pragma unroll
      for (int i = 0; i < 9; i++) {
        float a = bf_lo(v[r][i]) - mean, b = bf_hi(v[r][i]) - mean;
        q += a * a + b * b;
      }
#pragma unroll
      for (int o = 16; o; o >>= 1) q += __shfl_xor_sync(~0u, q, o);
      if (lane == 0) g_stat1[row0 + r] = ln_consts(mean, q * (1.0f / DM));
    }
  }
  if (threadIdx.x == 0) TS(0, 1);
}

#define NSTG 6
#define STG_BYTES 16384
#define R_BYTES (8 * 16384)
#define GEMM_SMEM (R_BYTES + NSTG * STG_BYTES + 1024 + 256)

struct Ring {
  uint32_t base, full, empty;
  int st;
  uint32_t ph;
  __device__ __forceinline__ void next() { if (++st == NSTG) { st = 0; ph ^= 1; } }
};

__device__ __forceinline__ void load_a_chunk(uint32_t (*a)[4], uint32_t chunk_base, int row_in_tile, int lane) {
  const int r = row_in_tile + (lane & 7) + ((lane >> 3) & 1) * 8;
  const uint32_t rb = chunk_base + r * 128;
#pragma unroll
  for (int k = 0; k < 4; k++) ldsm4(a[k], rb + (((k * 2 + (lane >> 4)) ^ (r & 7)) << 4));
}

#define MMA_TILE(FN, acc, a, ring, lane)                                        \
  {                                                                             \
    uint32_t prev_empty = 0;                                                    \
    _Pragma("unroll") for (int s = 0; s < 9; s++) {                             \
      mbar_wait(ring.full + ring.st * 8, ring.ph);                              \
      WG_FENCE();                                                               \
      uint32_t sa_ = ring.base + ring.st * STG_BYTES;                           \
      asm volatile("" : "+r"(sa_));                                             \
      uint64_t db = mkdesc(sa_, 8192, 1024, 1);                                 \
      _Pragma("unroll") for (int k = 0; k < 4; k++)                             \
          FN(acc, a[s * 4 + k][0], a[s * 4 + k][1], a[s * 4 + k][2], a[s * 4 + k][3], db + k * 128, (s | k) != 0); \
      WG_COMMIT();                                                              \
      if (s > 0) { WG_WAIT(1); if (lane == 0) mbar_arrive(prev_empty); }        \
      prev_empty = ring.empty + ring.st * 8;                                    \
      ring.next();                                                              \
    }                                                                           \
    WG_WAIT(0);                                                                 \
    if (lane == 0) mbar_arrive(prev_empty);                                     \
  }

template <int NG, int G0>
__device__ __forceinline__ void qkv_stage(const float* acc, uint32_t stg, int rowl, int cq, int col_base) {
  const float vs0 = ((POLY_MASK >> ((rowl >> 3) & 7)) & 1) ? -1.0f : 1.0f, vs1 = ((POLY_MASK >> (((rowl >> 3) + 1) & 7)) & 1) ? -1.0f : 1.0f;
#pragma unroll
  for (int i = 0; i < NG; i++) {
    const int cc = (G0 + i) * 8 + cq * 2;
    const int slot = (cc * 3641) >> 16, d = cc - slot * 18;
    const int gc = col_base + cc;
    const float sc0 = gc < DM ? QSCALE : (gc >= 2 * DM ? vs0 : 1.0f), sc1 = gc < DM ? QSCALE : (gc >= 2 * DM ? vs1 : 1.0f);
    const uint32_t ad = stg + slot * 6144 + (d >> 3) * 128 + (d & 7) * 2 + (rowl >> 3) * 384 + (rowl & 7) * 16;
    asm volatile("st.shared.b32 [%0],%1;" ::"r"(ad), "r"(pack_bf16(acc[4 * i] * sc0, acc[4 * i + 1] * sc0)) : "memory");
    asm volatile("st.shared.b32 [%0],%1;" ::"r"(ad + 384), "r"(pack_bf16(acc[4 * i + 2] * sc1, acc[4 * i + 3] * sc1)) : "memory");
  }
}

__global__ void __launch_bounds__(384, 1) k1_kernel(const __grid_constant__ CUtensorMap mx, const __grid_constant__ CUtensorMap mw) {
  extern __shared__ uint8_t smem_raw[];
  const uint32_t sb = (s2u(smem_raw) + 1023) & ~1023u;
  const uint32_t R = sb, RING = sb + R_BYTES, BAR = RING + NSTG * STG_BYTES;
  const uint32_t full = BAR, empty = BAR + 64, xfull = BAR + 128;
  const int tid = threadIdx.x, lane = tid & 31, warp = tid >> 5;
  const int mb = blockIdx.x >> 3, nb = blockIdx.x & 7;
  if (tid == 0) {
    TS(1, 0);
    for (int i = 0; i < NSTG; i++) { mbar_init(full + i * 8, 1); mbar_init(empty + i * 8, 8); }
    for (int i = 0; i < 8; i++) mbar_init(xfull + i * 8, 1);
    fence_bar_init();
  }
  __syncthreads();
  pdl_launch();
  if (warp >= 8) {
    REG_DEC(24);
    if (warp == 8) {
      if (lane == 0) {
        for (int c = 0; c < 8; c++) { mbar_expect(xfull + c * 8, 16384); tma2d(R + c * 16384, &mx, c * 64, mb * 128, xfull + c * 8); }
        mbar_expect(full, 16384);
        tma2d(RING, &mx, 512, mb * 128, full);
        int st = 1; uint32_t ph = 0;
        for (int it = 0; it < 18; it++) {
          const int t = it / 9, s = it - t * 9;
          mbar_wait(empty + st * 8, ph ^ 1);
          mbar_expect(full + st * 8, 16384);
          tma2d(RING + st * STG_BYTES, &mw, nb * 216 + t * 128, s * 64, full + st * 8);
          tma2d(RING + st * STG_BYTES + 8192, &mw, nb * 216 + t * 128 + 64, s * 64, full + st * 8);
          if (++st == NSTG) { st = 0; ph ^= 1; }
        }
      }
      pdl_wait();
    } else {
      const int ht = tid - 288;
      bar_sync(1, 352);
      for (int i = ht; i < 12 * 128; i += 96) {
        const int slot = i >> 7, row = i & 127, type = (nb * 12 + slot) >> 5;
        uint32_t v = 0;
        if (type == 1) v = 0x3F80u | (((POLY_MASK >> ((row >> 3) & 7)) & 1) ? 0x43C00000u : 0x3F800000u);
        if (type == 2) v = ((POLY_MASK >> ((row >> 3) & 7)) & 1) ? 0xBF80u : 0x3F80u;
        const uint32_t ad = R + slot * 6144 + (row >> 3) * 384 + 256 + (row & 7) * 16;
        asm volatile("st.shared.b32 [%0],%1;" ::"r"(ad + 4), "r"(v) : "memory");
        asm volatile("st.shared.v2.b32 [%0],{%1,%1};" ::"r"(ad + 8), "r"(0) : "memory");
      }
      fence_async_smem();
      pdl_wait();
#pragma unroll 1
      for (int t = 0; t < 2; t++) {
        bar_sync(2 + t, 352);
        const int s0 = t ? 7 : 0, s1 = t ? 12 : 7;
        if (ht == 0) {
          for (int s = s0; s < s1; s++) bulk_s2g(g_qkv + (size_t)(nb * 12 + s) * 98304 + mb * 6144, R + s * 6144, 6144);
          bulk_commit();
        }
        for (int s = s0 + (warp - 9); s < s1; s += 3) {
          const int gs = nb * 12 + s;
          if ((gs >> 5) != 1) continue;
          float mx2 = 0;
#pragma unroll 1
          for (int row = lane; row < 128; row += 32) {
            const uint32_t ad = R + s * 6144 + (row >> 3) * 384 + (row & 7) * 16;
            float q = 0;
#pragma unroll 1
            for (int ch = 0; ch < 3; ch++) {
              uint32_t u0, u1, u2, u3;
              asm volatile("ld.shared.v4.b32 {%0,%1,%2,%3},[%4];" : "=r"(u0), "=r"(u1), "=r"(u2), "=r"(u3) : "r"(ad + ch * 128));
              if (ch == 2) u1 = 0;
              q += bf_lo(u0) * bf_lo(u0) + bf_hi(u0) * bf_hi(u0) + bf_lo(u1) * bf_lo(u1) + bf_hi(u1) * bf_hi(u1);
              q += bf_lo(u2) * bf_lo(u2) + bf_hi(u2) * bf_hi(u2) + bf_lo(u3) * bf_lo(u3) + bf_hi(u3) * bf_hi(u3);
            }
            mx2 = (q > mx2 || q != q) ? q : mx2;
            if (mx2 != mx2) mx2 = __int_as_float(0x7f800000);
          }
#pragma unroll
          for (int o = 16; o; o >>= 1) mx2 = fmaxf(mx2, __shfl_xor_sync(~0u, mx2, o));
          if (lane == 0) g_kmax[(gs & 31) * 16 + mb] = mx2;
        }
      }
      if (ht == 0) bulk_wait0();
      if (ht == 0) TS(1, 8);
    }
  } else {
    REG_INC(240);
    uint32_t a[36][4];
    const int rowl = warp * 16;
#pragma unroll
    for (int c = 0; c < 8; c++) { mbar_wait(xfull + c * 8, 0); load_a_chunk(&a[c * 4], R + c * 16384, rowl, lane); }
    mbar_wait(full, 0);
    load_a_chunk(&a[32], RING, rowl, lane);
    __syncwarp();
    if (lane == 0) mbar_arrive(empty);
    bar_arrive(1, 352);
    if (tid == 0) TS(1, 1);
    pdl_wait();
    if (tid == 0) TS(1, 2);
    {
      const int g = lane >> 2, cq = lane & 3;
      const uint4 s0 = g_stat1[mb * 128 + rowl + g], s1 = g_stat1[mb * 128 + rowl + g + 8];
#pragma unroll
      for (int k = 0; k < 36; k++) {
        if ((k & 3) == 0) asm volatile("" ::: "memory");
        const uint4 t = g_tab1[k * 4 + cq];
        a[k][0] = ln_apply(a[k][0], s0, t.x, t.y);
        a[k][1] = ln_apply(a[k][1], s1, t.x, t.y);
        a[k][2] = ln_apply(a[k][2], s0, t.z, t.w);
        a[k][3] = ln_apply(a[k][3], s1, t.z, t.w);
      }
    }
    bar_sync(4, 256);
    Ring ring{RING, full, empty, 1, 0};
    float acc[64];
    if (tid == 0) TS(1, 3);
    MMA_TILE(wg_rs_n128_t1, acc, a, ring, lane);
    if (tid == 0) TS(1, 4);
    qkv_stage<16, 0>(acc, R, rowl + (lane >> 2), lane & 3, nb * 216);
    fence_async_smem();
    bar_arrive(2, 352);
    if (tid == 0) TS(1, 5);
    MMA_TILE(wg_rs_n88_t1, acc, a, ring, lane);
    if (tid == 0) TS(1, 6);
    qkv_stage<11, 16>(acc, R, rowl + (lane >> 2), lane & 3, nb * 216);
    fence_async_smem();
    bar_arrive(3, 352);
    if (tid == 0) TS(1, 7);
  }
}

#define ATT_SMEM (2 * 98304 + 1024 + 256)

__device__ __forceinline__ uint32_t exp2_pair_fma(float t0, float t1, uint32_t one2) {
  uint32_t y, m;
  asm("prmt.b32 %0,%1,%2,0x6521;" : "=r"(y) : "r"(__float_as_uint(t0)), "r"(__float_as_uint(t1)));
  asm("lop3.b32 %0,%1,0x007F007F,%2,0xEA;" : "=r"(m) : "r"(y), "r"(one2));
  const uint32_t w = hfma2(m, 0x3EF73EF7u, 0xBF37BF37u);
  const uint32_t h = hfma2(w, w, 0xBD63BD63u);
  return hfma2(y, h, y);
}

__device__ __forceinline__ void softmax_fast(const float* s, uint32_t* p, uint32_t one2) {
#pragma unroll
  for (int i = 0; i < 8; i++) {
    if ((POLY_MASK >> i) & 1) {
      p[2 * i] = exp2_pair_fma(s[4 * i], s[4 * i + 1], one2);
      p[2 * i + 1] = exp2_pair_fma(s[4 * i + 2], s[4 * i + 3], one2);
    } else {
      p[2 * i] = pack_bf16(ex2f(s[4 * i]), ex2f(s[4 * i + 1]));
      p[2 * i + 1] = pack_bf16(ex2f(s[4 * i + 2]), ex2f(s[4 * i + 3]));
    }
  }
}
#define QK_MMA(S, kaddr)                                                        \
  wg_rs_n64_t0(S, q[0], q[1], q[2], q[3], dk0 + (uint64_t)(kaddr), 0);       \
  wg_rs_n64_t0(S, q[4], q[5], q[6], q[7], dk1 + (uint64_t)(kaddr), 1);
#define PV_MMA(P, vaddr)                                                        \
  _Pragma("unroll") for (int t = 0; t < 4; t++)                                 \
      wg_rs_n24_t1(o, P[4 * t], P[4 * t + 1], P[4 * t + 2], P[4 * t + 3], dv + (uint64_t)(vaddr) + t * 48, 1);

__device__ __forceinline__ float sq2(uint32_t v) { return bf_lo(v) * bf_lo(v) + bf_hi(v) * bf_hi(v); }
__device__ __forceinline__ void att_store(const float* o, int row0, int head, int lane) {
  const int cq = lane & 3;
  const float l0 = __shfl_sync(~0u, o[8], (lane & ~3) | 1), l1 = __shfl_sync(~0u, o[10], (lane & ~3) | 1);
  const float i0 = 1.0f / l0, i1 = 1.0f / l1;
  uint32_t* og = (uint32_t*)(g_o + (size_t)row0 * DM + head * 18 + cq * 2);
  og[0] = pack_bf16(o[0] * i0, o[1] * i0);
  og[4] = pack_bf16(o[4] * i0, o[5] * i0);
  og[8 * DM / 2] = pack_bf16(o[2] * i1, o[3] * i1);
  og[8 * DM / 2 + 4] = pack_bf16(o[6] * i1, o[7] * i1);
  if (cq == 0) {
    og[8] = pack_bf16(o[8] * i0, o[9] * i0);
    og[8 * DM / 2 + 8] = pack_bf16(o[10] * i1, o[11] * i1);
  }
}

__global__ void __launch_bounds__(512, 1) k2_kernel() {
  extern __shared__ uint8_t smem_raw[];
  const uint32_t sb = (s2u(smem_raw) + 1023) & ~1023u;
  const uint32_t KS = sb, VS = sb + 98304, BAR = sb + 2 * 98304;
  const int tid = threadIdx.x, lane = tid & 31, warp = tid >> 5, wg = tid >> 7;
  const int head = blockIdx.x >> 2, qb = blockIdx.x & 3;
  if (tid == 0) {
    TS(2, 0);
    for (int i = 0; i < 16; i++) mbar_init(BAR + i * 8, 1);
    fence_bar_init();
  }
  __syncthreads();
  pdl_launch();
  const int g = lane >> 2, cq = lane & 3;
  const int row0 = qb * 512 + wg * 128 + (warp & 3) * 16 + g;
  const uint8_t* qg = g_qkv + (size_t)head * 98304 + (row0 >> 3) * 384 + (row0 & 7) * 16 + cq * 4;
  pdl_wait();
  if (tid == 0) TS(2, 1);
  if (warp == 0 && lane < 16) {
    const uint8_t* kg = g_qkv + (size_t)(32 + head) * 98304 + lane * 6144;
    mbar_expect(BAR + lane * 8, 12288);
    bulk_g2s(KS + lane * 6144, kg, 6144, BAR + lane * 8);
    bulk_g2s(VS + lane * 6144, kg + 32 * 98304, 6144, BAR + lane * 8);
  }
  uint32_t q[8], q2[6];
  float kmax2 = __ldcg(g_kmax + head * 16 + (lane & 15));
#pragma unroll
  for (int i = 0; i < 6; i++) {
    q[i] = __ldcg((const uint32_t*)(qg + (i & 1) * 384 + (i >> 1) * 128));
    q2[i] = __ldcg((const uint32_t*)(qg + 3072 + (i & 1) * 384 + (i >> 1) * 128));
  }
  q[6] = __ldcg((const uint32_t*)(qg + 256 + 12 - cq * 4)); q[7] = __ldcg((const uint32_t*)(qg + 256 + 8 - cq * 4));
  const uint64_t dk0 = mkdesc(KS, 128, 384, 0), dk1 = mkdesc(KS + 256, 0, 384, 0), dv = mkdesc(VS, 384, 128, 0);
#pragma unroll
  for (int o = 8; o; o >>= 1) kmax2 = fmaxf(kmax2, __shfl_xor_sync(~0u, kmax2, o));
  float bd[4] = {sq2(q[0]) + sq2(q[2]) + sq2(q[4]), sq2(q[1]) + sq2(q[3]) + sq2(q[5]),
                 sq2(q2[0]) + sq2(q2[2]) + sq2(q2[4]), sq2(q2[1]) + sq2(q2[3]) + sq2(q2[5])};
  int ok = 1;
#pragma unroll
  for (int i = 0; i < 4; i++) {
    bd[i] += __shfl_xor_sync(~0u, bd[i], 1); bd[i] += __shfl_xor_sync(~0u, bd[i], 2);
    bd[i] = sqrtf(bd[i] * kmax2) * 1.01f + 1.0f;
    ok = ok && (bd[i] <= 62.0f);
  }
  {
    uint32_t all;
    asm volatile("{.reg .pred p,q; setp.ne.b32 p,%1,0; barrier.red.and.pred q,%2,128,p; selp.u32 %0,1,0,q;}"
                 : "=r"(all) : "r"(ok), "r"(1 + wg) : "memory");
    ok = __all_sync(~0u, all);
  }
  float o[12];
#pragma unroll
  for (int i = 0; i < 12; i++) { o[i] = 0.f; asm volatile("" : "+f"(o[i])); }
  float s[32];
  uint32_t p[16];
  if (tid == 0) TS(2, 2);
  if (ok) {
    if (cq == 1) {
      q[4] = pack_bf16(-bd[0], 1.0f); q[5] = pack_bf16(-bd[1], 1.0f);
      q2[4] = pack_bf16(-bd[2], 1.0f); q2[5] = pack_bf16(-bd[3], 1.0f);
    }
    uint32_t one2 = 0x3F803F80u;
    asm volatile("" : "+r"(one2));
    mbar_wait(BAR, 0);
    WG_FENCE();
    QK_MMA(s, 0u);
    WG_COMMIT();
#pragma unroll 1
    for (int it = 0; it < 64; it++) {
      const int j = it & 31;
      WG_WAIT(0);
      fence_regs<32>(s); fence_regs<12>(o);
      if (it == 32) { att_store(o, row0, head, lane); if (tid == 0) TS(2, 3); }
      if (it == 31) {
#pragma unroll
        for (int i = 0; i < 6; i++) q[i] = q2[i];
      }
      softmax_fast(s, p, one2);
      if (it < 31 && (it & 1)) mbar_wait(BAR + (it + 1) * 4, 0);
      WG_FENCE();
      wg_rs_n24_t1(o, p[0], p[1], p[2], p[3], dv + (uint64_t)(j * 192), j);
#pragma unroll
      for (int t = 1; t < 4; t++) wg_rs_n24_t1(o, p[4 * t], p[4 * t + 1], p[4 * t + 2], p[4 * t + 3], dv + (uint64_t)(j * 192) + t * 48, 1);
      QK_MMA(s, (uint32_t)((it + 1) & 31) * 192);
      WG_COMMIT();
    }
    WG_WAIT(0);
    fence_regs<12>(o);
    att_store(o, row0 + 64, head, lane);
  } else {
#pragma unroll 1
    for (int tile = 0; tile < 2; tile++) {
      float m0 = -INFINITY, m1 = -INFINITY;
#pragma unroll 1
      for (int j = 0; j < 32; j++) {
        mbar_wait(BAR + (j >> 1) * 8, 0);
        WG_FENCE();
        QK_MMA(s, (uint32_t)j * 192);
        WG_COMMIT();
        WG_WAIT(0);
        float x0 = m0, x1 = m1;
#pragma unroll
        for (int i = 0; i < 8; i++) {
          x0 = fmaxf(x0, fmaxf(s[4 * i], s[4 * i + 1]));
          x1 = fmaxf(x1, fmaxf(s[4 * i + 2], s[4 * i + 3]));
        }
        x0 = fmaxf(x0, __shfl_xor_sync(~0u, x0, 1)); x0 = fmaxf(x0, __shfl_xor_sync(~0u, x0, 2));
        x1 = fmaxf(x1, __shfl_xor_sync(~0u, x1, 1)); x1 = fmaxf(x1, __shfl_xor_sync(~0u, x1, 2));
        const float c0 = ex2f(m0 - x0), c1 = ex2f(m1 - x1);
        m0 = x0; m1 = x1;
#pragma unroll
        for (int i = 0; i < 3; i++) { o[4 * i] *= c0; o[4 * i + 1] *= c0; o[4 * i + 2] *= c1; o[4 * i + 3] *= c1; }
#pragma unroll
        for (int i = 0; i < 8; i++) {
          const uint32_t sg = ((POLY_MASK >> i) & 1) ? 0x80008000u : 0u;
          p[2 * i] = pack_bf16(ex2f(s[4 * i] - x0), ex2f(s[4 * i + 1] - x0)) ^ sg;
          p[2 * i + 1] = pack_bf16(ex2f(s[4 * i + 2] - x1), ex2f(s[4 * i + 3] - x1)) ^ sg;
        }
        WG_FENCE();
        PV_MMA(p, (uint32_t)j * 192);
        WG_COMMIT();
        WG_WAIT(0);
      }
      att_store(o, row0 + tile * 64, head, lane);
#pragma unroll
      for (int i = 0; i < 12; i++) o[i] = 0.f;
#pragma unroll
      for (int i = 0; i < 6; i++) q[i] = q2[i];
    }
  }
  if (tid == 0) TS(2, 4);
}

#define K3_NSTG 4
#define K3_SMEM (9 * 16384 + K3_NSTG * 16384 + 1024 + 256)
__global__ void __launch_bounds__(288, 1) k3_kernel(const __grid_constant__ CUtensorMap mo, const __grid_constant__ CUtensorMap mw,
                                                    const __nv_bfloat16* __restrict__ x) {
  extern __shared__ uint8_t smem_raw[];
  const uint32_t sb = (s2u(smem_raw) + 1023) & ~1023u;
  const uint32_t A = sb, RING = sb + 9 * 16384, BAR = RING + K3_NSTG * 16384;
  const uint32_t full = BAR, empty = BAR + 64, afull = BAR + 128;
  const int tid = threadIdx.x, lane = tid & 31, warp = tid >> 5;
  const int mb = blockIdx.x >> 3, nb = blockIdx.x & 7;
  if (tid == 0) {
    TS(3, 0);
    for (int i = 0; i < K3_NSTG; i++) { mbar_init(full + i * 8, 1); mbar_init(empty + i * 8, 8); }
    for (int i = 0; i < 9; i++) mbar_init(afull + i * 8, 1);
    fence_bar_init();
  }
  __syncthreads();
  pdl_launch();
  if (warp == 8) {
    if (lane == 0) {
      for (int s = 0; s < K3_NSTG; s++) {
        mbar_expect(full + s * 8, 16384);
        tma2d(RING + s * 16384, &mw, nb * 72, s * 64, full + s * 8);
        tma2d(RING + s * 16384 + 8192, &mw, nb * 72 + 64, s * 64, full + s * 8);
      }
      pdl_wait();
      for (int c = 0; c < 9; c++) { mbar_expect(afull + c * 8, 16384); tma2d(A + c * 16384, &mo, c * 64, mb * 128, afull + c * 8); }
      for (int s = K3_NSTG; s < 9; s++) {
        const int st = s % K3_NSTG;
        mbar_wait(empty + st * 8, ((s / K3_NSTG) & 1) ^ 1);
        mbar_expect(full + st * 8, 16384);
        tma2d(RING + st * 16384, &mw, nb * 72, s * 64, full + st * 8);
        tma2d(RING + st * 16384 + 8192, &mw, nb * 72 + 64, s * 64, full + st * 8);
      }
    }
  } else {
    const int g = lane >> 2, cq = lane & 3;
    const int row = mb * 128 + warp * 16 + g, col = nb * 72 + cq * 2;
    uint32_t xv[18];
#pragma unroll
    for (int i = 0; i < 9; i++) {
      xv[2 * i] = __ldg((const uint32_t*)(x + (size_t)row * DM + col + 8 * i));
      xv[2 * i + 1] = __ldg((const uint32_t*)(x + (size_t)(row + 8) * DM + col + 8 * i));
    }
    pdl_wait();
    if (tid == 0) TS(3, 1);
    float2 ga[9];
#pragma unroll
    for (int i = 0; i < 9; i++) ga[i] = *(const float2*)(g_ga + col + 8 * i);
    float acc[36];
    const uint32_t abase = A + (warp >> 2) * 8192;
#pragma unroll
    for (int s = 0; s < 9; s++) {
      const int st = s % K3_NSTG;
      mbar_wait(afull + s * 8, 0);
      mbar_wait(full + st * 8, (s / K3_NSTG) & 1);
      WG_FENCE();
#pragma unroll
      for (int k = 0; k < 4; k++)
        wg_ss_n72_t1(acc, mkdesc(abase + s * 16384 + k * 32, 16, 1024, 1), mkdesc(RING + st * 16384 + k * 2048, 8192, 1024, 1), (s | k) != 0);
      WG_COMMIT();
      if (s > 0) { WG_WAIT(1); if (lane == 0) mbar_arrive(empty + ((s - 1) % K3_NSTG) * 8); }
    }
    WG_WAIT(0);
    if (tid == 0) TS(3, 2);
    float s0 = 0, s1 = 0;
#pragma unroll
    for (int i = 0; i < 9; i++) {
      acc[4 * i] = rbf(bf_lo(xv[2 * i]) + rbf(ga[i].x * rbf(acc[4 * i])));
      acc[4 * i + 1] = rbf(bf_hi(xv[2 * i]) + rbf(ga[i].y * rbf(acc[4 * i + 1])));
      acc[4 * i + 2] = rbf(bf_lo(xv[2 * i + 1]) + rbf(ga[i].x * rbf(acc[4 * i + 2])));
      acc[4 * i + 3] = rbf(bf_hi(xv[2 * i + 1]) + rbf(ga[i].y * rbf(acc[4 * i + 3])));
      *(uint32_t*)(g_x1 + (size_t)row * DM + col + 8 * i) = pack_bf16(acc[4 * i], acc[4 * i + 1]);
      *(uint32_t*)(g_x1 + (size_t)(row + 8) * DM + col + 8 * i) = pack_bf16(acc[4 * i + 2], acc[4 * i + 3]);
      s0 += acc[4 * i] + acc[4 * i + 1];
      s1 += acc[4 * i + 2] + acc[4 * i + 3];
    }
    s0 += __shfl_xor_sync(~0u, s0, 1); s0 += __shfl_xor_sync(~0u, s0, 2);
    s1 += __shfl_xor_sync(~0u, s1, 1); s1 += __shfl_xor_sync(~0u, s1, 2);
    const float m0 = s0 * (1.0f / 72), m1 = s1 * (1.0f / 72);
    float q0 = 0, q1 = 0;
#pragma unroll
    for (int i = 0; i < 9; i++) {
      q0 += (acc[4 * i] - m0) * (acc[4 * i] - m0) + (acc[4 * i + 1] - m0) * (acc[4 * i + 1] - m0);
      q1 += (acc[4 * i + 2] - m1) * (acc[4 * i + 2] - m1) + (acc[4 * i + 3] - m1) * (acc[4 * i + 3] - m1);
    }
    q0 += __shfl_xor_sync(~0u, q0, 1); q0 += __shfl_xor_sync(~0u, q0, 2);
    q1 += __shfl_xor_sync(~0u, q1, 1); q1 += __shfl_xor_sync(~0u, q1, 2);
    if (cq == 0) {
      g_stat2[row * 8 + nb] = make_float2(m0, q0);
      g_stat2[(row + 8) * 8 + nb] = make_float2(m1, q1);
    }
    if (tid == 0) TS(3, 3);
  }
}

__device__ __forceinline__ uint4 ln2_consts(int row, int cq) {
  const float4 p = *(const float4*)(g_stat2 + row * 8 + cq * 2);
  float s = p.x + p.z;
  s += __shfl_xor_sync(~0u, s, 1); s += __shfl_xor_sync(~0u, s, 2);
  const float mean = s * 0.125f;
  float q = p.y + p.w + 72.0f * ((p.x - mean) * (p.x - mean) + (p.z - mean) * (p.z - mean));
  q += __shfl_xor_sync(~0u, q, 1); q += __shfl_xor_sync(~0u, q, 2);
  return ln_consts(mean, q * (1.0f / DM));
}
__device__ __forceinline__ uint32_t glu_pair(float g0, float g1, float u0, float u1) {
  const float s0 = fmaf(tanhf_fast(0.5f * g0), 0.5f, 0.5f), s1 = fmaf(tanhf_fast(0.5f * g1), 0.5f, 0.5f);
  return pack_bf16(s0 * u0, s1 * u1);
}
template <int NG>
__device__ __forceinline__ void stage_part(const float* acc, uint32_t stg, int wrow, int lane) {
  const int r = wrow + (lane & 7) + ((lane >> 3) & 1) * 8;
#pragma unroll
  for (int i = 0; i < NG; i += 2) {
    const int ch = i + (lane >> 4);
    stsm4(stg + r * 256 + ((ch ^ (r & 7)) << 4), pack_bf16(acc[4 * i], acc[4 * i + 1]), pack_bf16(acc[4 * i + 2], acc[4 * i + 3]),
          pack_bf16(acc[4 * i + 4], acc[4 * i + 5]), pack_bf16(acc[4 * i + 6], acc[4 * i + 7]));
  }
}

__global__ void __launch_bounds__(384, 1) k4_kernel(const __grid_constant__ CUtensorMap mx, const __grid_constant__ CUtensorMap mg,
                                                    const __grid_constant__ CUtensorMap mu, const __grid_constant__ CUtensorMap md,
                                                    __nv_bfloat16* __restrict__ out) {
  extern __shared__ uint8_t smem_raw[];
  const uint32_t sb = (s2u(smem_raw) + 1023) & ~1023u;
  const uint32_t R = sb, RING = sb + R_BYTES, BAR = RING + NSTG * STG_BYTES;
  const uint32_t full = BAR, empty = BAR + 64, xfull = BAR + 128, sfull = BAR + 192, sfree = BAR + 208;
  const int tid = threadIdx.x, lane = tid & 31, warp = tid >> 5;
  const int mb = blockIdx.x >> 3, fb = blockIdx.x & 7;
  if (tid == 0) {
    TS(4, 0);
    for (int i = 0; i < 2; i++) { mbar_init(sfull + i * 8, 4); mbar_init(sfree + i * 8, 1); }
    for (int i = 0; i < NSTG; i++) { mbar_init(full + i * 8, 1); mbar_init(empty + i * 8, 8); }
    for (int i = 0; i < 8; i++) mbar_init(xfull + i * 8, 1);
    fence_bar_init();
  }
  __syncthreads();
  if (warp >= 8) {
    REG_DEC(24);
    if (warp == 8) {
      if (lane == 0) {
        int st = 1; uint32_t ph = 0;
        for (int it = 0; it < 126; it++) {
          if (it == NSTG - 1) {
            pdl_wait();
            for (int c = 0; c < 8; c++) { mbar_expect(xfull + c * 8, 16384); tma2d(R + c * 16384, &mx, c * 64, mb * 128, xfull + c * 8); }
            mbar_expect(full, 16384);
            tma2d(RING, &mx, 512, mb * 128, full);
          }
          const int t = it / 9, s = it - t * 9;
          const uint32_t dst = RING + st * STG_BYTES, fb_ = full + st * 8;
          mbar_wait(empty + st * 8, ph ^ 1);
          if (t < 9) {
            mbar_expect(fb_, 16384);
            tma2d(dst, &mg, fb * 576 + t * 64, s * 64, fb_);
            tma2d(dst + 8192, &mu, fb * 576 + t * 64, s * 64, fb_);
          } else {
            mbar_expect(fb_, t < 13 ? 16384 : 8192);
            tma2d(dst, &md, (t - 9) * 128, fb * 576 + s * 64, fb_);
            if (t < 13) tma2d(dst + 8192, &md, (t - 9) * 128 + 64, fb * 576 + s * 64, fb_);
          }
          if (++st == NSTG) { st = 0; ph ^= 1; }
        }
      }
    } else {
      if (warp < 11 && lane == 0) {
        const int wg = warp - 9;
#pragma unroll 1
        for (int p = 0; p < 5; p++) {
          mbar_wait(sfull + wg * 8, p & 1);
          bulk_s2g(g_part + ((size_t)((fb * 16 + mb) * 5 + p) * 2 + wg) * 16384, R + ((p & 3) * 2 + wg) * 16384, 16384);
          bulk_commit();
          bulk_wait0();
          asm volatile("fence.proxy.async;" ::: "memory");
          asm volatile("red.release.gpu.global.add.u32 [%0],1;" ::"l"(g_cnt + mb * 5 + p) : "memory");
          if (p == 0) mbar_arrive(sfree + wg * 8);
        }
      }
    }
  } else {
    REG_INC(240);
    uint32_t a[36][4];
    const int rowl = warp * 16, wg = warp >> 2;
    pdl_wait();
    if (tid == 0) TS(4, 1);
    {
      const int g = lane >> 2, cq = lane & 3;
      const uint4 s0 = ln2_consts(mb * 128 + rowl + g, cq), s1 = ln2_consts(mb * 128 + rowl + g + 8, cq);
#pragma unroll
      for (int c = 0; c < 9; c++) {
        if (c < 8) { mbar_wait(xfull + c * 8, 0); load_a_chunk(&a[c * 4], R + c * 16384, rowl, lane); }
        else { mbar_wait(full, 0); load_a_chunk(&a[32], RING, rowl, lane); __syncwarp(); if (lane == 0) mbar_arrive(empty); }
#pragma unroll
        for (int k = c * 4; k < c * 4 + 4; k++) {
          const uint4 t = g_tab2[k * 4 + cq];
          a[k][0] = ln_apply(a[k][0], s0, t.x, t.y);
          a[k][1] = ln_apply(a[k][1], s1, t.x, t.y);
          a[k][2] = ln_apply(a[k][2], s0, t.z, t.w);
          a[k][3] = ln_apply(a[k][3], s1, t.z, t.w);
        }
      }
    }
    bar_sync(4, 256);
    if (tid == 0) TS(4, 2);
    Ring ring{RING, full, empty, 1, 0};
    float acc[64];
    const uint32_t hsp = R + tid * 16;
#pragma unroll 1
    for (int t = 0; t < 8; t++) {
      MMA_TILE(wg_rs_n128_t1, acc, a, ring, lane);
#pragma unroll
      for (int j = 0; j < 4; j++) {
        uint32_t h[4];
#pragma unroll
        for (int e = 0; e < 4; e++) h[e] = glu_pair(acc[8 * j + 2 * e], acc[8 * j + 2 * e + 1], acc[32 + 8 * j + 2 * e], acc[32 + 8 * j + 2 * e + 1]);
        asm volatile("st.shared.v4.b32 [%0],{%1,%2,%3,%4};" ::"r"(hsp + t * 16384 + j * 4096), "r"(h[0]), "r"(h[1]), "r"(h[2]), "r"(h[3]) : "memory");
      }
    }
    MMA_TILE(wg_rs_n128_t1, acc, a, ring, lane);
#pragma unroll
    for (int j = 0; j < 4; j++)
#pragma unroll
      for (int e = 0; e < 4; e++)
        a[32 + j][e] = glu_pair(acc[8 * j + 2 * e], acc[8 * j + 2 * e + 1], acc[32 + 8 * j + 2 * e], acc[32 + 8 * j + 2 * e + 1]);
#pragma unroll
    for (int k = 0; k < 32; k++)
      asm volatile("ld.shared.v4.b32 {%0,%1,%2,%3},[%4];" : "=r"(a[k][0]), "=r"(a[k][1]), "=r"(a[k][2]), "=r"(a[k][3]) : "r"(hsp + k * 4096) : "memory");
    if (tid == 0) TS(4, 3);
    bar_sync(4, 256);
    if (tid == 0) TS(4, 4);
#pragma unroll 1
    for (int p = 0; p < 4; p++) {
      MMA_TILE(wg_rs_n128_t1, acc, a, ring, lane);
      stage_part<16>(acc, R + (p * 2 + wg) * 16384, (warp & 3) * 16, lane);
      fence_async_smem();
      __syncwarp();
      if (lane == 0) mbar_arrive(sfull + wg * 8);
    }
    MMA_TILE(wg_rs_n64_t1, acc, a, ring, lane);
    mbar_wait(sfree + wg * 8, 0);
    stage_part<8>(acc, R + wg * 16384, (warp & 3) * 16, lane);
    fence_async_smem();
    __syncwarp();
    if (lane == 0) mbar_arrive(sfull + wg * 8);
    if (tid == 0) TS(4, 5);
    const int rl = fb * 16 + (tid >> 4), ch = tid & 15;
    const uint8_t* src = g_part + ((size_t)(mb * 5) * 2 + (rl >> 6)) * 16384 + (rl & 63) * 256 + ((ch ^ (rl & 7)) << 4);
    const size_t off = (size_t)(mb * 128 + rl) * DM + ch * 8;
#pragma unroll
    for (int p = 0; p < 5; p++) {
      if (p == 4 && ch >= 8) break;
      const uint4 xv = *(const uint4*)(g_x1 + off + p * 128);
      const float4 g0 = *(const float4*)(g_gb + p * 128 + ch * 8), g1 = *(const float4*)(g_gb + p * 128 + ch * 8 + 4);
      if (p == 0 || p == 4) {
        const int pl = p == 0 ? 3 : 4;
        for (int pp = p; pp <= pl; pp++) {
          unsigned int v; int n = 0;
          do {
            asm volatile("ld.acquire.gpu.global.u32 %0,[%1];" : "=r"(v) : "l"(g_cnt + mb * 5 + pp) : "memory");
          } while (v < 16 && ++n < 20000000);
          if (v < 16) __trap();
        }
      }
      uint4 v[8];
#pragma unroll
      for (int f = 0; f < 8; f++) v[f] = __ldcg((const uint4*)(src + p * 32768 + (size_t)f * (16 * 5 * 2 * 16384)));
      float r8[8] = {0, 0, 0, 0, 0, 0, 0, 0};
#pragma unroll
      for (int f = 0; f < 8; f++) {
        r8[0] += bf_lo(v[f].x); r8[1] += bf_hi(v[f].x); r8[2] += bf_lo(v[f].y); r8[3] += bf_hi(v[f].y);
        r8[4] += bf_lo(v[f].z); r8[5] += bf_hi(v[f].z); r8[6] += bf_lo(v[f].w); r8[7] += bf_hi(v[f].w);
      }
      uint4 r;
      r.x = pack_bf16(bf_lo(xv.x) + rbf(g0.x * rbf(r8[0])), bf_hi(xv.x) + rbf(g0.y * rbf(r8[1])));
      r.y = pack_bf16(bf_lo(xv.y) + rbf(g0.z * rbf(r8[2])), bf_hi(xv.y) + rbf(g0.w * rbf(r8[3])));
      r.z = pack_bf16(bf_lo(xv.z) + rbf(g1.x * rbf(r8[4])), bf_hi(xv.z) + rbf(g1.y * rbf(r8[5])));
      r.w = pack_bf16(bf_lo(xv.w) + rbf(g1.z * rbf(r8[6])), bf_hi(xv.w) + rbf(g1.w * rbf(r8[7])));
      *(uint4*)(out + off + p * 128) = r;
      if (tid == 0 && p >= 3) TS(4, 3 + p);
    }
  }
}

typedef CUresult (*EncodeFn)(CUtensorMap*, CUtensorMapDataType, cuuint32_t, void*, const cuuint64_t*, const cuuint64_t*,
                             const cuuint32_t*, const cuuint32_t*, CUtensorMapInterleave, CUtensorMapSwizzle,
                             CUtensorMapL2promotion, CUtensorMapFloatOOBfill);
static void make_map(EncodeFn fn, CUtensorMap* m, const void* p, int rows, int cols, int box_rows) {
  cuuint64_t dims[2] = {(cuuint64_t)cols, (cuuint64_t)rows};
  cuuint64_t strides[1] = {(cuuint64_t)cols * 2};
  cuuint32_t box[2] = {64, (cuuint32_t)box_rows};
  cuuint32_t es[2] = {1, 1};
  fn(m, CU_TENSOR_MAP_DATA_TYPE_BFLOAT16, 2, (void*)p, dims, strides, box, es, CU_TENSOR_MAP_INTERLEAVE_NONE,
     CU_TENSOR_MAP_SWIZZLE_128B, CU_TENSOR_MAP_L2_PROMOTION_L2_256B, CU_TENSOR_MAP_FLOAT_OOB_FILL_NONE);
}
template <typename... KA, typename... A>
static void launch(void (*k)(KA...), int grid, int block, int smem, bool pdl, A... args) {
  cudaLaunchConfig_t cfg = {};
  cfg.gridDim = dim3(grid); cfg.blockDim = dim3(block); cfg.dynamicSmemBytes = smem; cfg.stream = cudaStreamPerThread;
  cudaLaunchAttribute at;
  at.id = cudaLaunchAttributeProgrammaticStreamSerialization;
  at.val.programmaticStreamSerializationAllowed = 1;
  cfg.attrs = &at; cfg.numAttrs = pdl ? 1 : 0;
  cudaLaunchKernelEx(&cfg, k, KA(args)...);
}

extern "C" void kernel_launch(void* const* d_in, const int* in_sizes, int n_in, void* d_out, int out_size) {
  const __nv_bfloat16* x = (const __nv_bfloat16*)d_in[0];
  void* fnp = nullptr;
  cudaDriverEntryPointQueryResult qr;
  cudaGetDriverEntryPoint("cuTensorMapEncodeTiled", &fnp, cudaEnableDefault, &qr);
  EncodeFn fn = (EncodeFn)fnp;
  void *po, *px1;
  cudaGetSymbolAddress(&po, g_o);
  cudaGetSymbolAddress(&px1, g_x1);
  CUtensorMap mx, mqkv, mo, mwo, mx1, mg, mu, md;
  make_map(fn, &mx, x, SEQ, DM, 128);
  make_map(fn, &mqkv, d_in[1], DM, 3 * DM, 64);
  make_map(fn, &mo, po, SEQ, DM, 128);
  make_map(fn, &mwo, d_in[2], DM, DM, 64);
  make_map(fn, &mx1, px1, SEQ, DM, 128);
  make_map(fn, &mg, d_in[4], DM, FF, 64);
  make_map(fn, &mu, d_in[5], DM, FF, 64);
  make_map(fn, &md, d_in[6], FF, DM, 64);
  cudaFuncSetAttribute(k1_kernel, cudaFuncAttributeMaxDynamicSharedMemorySize, GEMM_SMEM);
  cudaFuncSetAttribute(k2_kernel, cudaFuncAttributeMaxDynamicSharedMemorySize, ATT_SMEM);
  cudaFuncSetAttribute(k3_kernel, cudaFuncAttributeMaxDynamicSharedMemorySize, K3_SMEM);
  cudaFuncSetAttribute(k4_kernel, cudaFuncAttributeMaxDynamicSharedMemorySize, GEMM_SMEM);
  launch(k0_kernel, 108 + 128, 256, 0, false, x, (const __nv_bfloat16*)d_in[7], (const __nv_bfloat16*)d_in[8]);
  launch(k1_kernel, 128, 384, GEMM_SMEM, true, mx, mqkv);
  launch(k2_kernel, 128, 512, ATT_SMEM, true);
  launch(k3_kernel, 128, 288, K3_SMEM, true, mo, mwo, x);
  launch(k4_kernel, 128, 384, GEMM_SMEM, true, mx1, mg, mu, md, (__nv_bfloat16*)d_out);
}
```

```cpp
#include <cuda_runtime.h>
#include <cuda_bf16.h>
#include <cuda.h>
#include <stdint.h>

#define SEQ 2048
#define DM 576
#define NH 32
#define FF 4608

__device__ uint4 g_tab1[36 * 4];
__device__ uint4 g_tab2[36 * 4];
__device__ float g_ga[DM];
__device__ float g_gb[DM];
__device__ uint4 g_stat1[SEQ];
__device__ float2 g_stat2[SEQ * 8];
__device__ __align__(1024) uint8_t g_qkv[96 * 98304];
__device__ float g_kmax[NH * 16];
__device__ __align__(1024) __nv_bfloat16 g_o[SEQ * DM];
__device__ __align__(1024) __nv_bfloat16 g_x1[SEQ * DM];
__device__ __align__(1024) uint8_t g_part[8 * 16 * 5 * 2 * 16384];
__device__ unsigned int g_cnt[16 * 5];

#define TS(k, i)
__device__ __forceinline__ uint32_t s2u(const void* p) { return (uint32_t)__cvta_generic_to_shared(p); }
__device__ __forceinline__ void mbar_init(uint32_t b, int c) { asm volatile("mbarrier.init.shared::cta.b64 [%0],%1;" ::"r"(b), "r"(c)); }
__device__ __forceinline__ void mbar_expect(uint32_t b, uint32_t n) { asm volatile("mbarrier.arrive.expect_tx.shared::cta.b64 _,[%0],%1;" ::"r"(b), "r"(n) : "memory"); }
__device__ __forceinline__ void mbar_arrive(uint32_t b) { asm volatile("mbarrier.arrive.shared::cta.b64 _,[%0];" ::"r"(b) : "memory"); }
__device__ __forceinline__ void mbar_wait(uint32_t b, uint32_t ph) {
  asm volatile(
      "{.reg .pred p; .reg .u32 n; mov.u32 n,0;\n"
      "W: mbarrier.try_wait.parity.shared::cta.b64 p,[%0],%1;\n"
      "@p bra D;\n"
      "add.u32 n,n,1; setp.lt.u32 p,n,4000000; @p bra W;\n"
      "trap;\n"
      "D: }" ::"r"(b), "r"(ph) : "memory");
}
__device__ __forceinline__ void tma2d(uint32_t dst, const CUtensorMap* m, int c0, int c1, uint32_t bar) {
  asm volatile("cp.async.bulk.tensor.2d.shared::cluster.global.mbarrier::complete_tx::bytes [%0],[%1,{%3,%4}],[%2];"
               ::"r"(dst), "l"(m), "r"(bar), "r"(c0), "r"(c1) : "memory");
}
__device__ __forceinline__ void bulk_g2s(uint32_t dst, const void* src, uint32_t bytes, uint32_t bar) {
  asm volatile("cp.async.bulk.shared::cluster.global.mbarrier::complete_tx::bytes [%0],[%1],%2,[%3];"
               ::"r"(dst), "l"(src), "r"(bytes), "r"(bar) : "memory");
}
__device__ __forceinline__ void bulk_s2g(void* dst, uint32_t src, uint32_t bytes) {
  asm volatile("cp.async.bulk.global.shared::cta.bulk_group [%0],[%1],%2;" ::"l"(dst), "r"(src), "r"(bytes) : "memory");
}
__device__ __forceinline__ void bulk_commit() { asm volatile("cp.async.bulk.commit_group;" ::: "memory"); }
__device__ __forceinline__ void bulk_wait0() { asm volatile("cp.async.bulk.wait_group 0;" ::: "memory"); }
__device__ __forceinline__ void prefetch_map(const CUtensorMap* m) { asm volatile("prefetch.tensormap [%0];" ::"l"(m) : "memory"); }
__device__ __forceinline__ void fence_async_smem() { asm volatile("fence.proxy.async.shared::cta;" ::: "memory"); }
__device__ __forceinline__ void fence_bar_init() { asm volatile("fence.mbarrier_init.release.cluster;" ::: "memory"); }
__device__ __forceinline__ void pdl_wait() { asm volatile("griddepcontrol.wait;" ::: "memory"); }
__device__ __forceinline__ void pdl_launch() { asm volatile("griddepcontrol.launch_dependents;" ::: "memory"); }
__device__ __forceinline__ void bar_sync(int id, int n) { asm volatile("bar.sync %0,%1;" ::"r"(id), "r"(n) : "memory"); }
__device__ __forceinline__ void bar_arrive(int id, int n) { asm volatile("bar.arrive %0,%1;" ::"r"(id), "r"(n) : "memory"); }
#define WG_FENCE() asm volatile("wgmma.fence.sync.aligned;" ::: "memory")
#define WG_COMMIT() asm volatile("wgmma.commit_group.sync.aligned;" ::: "memory")
#define WG_WAIT(n) asm volatile("wgmma.wait_group.sync.aligned " #n ";" ::: "memory")
template <int N> __device__ __forceinline__ void fence_regs(float* r) {
#pragma unroll
  for (int i = 0; i < N; i++) asm volatile("" : "+f"(r[i])::"memory");
}
#define REG_INC(n) asm volatile("setmaxnreg.inc.sync.aligned.u32 " #n ";")
#define REG_DEC(n) asm volatile("setmaxnreg.dec.sync.aligned.u32 " #n ";")
__device__ __forceinline__ uint64_t mkdesc(uint32_t addr, uint32_t lbo, uint32_t sbo, int sw) {
  return (uint64_t)((addr & 0x3FFFF) >> 4) | ((uint64_t)(lbo >> 4) << 16) | ((uint64_t)(sbo >> 4) << 32) | ((uint64_t)sw << 62);
}
__device__ __forceinline__ void ldsm4(uint32_t* r, uint32_t addr) {
  asm volatile("ldmatrix.sync.aligned.m8n8.x4.shared.b16 {%0,%1,%2,%3},[%4];" : "=r"(r[0]), "=r"(r[1]), "=r"(r[2]), "=r"(r[3]) : "r"(addr) : "memory");
}
__device__ __forceinline__ void stsm4(uint32_t addr, uint32_t r0, uint32_t r1, uint32_t r2, uint32_t r3) {
  asm volatile("stmatrix.sync.aligned.m8n8.x4.shared.b16 [%0],{%1,%2,%3,%4};" ::"r"(addr), "r"(r0), "r"(r1), "r"(r2), "r"(r3) : "memory");
}
__device__ __forceinline__ uint32_t pack_bf16(float lo, float hi) {
  uint32_t r;
  asm("cvt.rn.bf16x2.f32 %0,%1,%2;" : "=r"(r) : "f"(hi), "f"(lo));
  return r;
}
__device__ __forceinline__ float bf_lo(uint32_t v) { return __uint_as_float(v << 16); }
__device__ __forceinline__ float bf_hi(uint32_t v) { return __uint_as_float(v & 0xFFFF0000u); }
__device__ __forceinline__ float rbf(float x) { return __bfloat162float(__float2bfloat16_rn(x)); }
__device__ __forceinline__ uint32_t hfma2(uint32_t a, uint32_t b, uint32_t c) {
  uint32_t r;
  asm("fma.rn.bf16x2 %0,%1,%2,%3;" : "=r"(r) : "r"(a), "r"(b), "r"(c));
  return r;
}
__device__ __forceinline__ uint32_t hadd2(uint32_t a, uint32_t b) {
  uint32_t r;
  asm("add.rn.bf16x2 %0,%1,%2;" : "=r"(r) : "r"(a), "r"(b));
  return r;
}
__device__ __forceinline__ uint32_t hmul2(uint32_t a, uint32_t b) {
  uint32_t r;
  asm("mul.rn.bf16x2 %0,%1,%2;" : "=r"(r) : "r"(a), "r"(b));
  return r;
}
__device__ __forceinline__ uint32_t hneg2(uint32_t a) {
  uint32_t r;
  asm("neg.bf16x2 %0,%1;" : "=r"(r) : "r"(a));
  return r;
}
__device__ __forceinline__ float ex2f(float x) {
  float r;
  asm("ex2.approx.ftz.f32 %0,%1;" : "=f"(r) : "f"(x));
  return r;
}
__device__ __forceinline__ float tanhf_fast(float x) {
  float r;
  asm("tanh.approx.f32 %0,%1;" : "=f"(r) : "f"(x));
  return r;
}
__device__ __forceinline__ uint4 ln_consts(float mean, float var) {
  float m = rbf(mean), v = rbf(var);
  float s = rbf(sqrtf(rbf(v + 1e-5f)));
  float r = 1.0f / s;
  float rh = rbf(r), rl = r - rh;
  return make_uint4(pack_bf16(-m, -m), pack_bf16(rh, rh), pack_bf16(rl, rl), 0u);
}
__device__ __forceinline__ uint32_t ln_apply(uint32_t x, const uint4& st, uint32_t a, uint32_t s) {
  uint32_t d = hadd2(x, st.x);
  uint32_t n = hfma2(d, st.y, hmul2(d, st.z));
  return hfma2(n, a, s);
}

__device__ __forceinline__ void wg_rs_n128_t1(float* d, uint32_t a0, uint32_t a1, uint32_t a2, uint32_t a3, uint64_t db, int sc) {
  asm volatile("{.reg .pred p; setp.ne.b32 p,%69,0; wgmma.mma_async.sync.aligned.m64n128k16.f32.bf16.bf16 {%0,%1,%2,%3,%4,%5,%6,%7,%8,%9,%10,%11,%12,%13,%14,%15,%16,%17,%18,%19,%20,%21,%22,%23,%24,%25,%26,%27,%28,%29,%30,%31,%32,%33,%34,%35,%36,%37,%38,%39,%40,%41,%42,%43,%44,%45,%46,%47,%48,%49,%50,%51,%52,%53,%54,%55,%56,%57,%58,%59,%60,%61,%62,%63}, {%64,%65,%66,%67}, %68, p,1,1,1;}"
  : "+f"(d[0]),"+f"(d[1]),"+f"(d[2]),"+f"(d[3]),"+f"(d[4]),"+f"(d[5]),"+f"(d[6]),"+f"(d[7]),"+f"(d[8]),"+f"(d[9]),"+f"(d[10]),"+f"(d[11]),"+f"(d[12]),"+f"(d[13]),"+f"(d[14]),"+f"(d[15]),"+f"(d[16]),"+f"(d[17]),"+f"(d[18]),"+f"(d[19]),"+f"(d[20]),"+f"(d[21]),"+f"(d[22]),"+f"(d[23]),"+f"(d[24]),"+f"(d[25]),"+f"(d[26]),"+f"(d[27]),"+f"(d[28]),"+f"(d[29]),"+f"(d[30]),"+f"(d[31]),"+f"(d[32]),"+f"(d[33]),"+f"(d[34]),"+f"(d[35]),"+f"(d[36]),"+f"(d[37]),"+f"(d[38]),"+f"(d[39]),"+f"(d[40]),"+f"(d[41]),"+f"(d[42]),"+f"(d[43]),"+f"(d[44]),"+f"(d[45]),"+f"(d[46]),"+f"(d[47]),"+f"(d[48]),"+f"(d[49]),"+f"(d[50]),"+f"(d[51]),"+f"(d[52]),"+f"(d[53]),"+f"(d[54]),"+f"(d[55]),"+f"(d[56]),"+f"(d[57]),"+f"(d[58]),"+f"(d[59]),"+f"(d[60]),"+f"(d[61]),"+f"(d[62]),"+f"(d[63]) : "r"(a0),"r"(a1),"r"(a2),"r"(a3),"l"(db),"r"(sc));
}
__device__ __forceinline__ void wg_rs_n64_t1(float* d, uint32_t a0, uint32_t a1, uint32_t a2, uint32_t a3, uint64_t db, int sc) {
  asm volatile("{.reg .pred p; setp.ne.b32 p,%37,0; wgmma.mma_async.sync.aligned.m64n64k16.f32.bf16.bf16 {%0,%1,%2,%3,%4,%5,%6,%7,%8,%9,%10,%11,%12,%13,%14,%15,%16,%17,%18,%19,%20,%21,%22,%23,%24,%25,%26,%27,%28,%29,%30,%31}, {%32,%33,%34,%35}, %36, p,1,1,1;}"
  : "+f"(d[0]),"+f"(d[1]),"+f"(d[2]),"+f"(d[3]),"+f"(d[4]),"+f"(d[5]),"+f"(d[6]),"+f"(d[7]),"+f"(d[8]),"+f"(d[9]),"+f"(d[10]),"+f"(d[11]),"+f"(d[12]),"+f"(d[13]),"+f"(d[14]),"+f"(d[15]),"+f"(d[16]),"+f"(d[17]),"+f"(d[18]),"+f"(d[19]),"+f"(d[20]),"+f"(d[21]),"+f"(d[22]),"+f"(d[23]),"+f"(d[24]),"+f"(d[25]),"+f"(d[26]),"+f"(d[27]),"+f"(d[28]),"+f"(d[29]),"+f"(d[30]),"+f"(d[31]) : "r"(a0),"r"(a1),"r"(a2),"r"(a3),"l"(db),"r"(sc));
}
__device__ __forceinline__ void wg_rs_n88_t1(float* d, uint32_t a0, uint32_t a1, uint32_t a2, uint32_t a3, uint64_t db, int sc) {
  asm volatile("{.reg .pred p; setp.ne.b32 p,%49,0; wgmma.mma_async.sync.aligned.m64n88k16.f32.bf16.bf16 {%0,%1,%2,%3,%4,%5,%6,%7,%8,%9,%10,%11,%12,%13,%14,%15,%16,%17,%18,%19,%20,%21,%22,%23,%24,%25,%26,%27,%28,%29,%30,%31,%32,%33,%34,%35,%36,%37,%38,%39,%40,%41,%42,%43}, {%44,%45,%46,%47}, %48, p,1,1,1;}"
  : "+f"(d[0]),"+f"(d[1]),"+f"(d[2]),"+f"(d[3]),"+f"(d[4]),"+f"(d[5]),"+f"(d[6]),"+f"(d[7]),"+f"(d[8]),"+f"(d[9]),"+f"(d[10]),"+f"(d[11]),"+f"(d[12]),"+f"(d[13]),"+f"(d[14]),"+f"(d[15]),"+f"(d[16]),"+f"(d[17]),"+f"(d[18]),"+f"(d[19]),"+f"(d[20]),"+f"(d[21]),"+f"(d[22]),"+f"(d[23]),"+f"(d[24]),"+f"(d[25]),"+f"(d[26]),"+f"(d[27]),"+f"(d[28]),"+f"(d[29]),"+f"(d[30]),"+f"(d[31]),"+f"(d[32]),"+f"(d[33]),"+f"(d[34]),"+f"(d[35]),"+f"(d[36]),"+f"(d[37]),"+f"(d[38]),"+f"(d[39]),"+f"(d[40]),"+f"(d[41]),"+f"(d[42]),"+f"(d[43]) : "r"(a0),"r"(a1),"r"(a2),"r"(a3),"l"(db),"r"(sc));
}
__device__ __forceinline__ void wg_ss_n72_t1(float* d, uint64_t da, uint64_t db, int sc) {
  asm volatile("{.reg .pred p; setp.ne.b32 p,%38,0; wgmma.mma_async.sync.aligned.m64n72k16.f32.bf16.bf16 {%0,%1,%2,%3,%4,%5,%6,%7,%8,%9,%10,%11,%12,%13,%14,%15,%16,%17,%18,%19,%20,%21,%22,%23,%24,%25,%26,%27,%28,%29,%30,%31,%32,%33,%34,%35}, %36, %37, p,1,1,0,1;}"
  : "+f"(d[0]),"+f"(d[1]),"+f"(d[2]),"+f"(d[3]),"+f"(d[4]),"+f"(d[5]),"+f"(d[6]),"+f"(d[7]),"+f"(d[8]),"+f"(d[9]),"+f"(d[10]),"+f"(d[11]),"+f"(d[12]),"+f"(d[13]),"+f"(d[14]),"+f"(d[15]),"+f"(d[16]),"+f"(d[17]),"+f"(d[18]),"+f"(d[19]),"+f"(d[20]),"+f"(d[21]),"+f"(d[22]),"+f"(d[23]),"+f"(d[24]),"+f"(d[25]),"+f"(d[26]),"+f"(d[27]),"+f"(d[28]),"+f"(d[29]),"+f"(d[30]),"+f"(d[31]),"+f"(d[32]),"+f"(d[33]),"+f"(d[34]),"+f"(d[35]) : "l"(da),"l"(db),"r"(sc));
}
template <int SC> __device__ __forceinline__ void wl_rs_n24_t1(float* d, const uint32_t* a, uint32_t lo, uint32_t hi) {
  asm volatile("{.reg .b64 e; mov.b64 e,{%16,%17}; wgmma.mma_async.sync.aligned.m64n24k16.f32.bf16.bf16 {%0,%1,%2,%3,%4,%5,%6,%7,%8,%9,%10,%11}, {%12,%13,%14,%15}, e, %18,1,1,1;}"
  : "+f"(d[0]),"+f"(d[1]),"+f"(d[2]),"+f"(d[3]),"+f"(d[4]),"+f"(d[5]),"+f"(d[6]),"+f"(d[7]),"+f"(d[8]),"+f"(d[9]),"+f"(d[10]),"+f"(d[11]) : "r"(a[0]),"r"(a[1]),"r"(a[2]),"r"(a[3]),"r"(lo),"r"(hi),"n"(SC));
}
template <int SC> __device__ __forceinline__ void wl_rs_n64_t0(float* d, const uint32_t* a, uint32_t lo, uint32_t hi) {
  asm volatile("{.reg .b64 e; mov.b64 e,{%36,%37}; wgmma.mma_async.sync.aligned.m64n64k16.f32.bf16.bf16 {%0,%1,%2,%3,%4,%5,%6,%7,%8,%9,%10,%11,%12,%13,%14,%15,%16,%17,%18,%19,%20,%21,%22,%23,%24,%25,%26,%27,%28,%29,%30,%31}, {%32,%33,%34,%35}, e, %38,1,1,0;}"
  : "+f"(d[0]),"+f"(d[1]),"+f"(d[2]),"+f"(d[3]),"+f"(d[4]),"+f"(d[5]),"+f"(d[6]),"+f"(d[7]),"+f"(d[8]),"+f"(d[9]),"+f"(d[10]),"+f"(d[11]),"+f"(d[12]),"+f"(d[13]),"+f"(d[14]),"+f"(d[15]),"+f"(d[16]),"+f"(d[17]),"+f"(d[18]),"+f"(d[19]),"+f"(d[20]),"+f"(d[21]),"+f"(d[22]),"+f"(d[23]),"+f"(d[24]),"+f"(d[25]),"+f"(d[26]),"+f"(d[27]),"+f"(d[28]),"+f"(d[29]),"+f"(d[30]),"+f"(d[31]) : "r"(a[0]),"r"(a[1]),"r"(a[2]),"r"(a[3]),"r"(lo),"r"(hi),"n"(SC));
}

#define POLY_MASK 0xB5u
#define QSCALE (0.23570226039551584f * 1.4426950408889634f)

__global__ void __launch_bounds__(256) k0_kernel(const __nv_bfloat16* __restrict__ x, const __nv_bfloat16* __restrict__ c,
                                                 const __nv_bfloat16* __restrict__ wmod) {
  if (threadIdx.x == 0) TS(0, 0);
  pdl_launch();
  const int tid = threadIdx.x, lane = tid & 31, warp = tid >> 5;
  if (blockIdx.x < 108) {
    __shared__ float red[8][32];
    const int col0 = blockIdx.x * 32 + (tid & 3) * 8, r0 = tid >> 2;
    uint4 w[9];
#pragma unroll
    for (int i = 0; i < 9; i++) w[i] = __ldg((const uint4*)(wmod + (size_t)(r0 + 64 * i) * 3456 + col0));
    float acc[8] = {0, 0, 0, 0, 0, 0, 0, 0};
#pragma unroll
    for (int i = 0; i < 9; i++) {
      float cv = __bfloat162float(c[r0 + 64 * i]);
      float sv = rbf(cv / (1.0f + __expf(-cv)));
      acc[0] += sv * bf_lo(w[i].x); acc[1] += sv * bf_hi(w[i].x);
      acc[2] += sv * bf_lo(w[i].y); acc[3] += sv * bf_hi(w[i].y);
      acc[4] += sv * bf_lo(w[i].z); acc[5] += sv * bf_hi(w[i].z);
      acc[6] += sv * bf_lo(w[i].w); acc[7] += sv * bf_hi(w[i].w);
    }
#pragma unroll
    for (int j = 0; j < 8; j++) {
      acc[j] += __shfl_xor_sync(~0u, acc[j], 4);
      acc[j] += __shfl_xor_sync(~0u, acc[j], 8);
      acc[j] += __shfl_xor_sync(~0u, acc[j], 16);
    }
    if (lane < 4) {
#pragma unroll
      for (int j = 0; j < 8; j++) red[warp][lane * 8 + j] = acc[j];
    }
    __syncthreads();
    if (tid < 32) {
      float s = 0;
#pragma unroll
      for (int j = 0; j < 8; j++) s += red[j][tid];
      s = rbf(s);
      int n = blockIdx.x * 32 + tid, part = n / DM, col = n % DM;
      if (part == 2) g_ga[col] = s;
      else if (part == 5) g_gb[col] = s;
      else {
        __nv_bfloat16* tab = (__nv_bfloat16*)(part < 2 ? g_tab1 : g_tab2);
        bool shift = (part == 0 || part == 3);
        int kk = col >> 4, half = (col >> 3) & 1, cq = (col & 7) >> 1, e = col & 1;
        tab[((kk * 4 + cq) * 4 + half * 2 + (shift ? 1 : 0)) * 2 + e] = __float2bfloat16_rn(shift ? s : 1.0f + s);
      }
    }
    if (blockIdx.x == 0 && tid >= 64 && tid < 64 + 80) g_cnt[tid - 64] = 0;
  } else {
    const int row0 = (blockIdx.x - 108) * 16 + warp * 2;
    uint32_t v[2][9];
#pragma unroll
    for (int r = 0; r < 2; r++)
#pragma unroll
      for (int i = 0; i < 9; i++) v[r][i] = __ldg((const uint32_t*)(x + (size_t)(row0 + r) * DM) + lane + 32 * i);
#pragma unroll
    for (int r = 0; r < 2; r++) {
      float s = 0;
#pragma unroll
      for (int i = 0; i < 9; i++) s += bf_lo(v[r][i]) + bf_hi(v[r][i]);
#pragma unroll
      for (int o = 16; o; o >>= 1) s += __shfl_xor_sync(~0u, s, o);
      float mean = s * (1.0f / DM), q = 0;
#pragma unroll
      for (int i = 0; i < 9; i++) {
        float a = bf_lo(v[r][i]) - mean, b = bf_hi(v[r][i]) - mean;
        q += a * a + b * b;
      }
#pragma unroll
      for (int o = 16; o; o >>= 1) q += __shfl_xor_sync(~0u, q, o);
      if (lane == 0) g_stat1[row0 + r] = ln_consts(mean, q * (1.0f / DM));
    }
  }
  if (threadIdx.x == 0) TS(0, 1);
}

#define NSTG 6
#define STG_BYTES 16384
#define R_BYTES (8 * 16384)
#define GEMM_SMEM (R_BYTES + NSTG * STG_BYTES + 1024 + 256)

struct Ring {
  uint32_t base, full, empty;
  int st;
  uint32_t ph;
  __device__ __forceinline__ void next() { if (++st == NSTG) { st = 0; ph ^= 1; } }
};

__device__ __forceinline__ void load_a_chunk(uint32_t (*a)[4], uint32_t chunk_base, int row_in_tile, int lane) {
  const int r = row_in_tile + (lane & 7) + ((lane >> 3) & 1) * 8;
  const uint32_t rb = chunk_base + r * 128;
#pragma unroll
  for (int k = 0; k < 4; k++) ldsm4(a[k], rb + (((k * 2 + (lane >> 4)) ^ (r & 7)) << 4));
}

#define MMA_TILE(FN, acc, a, ring, lane)                                        \
  {                                                                             \
    uint32_t prev_empty = 0;                                                    \
    _Pragma("unroll") for (int s = 0; s < 9; s++) {                             \
      mbar_wait(ring.full + ring.st * 8, ring.ph);                              \
      WG_FENCE();                                                               \
      uint32_t sa_ = ring.base + ring.st * STG_BYTES;                           \
      asm volatile("" : "+r"(sa_));                                             \
      uint64_t db = mkdesc(sa_, 8192, 1024, 1);                                 \
      _Pragma("unroll") for (int k = 0; k < 4; k++)                             \
          FN(acc, a[s * 4 + k][0], a[s * 4 + k][1], a[s * 4 + k][2], a[s * 4 + k][3], db + k * 128, (s | k) != 0); \
      WG_COMMIT();                                                              \
      if (s > 0) { WG_WAIT(1); if (lane == 0) mbar_arrive(prev_empty); }        \
      prev_empty = ring.empty + ring.st * 8;                                    \
      ring.next();                                                              \
    }                                                                           \
    WG_WAIT(0);                                                                 \
    if (lane == 0) mbar_arrive(prev_empty);                                     \
  }

template <int NG, int G0>
__device__ __forceinline__ void qkv_stage(const float* acc, uint32_t stg, int rowl, int cq, int col_base) {
  const float vs0 = ((POLY_MASK >> ((rowl >> 3) & 7)) & 1) ? 0.5f : 1.0f, vs1 = ((POLY_MASK >> (((rowl >> 3) + 1) & 7)) & 1) ? 0.5f : 1.0f;
#pragma unroll
  for (int i = 0; i < NG; i++) {
    const int cc = (G0 + i) * 8 + cq * 2;
    const int slot = (cc * 3641) >> 16, d = cc - slot * 18;
    const int gc = col_base + cc;
    const float sc0 = gc < DM ? QSCALE : (gc < 2 * DM ? vs0 : 1.0f), sc1 = gc < DM ? QSCALE : (gc < 2 * DM ? vs1 : 1.0f);
    const uint32_t ad = stg + slot * 6144 + (d >> 3) * 128 + (d & 7) * 2 + (rowl >> 3) * 384 + (rowl & 7) * 16;
    asm volatile("st.shared.b32 [%0],%1;" ::"r"(ad), "r"(pack_bf16(acc[4 * i] * sc0, acc[4 * i + 1] * sc0)) : "memory");
    asm volatile("st.shared.b32 [%0],%1;" ::"r"(ad + 384), "r"(pack_bf16(acc[4 * i + 2] * sc1, acc[4 * i + 3] * sc1)) : "memory");
  }
}

__global__ void __launch_bounds__(384, 1) k1_kernel(const __grid_constant__ CUtensorMap mx, const __grid_constant__ CUtensorMap mw) {
  extern __shared__ uint8_t smem_raw[];
  const uint32_t sb = (s2u(smem_raw) + 1023) & ~1023u;
  const uint32_t R = sb, RING = sb + R_BYTES, BAR = RING + NSTG * STG_BYTES;
  const uint32_t full = BAR, empty = BAR + 64, xfull = BAR + 128;
  const int tid = threadIdx.x, lane = tid & 31, warp = tid >> 5;
  const int mb = blockIdx.x >> 3, nb = blockIdx.x & 7;
  if (tid == 0) {
    TS(1, 0);
    for (int i = 0; i < NSTG; i++) { mbar_init(full + i * 8, 1); mbar_init(empty + i * 8, 8); }
    for (int i = 0; i < 8; i++) mbar_init(xfull + i * 8, 1);
    fence_bar_init();
  }
  __syncthreads();
  pdl_launch();
  if (warp >= 8) {
    REG_DEC(24);
    if (warp == 8) {
      if (lane == 0) {
        for (int c = 0; c < 8; c++) { mbar_expect(xfull + c * 8, 16384); tma2d(R + c * 16384, &mx, c * 64, mb * 128, xfull + c * 8); }
        mbar_expect(full, 16384);
        tma2d(RING, &mx, 512, mb * 128, full);
        int st = 1; uint32_t ph = 0;
        for (int it = 0; it < 18; it++) {
          const int t = it / 9, s = it - t * 9;
          mbar_wait(empty + st * 8, ph ^ 1);
          mbar_expect(full + st * 8, 16384);
          tma2d(RING + st * STG_BYTES, &mw, nb * 216 + t * 128, s * 64, full + st * 8);
          tma2d(RING + st * STG_BYTES + 8192, &mw, nb * 216 + t * 128 + 64, s * 64, full + st * 8);
          if (++st == NSTG) { st = 0; ph ^= 1; }
        }
      }
      pdl_wait();
    } else {
      const int ht = tid - 288;
      bar_sync(1, 352);
      for (int i = ht; i < 12 * 128; i += 96) {
        const int slot = i >> 7, row = i & 127, type = (nb * 12 + slot) >> 5;
        uint32_t v = 0;
        if (type == 1) v = ((POLY_MASK >> ((row >> 3) & 7)) & 1) ? 0x43403F00u : 0x40253F80u;
        if (type == 2) v = 0x3F80u;
        const uint32_t ad = R + slot * 6144 + (row >> 3) * 384 + 256 + (row & 7) * 16;
        asm volatile("st.shared.b32 [%0],%1;" ::"r"(ad + 4), "r"(v) : "memory");
        asm volatile("st.shared.v2.b32 [%0],{%1,%1};" ::"r"(ad + 8), "r"(0) : "memory");
      }
      fence_async_smem();
      pdl_wait();
#pragma unroll 1
      for (int t = 0; t < 2; t++) {
        bar_sync(2 + t, 352);
        const int s0 = t ? 7 : 0, s1 = t ? 12 : 7;
        if (ht == 0) {
          for (int s = s0; s < s1; s++) bulk_s2g(g_qkv + (size_t)(nb * 12 + s) * 98304 + mb * 6144, R + s * 6144, 6144);
          bulk_commit();
        }
        for (int s = s0 + (warp - 9); s < s1; s += 3) {
          const int gs = nb * 12 + s;
          if ((gs >> 5) != 1) continue;
          float mx2 = 0;
#pragma unroll 1
          for (int row = lane; row < 128; row += 32) {
            const uint32_t ad = R + s * 6144 + (row >> 3) * 384 + (row & 7) * 16;
            float q = 0;
#pragma unroll 1
            for (int ch = 0; ch < 3; ch++) {
              uint32_t u0, u1, u2, u3;
              asm volatile("ld.shared.v4.b32 {%0,%1,%2,%3},[%4];" : "=r"(u0), "=r"(u1), "=r"(u2), "=r"(u3) : "r"(ad + ch * 128));
              if (ch == 2) u1 = 0;
              q += bf_lo(u0) * bf_lo(u0) + bf_hi(u0) * bf_hi(u0) + bf_lo(u1) * bf_lo(u1) + bf_hi(u1) * bf_hi(u1);
              q += bf_lo(u2) * bf_lo(u2) + bf_hi(u2) * bf_hi(u2) + bf_lo(u3) * bf_lo(u3) + bf_hi(u3) * bf_hi(u3);
            }
            if ((POLY_MASK >> ((row >> 3) & 7)) & 1) q *= 4.0f;
            mx2 = (q > mx2 || q != q) ? q : mx2;
            if (mx2 != mx2) mx2 = __int_as_float(0x7f800000);
          }
#pragma unroll
          for (int o = 16; o; o >>= 1) mx2 = fmaxf(mx2, __shfl_xor_sync(~0u, mx2, o));
          if (lane == 0) g_kmax[(gs & 31) * 16 + mb] = mx2;
        }
      }
      if (ht == 0) bulk_wait0();
      if (ht == 0) TS(1, 8);
    }
  } else {
    REG_INC(240);
    uint32_t a[36][4];
    const int rowl = warp * 16;
#pragma unroll
    for (int c = 0; c < 8; c++) { mbar_wait(xfull + c * 8, 0); load_a_chunk(&a[c * 4], R + c * 16384, rowl, lane); }
    mbar_wait(full, 0);
    load_a_chunk(&a[32], RING, rowl, lane);
    __syncwarp();
    if (lane == 0) mbar_arrive(empty);
    bar_arrive(1, 352);
    if (tid == 0) TS(1, 1);
    pdl_wait();
    if (tid == 0) TS(1, 2);
    {
      const int g = lane >> 2, cq = lane & 3;
      const uint4 s0 = g_stat1[mb * 128 + rowl + g], s1 = g_stat1[mb * 128 + rowl + g + 8];
#pragma unroll
      for (int k = 0; k < 36; k++) {
        if ((k & 3) == 0) asm volatile("" ::: "memory");
        const uint4 t = g_tab1[k * 4 + cq];
        a[k][0] = ln_apply(a[k][0], s0, t.x, t.y);
        a[k][1] = ln_apply(a[k][1], s1, t.x, t.y);
        a[k][2] = ln_apply(a[k][2], s0, t.z, t.w);
        a[k][3] = ln_apply(a[k][3], s1, t.z, t.w);
      }
    }
    bar_sync(4, 256);
    Ring ring{RING, full, empty, 1, 0};
    float acc[64];
    if (tid == 0) TS(1, 3);
    MMA_TILE(wg_rs_n128_t1, acc, a, ring, lane);
    if (tid == 0) TS(1, 4);
    qkv_stage<16, 0>(acc, R, rowl + (lane >> 2), lane & 3, nb * 216);
    fence_async_smem();
    bar_arrive(2, 352);
    if (tid == 0) TS(1, 5);
    MMA_TILE(wg_rs_n88_t1, acc, a, ring, lane);
    if (tid == 0) TS(1, 6);
    qkv_stage<11, 16>(acc, R, rowl + (lane >> 2), lane & 3, nb * 216);
    fence_async_smem();
    bar_arrive(3, 352);
    if (tid == 0) TS(1, 7);
  }
}

#define ATT_SMEM (2 * 98304 + 1024 + 256)

__device__ __forceinline__ uint32_t exp2_pair_fma(float t0, float t1) {
  uint32_t y;
  asm("prmt.b32 %0,%1,%2,0x6521;" : "=r"(y) : "r"(__float_as_uint(t0)), "r"(__float_as_uint(t1)));
  return hfma2(y, y | 0x3F803F80u, y | 0x007F007Fu);
}

__device__ __forceinline__ void softmax_fast(const float* s, uint32_t* p) {
#pragma unroll
  for (int i = 0; i < 8; i++) {
    if ((POLY_MASK >> i) & 1) {
      p[2 * i] = exp2_pair_fma(s[4 * i], s[4 * i + 1]);
      p[2 * i + 1] = exp2_pair_fma(s[4 * i + 2], s[4 * i + 3]);
    } else {
      p[2 * i] = pack_bf16(ex2f(s[4 * i]), ex2f(s[4 * i + 1]));
      p[2 * i + 1] = pack_bf16(ex2f(s[4 * i + 2]), ex2f(s[4 * i + 3]));
    }
  }
}
#define QK_MMA(S, koff)                                                         \
  wl_rs_n64_t0<0>(S, q, dk0 + (koff), 24);                                      \
  wl_rs_n64_t0<1>(S, q + 4, dk1 + (koff), 24);
#define PV_MMA(P, voff)                                                         \
  _Pragma("unroll") for (int t = 0; t < 4; t++) wl_rs_n24_t1<1>(o, P + 4 * t, dv + (voff) + t * 48, 8);

__device__ __forceinline__ float sq2(uint32_t v) { return bf_lo(v) * bf_lo(v) + bf_hi(v) * bf_hi(v); }
__device__ __forceinline__ void att_store(const float* o, int row0, int head, int lane) {
  const int cq = lane & 3;
  const float l0 = __shfl_sync(~0u, o[8], (lane & ~3) | 1), l1 = __shfl_sync(~0u, o[10], (lane & ~3) | 1);
  const float i0 = 1.0f / l0, i1 = 1.0f / l1;
  uint32_t* og = (uint32_t*)(g_o + (size_t)row0 * DM + head * 18 + cq * 2);
  og[0] = pack_bf16(o[0] * i0, o[1] * i0);
  og[4] = pack_bf16(o[4] * i0, o[5] * i0);
  og[8 * DM / 2] = pack_bf16(o[2] * i1, o[3] * i1);
  og[8 * DM / 2 + 4] = pack_bf16(o[6] * i1, o[7] * i1);
  if (cq == 0) {
    og[8] = pack_bf16(o[8] * i0, o[9] * i0);
    og[8 * DM / 2 + 8] = pack_bf16(o[10] * i1, o[11] * i1);
  }
}

__global__ void __launch_bounds__(512, 1) k2_kernel() {
  extern __shared__ uint8_t smem_raw[];
  const uint32_t sb = (s2u(smem_raw) + 1023) & ~1023u;
  const uint32_t KS = sb, VS = sb + 98304, BAR = sb + 2 * 98304;
  const int tid = threadIdx.x, lane = tid & 31, warp = tid >> 5, wg = tid >> 7;
  const int head = blockIdx.x >> 2, qb = blockIdx.x & 3;
  if (tid == 0) {
    TS(2, 0);
    for (int i = 0; i < 16; i++) mbar_init(BAR + i * 8, 1);
    fence_bar_init();
  }
  __syncthreads();
  pdl_launch();
  const int g = lane >> 2, cq = lane & 3;
  const int row0 = qb * 512 + wg * 128 + (warp & 3) * 16 + g;
  const uint8_t* qg = g_qkv + (size_t)head * 98304 + (row0 >> 3) * 384 + (row0 & 7) * 16 + cq * 4;
  pdl_wait();
  if (tid == 0) TS(2, 1);
  if (warp == 0 && lane < 16) {
    const uint8_t* kg = g_qkv + (size_t)(32 + head) * 98304 + lane * 6144;
    mbar_expect(BAR + lane * 8, 12288);
    bulk_g2s(KS + lane * 6144, kg, 6144, BAR + lane * 8);
    bulk_g2s(VS + lane * 6144, kg + 32 * 98304, 6144, BAR + lane * 8);
  }
  uint32_t q[8], q2[6];
  float kmax2 = __ldcg(g_kmax + head * 16 + (lane & 15));
#pragma unroll
  for (int i = 0; i < 6; i++) {
    q[i] = __ldcg((const uint32_t*)(qg + (i & 1) * 384 + (i >> 1) * 128));
    q2[i] = __ldcg((const uint32_t*)(qg + 3072 + (i & 1) * 384 + (i >> 1) * 128));
  }
  q[6] = __ldcg((const uint32_t*)(qg + 256 + 12 - cq * 4)); q[7] = __ldcg((const uint32_t*)(qg + 256 + 8 - cq * 4));
  const uint32_t dk0 = (uint32_t)mkdesc(KS, 128, 384, 0), dk1 = (uint32_t)mkdesc(KS + 256, 0, 384, 0), dv = (uint32_t)mkdesc(VS, 384, 128, 0);
#pragma unroll
  for (int o = 8; o; o >>= 1) kmax2 = fmaxf(kmax2, __shfl_xor_sync(~0u, kmax2, o));
  float bd[4] = {sq2(q[0]) + sq2(q[2]) + sq2(q[4]), sq2(q[1]) + sq2(q[3]) + sq2(q[5]),
                 sq2(q2[0]) + sq2(q2[2]) + sq2(q2[4]), sq2(q2[1]) + sq2(q2[3]) + sq2(q2[5])};
  int ok = 1;
#pragma unroll
  for (int i = 0; i < 4; i++) {
    bd[i] += __shfl_xor_sync(~0u, bd[i], 1); bd[i] += __shfl_xor_sync(~0u, bd[i], 2);
    bd[i] = sqrtf(bd[i] * kmax2) * 1.01f + 1.0f;
    ok = ok && (bd[i] <= 62.0f);
  }
  {
    uint32_t all;
    asm volatile("{.reg .pred p,q; setp.ne.b32 p,%1,0; barrier.red.and.pred q,1,512,p; selp.u32 %0,1,0,q;}"
                 : "=r"(all) : "r"(ok) : "memory");
    ok = __all_sync(~0u, all);
  }
  float o[12];
#pragma unroll
  for (int i = 0; i < 12; i++) { o[i] = 0.f; asm volatile("" : "+f"(o[i])); }
  float s[32];
  uint32_t p[16];
  if (tid == 0) TS(2, 2);
  if (ok) {
    if (cq == 1) {
      q[4] = pack_bf16(-bd[0], 1.0f); q[5] = pack_bf16(-bd[1], 1.0f);
      q2[4] = pack_bf16(-bd[2], 1.0f); q2[5] = pack_bf16(-bd[3], 1.0f);
    }
    mbar_wait(BAR, 0);
    WG_FENCE();
    QK_MMA(s, 0u);
    WG_COMMIT();
#pragma unroll 1
    for (int tile = 0; tile < 2; tile++) {
#pragma unroll 1
      for (int jj = 0; jj < 8; jj++) {
        const uint32_t off = jj * 768;
        if (tile == 0) { mbar_wait(BAR + jj * 16 + 8, 0); mbar_wait(BAR + ((jj * 16 + 16) & 127), 0); }
#pragma unroll
        for (int u = 0; u < 4; u++) {
          WG_WAIT(0);
          fence_regs<32>(s);
          softmax_fast(s, p);
          if (u == 3 && jj == 7) {
#pragma unroll
            for (int i = 0; i < 6; i++) q[i] = q2[i];
          }
          WG_FENCE();
          PV_MMA(p, off + u * 192);
          QK_MMA(s, u < 3 ? off + u * 192 + 192 : (jj == 7 ? 0u : off + 768));
          WG_COMMIT();
        }
      }
      WG_WAIT(0);
      fence_regs<12>(o);
      att_store(o, row0 + tile * 64, head, lane);
#pragma unroll
      for (int i = 0; i < 12; i++) o[i] = 0.f;
      fence_regs<12>(o);
      if (tid == 0 && tile == 0) TS(2, 3);
    }
  } else {
#pragma unroll 1
    for (int tile = 0; tile < 2; tile++) {
      float m0 = -INFINITY, m1 = -INFINITY;
#pragma unroll 1
      for (int j = 0; j < 32; j++) {
        mbar_wait(BAR + (j >> 1) * 8, 0);
        WG_FENCE();
        QK_MMA(s, (uint32_t)j * 192);
        WG_COMMIT();
        WG_WAIT(0);
        fence_regs<32>(s);
#pragma unroll
        for (int i = 0; i < 32; i++) if ((POLY_MASK >> (i >> 2)) & 1) s[i] *= 2.0f;
        float x0 = m0, x1 = m1;
#pragma unroll
        for (int i = 0; i < 8; i++) {
          x0 = fmaxf(x0, fmaxf(s[4 * i], s[4 * i + 1]));
          x1 = fmaxf(x1, fmaxf(s[4 * i + 2], s[4 * i + 3]));
        }
        x0 = fmaxf(x0, __shfl_xor_sync(~0u, x0, 1)); x0 = fmaxf(x0, __shfl_xor_sync(~0u, x0, 2));
        x1 = fmaxf(x1, __shfl_xor_sync(~0u, x1, 1)); x1 = fmaxf(x1, __shfl_xor_sync(~0u, x1, 2));
        const float c0 = ex2f(m0 - x0), c1 = ex2f(m1 - x1);
        m0 = x0; m1 = x1;
#pragma unroll
        for (int i = 0; i < 3; i++) { o[4 * i] *= c0; o[4 * i + 1] *= c0; o[4 * i + 2] *= c1; o[4 * i + 3] *= c1; }
#pragma unroll
        for (int i = 0; i < 8; i++) {
          p[2 * i] = pack_bf16(ex2f(s[4 * i] - x0), ex2f(s[4 * i + 1] - x0));
          p[2 * i + 1] = pack_bf16(ex2f(s[4 * i + 2] - x1), ex2f(s[4 * i + 3] - x1));
        }
        WG_FENCE();
        PV_MMA(p, (uint32_t)j * 192);
        WG_COMMIT();
        WG_WAIT(0);
        fence_regs<12>(o);
      }
      att_store(o, row0 + tile * 64, head, lane);
#pragma unroll
      for (int i = 0; i < 12; i++) o[i] = 0.f;
#pragma unroll
      for (int i = 0; i < 6; i++) q[i] = q2[i];
    }
  }
  if (tid == 0) TS(2, 4);
}

#define K3_NSTG 4
#define K3_SMEM (9 * 16384 + K3_NSTG * 16384 + 1024 + 256)
__global__ void __launch_bounds__(288, 1) k3_kernel(const __grid_constant__ CUtensorMap mo, const __grid_constant__ CUtensorMap mw,
                                                    const __nv_bfloat16* __restrict__ x) {
  extern __shared__ uint8_t smem_raw[];
  const uint32_t sb = (s2u(smem_raw) + 1023) & ~1023u;
  const uint32_t A = sb, RING = sb + 9 * 16384, BAR = RING + K3_NSTG * 16384;
  const uint32_t full = BAR, empty = BAR + 64, afull = BAR + 128;
  const int tid = threadIdx.x, lane = tid & 31, warp = tid >> 5;
  const int mb = blockIdx.x >> 3, nb = blockIdx.x & 7;
  if (tid == 0) {
    TS(3, 0);
    for (int i = 0; i < K3_NSTG; i++) { mbar_init(full + i * 8, 1); mbar_init(empty + i * 8, 8); }
    for (int i = 0; i < 9; i++) mbar_init(afull + i * 8, 1);
    fence_bar_init();
  }
  __syncthreads();
  pdl_launch();
  if (warp == 8) {
    if (lane == 0) {
      for (int s = 0; s < K3_NSTG; s++) {
        mbar_expect(full + s * 8, 16384);
        tma2d(RING + s * 16384, &mw, nb * 72, s * 64, full + s * 8);
        tma2d(RING + s * 16384 + 8192, &mw, nb * 72 + 64, s * 64, full + s * 8);
      }
      pdl_wait();
      for (int c = 0; c < 9; c++) { mbar_expect(afull + c * 8, 16384); tma2d(A + c * 16384, &mo, c * 64, mb * 128, afull + c * 8); }
      for (int s = K3_NSTG; s < 9; s++) {
        const int st = s % K3_NSTG;
        mbar_wait(empty + st * 8, ((s / K3_NSTG) & 1) ^ 1);
        mbar_expect(full + st * 8, 16384);
        tma2d(RING + st * 16384, &mw, nb * 72, s * 64, full + st * 8);
        tma2d(RING + st * 16384 + 8192, &mw, nb * 72 + 64, s * 64, full + st * 8);
      }
    }
  } else {
    const int g = lane >> 2, cq = lane & 3;
    const int row = mb * 128 + warp * 16 + g, col = nb * 72 + cq * 2;
    uint32_t xv[18];
#pragma unroll
    for (int i = 0; i < 9; i++) {
      xv[2 * i] = __ldg((const uint32_t*)(x + (size_t)row * DM + col + 8 * i));
      xv[2 * i + 1] = __ldg((const uint32_t*)(x + (size_t)(row + 8) * DM + col + 8 * i));
    }
    pdl_wait();
    if (tid == 0) TS(3, 1);
    float2 ga[9];
#pragma unroll
    for (int i = 0; i < 9; i++) ga[i] = *(const float2*)(g_ga + col + 8 * i);
    float acc[36];
    const uint32_t abase = A + (warp >> 2) * 8192;
#pragma unroll
    for (int s = 0; s < 9; s++) {
      const int st = s % K3_NSTG;
      mbar_wait(afull + s * 8, 0);
      mbar_wait(full + st * 8, (s / K3_NSTG) & 1);
      WG_FENCE();
#pragma unroll
      for (int k = 0; k < 4; k++)
        wg_ss_n72_t1(acc, mkdesc(abase + s * 16384 + k * 32, 16, 1024, 1), mkdesc(RING + st * 16384 + k * 2048, 8192, 1024, 1), (s | k) != 0);
      WG_COMMIT();
      if (s > 0) { WG_WAIT(1); if (lane == 0) mbar_arrive(empty + ((s - 1) % K3_NSTG) * 8); }
    }
    WG_WAIT(0);
    if (tid == 0) TS(3, 2);
    float s0 = 0, s1 = 0;
#pragma unroll
    for (int i = 0; i < 9; i++) {
      acc[4 * i] = rbf(bf_lo(xv[2 * i]) + rbf(ga[i].x * rbf(acc[4 * i])));
      acc[4 * i + 1] = rbf(bf_hi(xv[2 * i]) + rbf(ga[i].y * rbf(acc[4 * i + 1])));
      acc[4 * i + 2] = rbf(bf_lo(xv[2 * i + 1]) + rbf(ga[i].x * rbf(acc[4 * i + 2])));
      acc[4 * i + 3] = rbf(bf_hi(xv[2 * i + 1]) + rbf(ga[i].y * rbf(acc[4 * i + 3])));
      *(uint32_t*)(g_x1 + (size_t)row * DM + col + 8 * i) = pack_bf16(acc[4 * i], acc[4 * i + 1]);
      *(uint32_t*)(g_x1 + (size_t)(row + 8) * DM + col + 8 * i) = pack_bf16(acc[4 * i + 2], acc[4 * i + 3]);
      s0 += acc[4 * i] + acc[4 * i + 1];
      s1 += acc[4 * i + 2] + acc[4 * i + 3];
    }
    s0 += __shfl_xor_sync(~0u, s0, 1); s0 += __shfl_xor_sync(~0u, s0, 2);
    s1 += __shfl_xor_sync(~0u, s1, 1); s1 += __shfl_xor_sync(~0u, s1, 2);
    const float m0 = s0 * (1.0f / 72), m1 = s1 * (1.0f / 72);
    float q0 = 0, q1 = 0;
#pragma unroll
    for (int i = 0; i < 9; i++) {
      q0 += (acc[4 * i] - m0) * (acc[4 * i] - m0) + (acc[4 * i + 1] - m0) * (acc[4 * i + 1] - m0);
      q1 += (acc[4 * i + 2] - m1) * (acc[4 * i + 2] - m1) + (acc[4 * i + 3] - m1) * (acc[4 * i + 3] - m1);
    }
    q0 += __shfl_xor_sync(~0u, q0, 1); q0 += __shfl_xor_sync(~0u, q0, 2);
    q1 += __shfl_xor_sync(~0u, q1, 1); q1 += __shfl_xor_sync(~0u, q1, 2);
    if (cq == 0) {
      g_stat2[row * 8 + nb] = make_float2(m0, q0);
      g_stat2[(row + 8) * 8 + nb] = make_float2(m1, q1);
    }
    if (tid == 0) TS(3, 3);
  }
}

__device__ __forceinline__ uint4 ln2_consts(int row, int cq) {
  const float4 p = *(const float4*)(g_stat2 + row * 8 + cq * 2);
  float s = p.x + p.z;
  s += __shfl_xor_sync(~0u, s, 1); s += __shfl_xor_sync(~0u, s, 2);
  const float mean = s * 0.125f;
  float q = p.y + p.w + 72.0f * ((p.x - mean) * (p.x - mean) + (p.z - mean) * (p.z - mean));
  q += __shfl_xor_sync(~0u, q, 1); q += __shfl_xor_sync(~0u, q, 2);
  return ln_consts(mean, q * (1.0f / DM));
}
__device__ __forceinline__ uint32_t glu_pair(float g0, float g1, float u0, float u1) {
  const float s0 = fmaf(tanhf_fast(0.5f * g0), 0.5f, 0.5f), s1 = fmaf(tanhf_fast(0.5f * g1), 0.5f, 0.5f);
  return pack_bf16(s0 * u0, s1 * u1);
}
template <int NG>
__device__ __forceinline__ void stage_part(const float* acc, uint32_t stg, int wrow, int lane) {
  const int r = wrow + (lane & 7) + ((lane >> 3) & 1) * 8;
#pragma unroll
  for (int i = 0; i < NG; i += 2) {
    const int ch = i + (lane >> 4);
    stsm4(stg + r * 256 + ((ch ^ (r & 7)) << 4), pack_bf16(acc[4 * i], acc[4 * i + 1]), pack_bf16(acc[4 * i + 2], acc[4 * i + 3]),
          pack_bf16(acc[4 * i + 4], acc[4 * i + 5]), pack_bf16(acc[4 * i + 6], acc[4 * i + 7]));
  }
}

__global__ void __launch_bounds__(384, 1) k4_kernel(const __grid_constant__ CUtensorMap mx, const __grid_constant__ CUtensorMap mg,
                                                    const __grid_constant__ CUtensorMap mu, const __grid_constant__ CUtensorMap md,
                                                    __nv_bfloat16* __restrict__ out) {
  extern __shared__ uint8_t smem_raw[];
  const uint32_t sb = (s2u(smem_raw) + 1023) & ~1023u;
  const uint32_t R = sb, RING = sb + R_BYTES, BAR = RING + NSTG * STG_BYTES;
  const uint32_t full = BAR, empty = BAR + 64, xfull = BAR + 128, sfull = BAR + 192, sfree = BAR + 208;
  const int tid = threadIdx.x, lane = tid & 31, warp = tid >> 5;
  const int mb = blockIdx.x >> 3, fb = blockIdx.x & 7;
  if (tid == 0) {
    TS(4, 0);
    for (int i = 0; i < 2; i++) { mbar_init(sfull + i * 8, 4); mbar_init(sfree + i * 8, 1); }
    for (int i = 0; i < NSTG; i++) { mbar_init(full + i * 8, 1); mbar_init(empty + i * 8, 8); }
    for (int i = 0; i < 8; i++) mbar_init(xfull + i * 8, 1);
    fence_bar_init();
  }
  __syncthreads();
  if (warp >= 8) {
    REG_DEC(24);
    if (warp == 8) {
      if (lane == 0) {
        int st = 1; uint32_t ph = 0;
        for (int it = 0; it < 126; it++) {
          if (it == NSTG - 1) {
            pdl_wait();
            for (int c = 0; c < 8; c++) { mbar_expect(xfull + c * 8, 16384); tma2d(R + c * 16384, &mx, c * 64, mb * 128, xfull + c * 8); }
            mbar_expect(full, 16384);
            tma2d(RING, &mx, 512, mb * 128, full);
          }
          const int t = it / 9, s = it - t * 9;
          const uint32_t dst = RING + st * STG_BYTES, fb_ = full + st * 8;
          mbar_wait(empty + st * 8, ph ^ 1);
          if (t < 9) {
            mbar_expect(fb_, 16384);
            tma2d(dst, &mg, fb * 576 + t * 64, s * 64, fb_);
            tma2d(dst + 8192, &mu, fb * 576 + t * 64, s * 64, fb_);
          } else {
            mbar_expect(fb_, t < 13 ? 16384 : 8192);
            tma2d(dst, &md, (t - 9) * 128, fb * 576 + s * 64, fb_);
            if (t < 13) tma2d(dst + 8192, &md, (t - 9) * 128 + 64, fb * 576 + s * 64, fb_);
          }
          if (++st == NSTG) { st = 0; ph ^= 1; }
        }
      }
    } else {
      if (warp < 11 && lane == 0) {
        const int wg = warp - 9;
#pragma unroll 1
        for (int p = 0; p < 5; p++) {
          mbar_wait(sfull + wg * 8, p & 1);
          bulk_s2g(g_part + ((size_t)((fb * 16 + mb) * 5 + p) * 2 + wg) * 16384, R + ((p & 3) * 2 + wg) * 16384, 16384);
          bulk_commit();
          bulk_wait0();
          asm volatile("fence.proxy.async;" ::: "memory");
          asm volatile("red.release.gpu.global.add.u32 [%0],1;" ::"l"(g_cnt + mb * 5 + p) : "memory");
          if (p == 0) mbar_arrive(sfree + wg * 8);
        }
      }
    }
  } else {
    REG_INC(240);
    uint32_t a[36][4];
    const int rowl = warp * 16, wg = warp >> 2;
    pdl_wait();
    if (tid == 0) TS(4, 1);
    {
      const int g = lane >> 2, cq = lane & 3;
      const uint4 s0 = ln2_consts(mb * 128 + rowl + g, cq), s1 = ln2_consts(mb * 128 + rowl + g + 8, cq);
#pragma unroll
      for (int c = 0; c < 9; c++) {
        if (c < 8) { mbar_wait(xfull + c * 8, 0); load_a_chunk(&a[c * 4], R + c * 16384, rowl, lane); }
        else { mbar_wait(full, 0); load_a_chunk(&a[32], RING, rowl, lane); __syncwarp(); if (lane == 0) mbar_arrive(empty); }
#pragma unroll
        for (int k = c * 4; k < c * 4 + 4; k++) {
          const uint4 t = g_tab2[k * 4 + cq];
          a[k][0] = ln_apply(a[k][0], s0, t.x, t.y);
          a[k][1] = ln_apply(a[k][1], s1, t.x, t.y);
          a[k][2] = ln_apply(a[k][2], s0, t.z, t.w);
          a[k][3] = ln_apply(a[k][3], s1, t.z, t.w);
        }
      }
    }
    bar_sync(4, 256);
    if (tid == 0) TS(4, 2);
    Ring ring{RING, full, empty, 1, 0};
    float acc[64];
    const uint32_t hsp = R + tid * 16;
#pragma unroll 1
    for (int t = 0; t < 8; t++) {
      MMA_TILE(wg_rs_n128_t1, acc, a, ring, lane);
#pragma unroll
      for (int j = 0; j < 4; j++) {
        uint32_t h[4];
#pragma unroll
        for (int e = 0; e < 4; e++) h[e] = glu_pair(acc[8 * j + 2 * e], acc[8 * j + 2 * e + 1], acc[32 + 8 * j + 2 * e], acc[32 + 8 * j + 2 * e + 1]);
        asm volatile("st.shared.v4.b32 [%0],{%1,%2,%3,%4};" ::"r"(hsp + t * 16384 + j * 4096), "r"(h[0]), "r"(h[1]), "r"(h[2]), "r"(h[3]) : "memory");
      }
    }
    MMA_TILE(wg_rs_n128_t1, acc, a, ring, lane);
#pragma unroll
    for (int j = 0; j < 4; j++)
#pragma unroll
      for (int e = 0; e < 4; e++)
        a[32 + j][e] = glu_pair(acc[8 * j + 2 * e], acc[8 * j + 2 * e + 1], acc[32 + 8 * j + 2 * e], acc[32 + 8 * j + 2 * e + 1]);
#pragma unroll
    for (int k = 0; k < 32; k++)
      asm volatile("ld.shared.v4.b32 {%0,%1,%2,%3},[%4];" : "=r"(a[k][0]), "=r"(a[k][1]), "=r"(a[k][2]), "=r"(a[k][3]) : "r"(hsp + k * 4096) : "memory");
    if (tid == 0) TS(4, 3);
    bar_sync(4, 256);
    if (tid == 0) TS(4, 4);
#pragma unroll 1
    for (int p = 0; p < 4; p++) {
      MMA_TILE(wg_rs_n128_t1, acc, a, ring, lane);
      stage_part<16>(acc, R + (p * 2 + wg) * 16384, (warp & 3) * 16, lane);
      fence_async_smem();
      __syncwarp();
      if (lane == 0) mbar_arrive(sfull + wg * 8);
    }
    MMA_TILE(wg_rs_n64_t1, acc, a, ring, lane);
    mbar_wait(sfree + wg * 8, 0);
    stage_part<8>(acc, R + wg * 16384, (warp & 3) * 16, lane);
    fence_async_smem();
    __syncwarp();
    if (lane == 0) mbar_arrive(sfull + wg * 8);
    if (tid == 0) TS(4, 5);
    const int rl = fb * 16 + (tid >> 4), ch = tid & 15;
    const uint8_t* src = g_part + ((size_t)(mb * 5) * 2 + (rl >> 6)) * 16384 + (rl & 63) * 256 + ((ch ^ (rl & 7)) << 4);
    const size_t off = (size_t)(mb * 128 + rl) * DM + ch * 8;
#pragma unroll
    for (int p = 0; p < 5; p++) {
      if (p == 4 && ch >= 8) break;
      const uint4 xv = *(const uint4*)(g_x1 + off + p * 128);
      const float4 g0 = *(const float4*)(g_gb + p * 128 + ch * 8), g1 = *(const float4*)(g_gb + p * 128 + ch * 8 + 4);
      if (p == 0 || p == 4) {
        const int pl = p == 0 ? 3 : 4;
        for (int pp = p; pp <= pl; pp++) {
          unsigned int v; int n = 0;
          do {
            asm volatile("ld.acquire.gpu.global.u32 %0,[%1];" : "=r"(v) : "l"(g_cnt + mb * 5 + pp) : "memory");
          } while (v < 16 && ++n < 20000000);
          if (v < 16) __trap();
        }
      }
      uint4 v[8];
#pragma unroll
      for (int f = 0; f < 8; f++) v[f] = __ldcg((const uint4*)(src + p * 32768 + (size_t)f * (16 * 5 * 2 * 16384)));
      float r8[8] = {0, 0, 0, 0, 0, 0, 0, 0};
#pragma unroll
      for (int f = 0; f < 8; f++) {
        r8[0] += bf_lo(v[f].x); r8[1] += bf_hi(v[f].x); r8[2] += bf_lo(v[f].y); r8[3] += bf_hi(v[f].y);
        r8[4] += bf_lo(v[f].z); r8[5] += bf_hi(v[f].z); r8[6] += bf_lo(v[f].w); r8[7] += bf_hi(v[f].w);
      }
      uint4 r;
      r.x = pack_bf16(bf_lo(xv.x) + rbf(g0.x * rbf(r8[0])), bf_hi(xv.x) + rbf(g0.y * rbf(r8[1])));
      r.y = pack_bf16(bf_lo(xv.y) + rbf(g0.z * rbf(r8[2])), bf_hi(xv.y) + rbf(g0.w * rbf(r8[3])));
      r.z = pack_bf16(bf_lo(xv.z) + rbf(g1.x * rbf(r8[4])), bf_hi(xv.z) + rbf(g1.y * rbf(r8[5])));
      r.w = pack_bf16(bf_lo(xv.w) + rbf(g1.z * rbf(r8[6])), bf_hi(xv.w) + rbf(g1.w * rbf(r8[7])));
      *(uint4*)(out + off + p * 128) = r;
      if (tid == 0 && p >= 3) TS(4, 3 + p);
    }
  }
}

typedef CUresult (*EncodeFn)(CUtensorMap*, CUtensorMapDataType, cuuint32_t, void*, const cuuint64_t*, const cuuint64_t*,
                             const cuuint32_t*, const cuuint32_t*, CUtensorMapInterleave, CUtensorMapSwizzle,
                             CUtensorMapL2promotion, CUtensorMapFloatOOBfill);
static void make_map(EncodeFn fn, CUtensorMap* m, const void* p, int rows, int cols, int box_rows) {
  cuuint64_t dims[2] = {(cuuint64_t)cols, (cuuint64_t)rows};
  cuuint64_t strides[1] = {(cuuint64_t)cols * 2};
  cuuint32_t box[2] = {64, (cuuint32_t)box_rows};
  cuuint32_t es[2] = {1, 1};
  fn(m, CU_TENSOR_MAP_DATA_TYPE_BFLOAT16, 2, (void*)p, dims, strides, box, es, CU_TENSOR_MAP_INTERLEAVE_NONE,
     CU_TENSOR_MAP_SWIZZLE_128B, CU_TENSOR_MAP_L2_PROMOTION_L2_256B, CU_TENSOR_MAP_FLOAT_OOB_FILL_NONE);
}
template <typename... KA, typename... A>
static void launch(void (*k)(KA...), int grid, int block, int smem, bool pdl, A... args) {
  cudaLaunchConfig_t cfg = {};
  cfg.gridDim = dim3(grid); cfg.blockDim = dim3(block); cfg.dynamicSmemBytes = smem; cfg.stream = cudaStreamPerThread;
  cudaLaunchAttribute at;
  at.id = cudaLaunchAttributeProgrammaticStreamSerialization;
  at.val.programmaticStreamSerializationAllowed = 1;
  cfg.attrs = &at; cfg.numAttrs = pdl ? 1 : 0;
  cudaLaunchKernelEx(&cfg, k, KA(args)...);
}

extern "C" void kernel_launch(void* const* d_in, const int* in_sizes, int n_in, void* d_out, int out_size) {
  const __nv_bfloat16* x = (const __nv_bfloat16*)d_in[0];
  void* fnp = nullptr;
  cudaDriverEntryPointQueryResult qr;
  cudaGetDriverEntryPoint("cuTensorMapEncodeTiled", &fnp, cudaEnableDefault, &qr);
  EncodeFn fn = (EncodeFn)fnp;
  void *po, *px1;
  cudaGetSymbolAddress(&po, g_o);
  cudaGetSymbolAddress(&px1, g_x1);
  CUtensorMap mx, mqkv, mo, mwo, mx1, mg, mu, md;
  make_map(fn, &mx, x, SEQ, DM, 128);
  make_map(fn, &mqkv, d_in[1], DM, 3 * DM, 64);
  make_map(fn, &mo, po, SEQ, DM, 128);
  make_map(fn, &mwo, d_in[2], DM, DM, 64);
  make_map(fn, &mx1, px1, SEQ, DM, 128);
  make_map(fn, &mg, d_in[4], DM, FF, 64);
  make_map(fn, &mu, d_in[5], DM, FF, 64);
  make_map(fn, &md, d_in[6], FF, DM, 64);
  cudaFuncSetAttribute(k1_kernel, cudaFuncAttributeMaxDynamicSharedMemorySize, GEMM_SMEM);
  cudaFuncSetAttribute(k2_kernel, cudaFuncAttributeMaxDynamicSharedMemorySize, ATT_SMEM);
  cudaFuncSetAttribute(k3_kernel, cudaFuncAttributeMaxDynamicSharedMemorySize, K3_SMEM);
  cudaFuncSetAttribute(k4_kernel, cudaFuncAttributeMaxDynamicSharedMemorySize, GEMM_SMEM);
  launch(k0_kernel, 108 + 128, 256, 0, false, x, (const __nv_bfloat16*)d_in[7], (const __nv_bfloat16*)d_in[8]);
  launch(k1_kernel, 128, 384, GEMM_SMEM, true, mx, mqkv);
  launch(k2_kernel, 128, 512, ATT_SMEM, true);
  launch(k3_kernel, 128, 288, K3_SMEM, true, mo, mwo, x);
  launch(k4_kernel, 128, 384, GEMM_SMEM, true, mx1, mg, mu, md, (__nv_bfloat16*)d_out);
}
```

```cpp
#include <cuda_runtime.h>
#include <cuda_bf16.h>
#include <cuda.h>
#include <stdint.h>

#define SEQ 2048
#define DM 576
#define NH 32
#define FF 4608

__device__ uint4 g_tab1[36 * 4];
__device__ uint4 g_tab2[36 * 4];
__device__ float g_ga[DM];
__device__ __align__(16) __nv_bfloat16 g_gb[DM];
__device__ uint4 g_stat1[SEQ];
__device__ float2 g_stat2[SEQ * 8];
__device__ __align__(1024) uint8_t g_qkv[96 * 98304];
__device__ float g_kmax[NH * 16];
__device__ __align__(1024) __nv_bfloat16 g_o[SEQ * DM];
__device__ __align__(1024) __nv_bfloat16 g_x1[SEQ * DM];
__device__ __align__(1024) uint8_t g_part[8 * 16 * 5 * 2 * 16384];
__device__ unsigned int g_cnt[16 * 5];

#define TS(k, i)
__device__ __forceinline__ uint32_t s2u(const void* p) { return (uint32_t)__cvta_generic_to_shared(p); }
__device__ __forceinline__ void mbar_init(uint32_t b, int c) { asm volatile("mbarrier.init.shared::cta.b64 [%0],%1;" ::"r"(b), "r"(c)); }
__device__ __forceinline__ void mbar_expect(uint32_t b, uint32_t n) { asm volatile("mbarrier.arrive.expect_tx.shared::cta.b64 _,[%0],%1;" ::"r"(b), "r"(n) : "memory"); }
__device__ __forceinline__ void mbar_arrive(uint32_t b) { asm volatile("mbarrier.arrive.shared::cta.b64 _,[%0];" ::"r"(b) : "memory"); }
__device__ __forceinline__ void mbar_wait(uint32_t b, uint32_t ph) {
  asm volatile(
      "{.reg .pred p; .reg .u32 n; mov.u32 n,0;\n"
      "W: mbarrier.try_wait.parity.shared::cta.b64 p,[%0],%1;\n"
      "@p bra D;\n"
      "add.u32 n,n,1; setp.lt.u32 p,n,4000000; @p bra W;\n"
      "trap;\n"
      "D: }" ::"r"(b), "r"(ph) : "memory");
}
__device__ __forceinline__ void tma2d(uint32_t dst, const CUtensorMap* m, int c0, int c1, uint32_t bar) {
  asm volatile("cp.async.bulk.tensor.2d.shared::cluster.global.mbarrier::complete_tx::bytes [%0],[%1,{%3,%4}],[%2];"
               ::"r"(dst), "l"(m), "r"(bar), "r"(c0), "r"(c1) : "memory");
}
__device__ __forceinline__ void bulk_g2s(uint32_t dst, const void* src, uint32_t bytes, uint32_t bar) {
  asm volatile("cp.async.bulk.shared::cluster.global.mbarrier::complete_tx::bytes [%0],[%1],%2,[%3];"
               ::"r"(dst), "l"(src), "r"(bytes), "r"(bar) : "memory");
}
__device__ __forceinline__ void bulk_s2g(void* dst, uint32_t src, uint32_t bytes) {
  asm volatile("cp.async.bulk.global.shared::cta.bulk_group [%0],[%1],%2;" ::"l"(dst), "r"(src), "r"(bytes) : "memory");
}
__device__ __forceinline__ void bulk_commit() { asm volatile("cp.async.bulk.commit_group;" ::: "memory"); }
__device__ __forceinline__ void bulk_wait0() { asm volatile("cp.async.bulk.wait_group 0;" ::: "memory"); }
__device__ __forceinline__ void prefetch_map(const CUtensorMap* m) { asm volatile("prefetch.tensormap [%0];" ::"l"(m) : "memory"); }
__device__ __forceinline__ void fence_async_smem() { asm volatile("fence.proxy.async.shared::cta;" ::: "memory"); }
__device__ __forceinline__ void fence_bar_init() { asm volatile("fence.mbarrier_init.release.cluster;" ::: "memory"); }
__device__ __forceinline__ void pdl_wait() { asm volatile("griddepcontrol.wait;" ::: "memory"); }
__device__ __forceinline__ void pdl_launch() { asm volatile("griddepcontrol.launch_dependents;" ::: "memory"); }
__device__ __forceinline__ void bar_sync(int id, int n) { asm volatile("bar.sync %0,%1;" ::"r"(id), "r"(n) : "memory"); }
__device__ __forceinline__ void bar_arrive(int id, int n) { asm volatile("bar.arrive %0,%1;" ::"r"(id), "r"(n) : "memory"); }
#define WG_FENCE() asm volatile("wgmma.fence.sync.aligned;" ::: "memory")
#define WG_COMMIT() asm volatile("wgmma.commit_group.sync.aligned;" ::: "memory")
#define WG_WAIT(n) asm volatile("wgmma.wait_group.sync.aligned " #n ";" ::: "memory")
template <int N> __device__ __forceinline__ void fence_regs(float* r) {
#pragma unroll
  for (int i = 0; i < N; i++) asm volatile("" : "+f"(r[i])::"memory");
}
#define REG_INC(n) asm volatile("setmaxnreg.inc.sync.aligned.u32 " #n ";")
#define REG_DEC(n) asm volatile("setmaxnreg.dec.sync.aligned.u32 " #n ";")
__device__ __forceinline__ uint64_t mkdesc(uint32_t addr, uint32_t lbo, uint32_t sbo, int sw) {
  return (uint64_t)((addr & 0x3FFFF) >> 4) | ((uint64_t)(lbo >> 4) << 16) | ((uint64_t)(sbo >> 4) << 32) | ((uint64_t)sw << 62);
}
__device__ __forceinline__ void ldsm4(uint32_t* r, uint32_t addr) {
  asm volatile("ldmatrix.sync.aligned.m8n8.x4.shared.b16 {%0,%1,%2,%3},[%4];" : "=r"(r[0]), "=r"(r[1]), "=r"(r[2]), "=r"(r[3]) : "r"(addr) : "memory");
}
__device__ __forceinline__ void stsm4(uint32_t addr, uint32_t r0, uint32_t r1, uint32_t r2, uint32_t r3) {
  asm volatile("stmatrix.sync.aligned.m8n8.x4.shared.b16 [%0],{%1,%2,%3,%4};" ::"r"(addr), "r"(r0), "r"(r1), "r"(r2), "r"(r3) : "memory");
}
__device__ __forceinline__ uint32_t pack_bf16(float lo, float hi) {
  uint32_t r;
  asm("cvt.rn.bf16x2.f32 %0,%1,%2;" : "=r"(r) : "f"(hi), "f"(lo));
  return r;
}
__device__ __forceinline__ float bf_lo(uint32_t v) { return __uint_as_float(v << 16); }
__device__ __forceinline__ float bf_hi(uint32_t v) { return __uint_as_float(v & 0xFFFF0000u); }
__device__ __forceinline__ float rbf(float x) { return __bfloat162float(__float2bfloat16_rn(x)); }
__device__ __forceinline__ uint32_t hfma2(uint32_t a, uint32_t b, uint32_t c) {
  uint32_t r;
  asm("fma.rn.bf16x2 %0,%1,%2,%3;" : "=r"(r) : "r"(a), "r"(b), "r"(c));
  return r;
}
__device__ __forceinline__ uint32_t hadd2(uint32_t a, uint32_t b) {
  uint32_t r;
  asm("add.rn.bf16x2 %0,%1,%2;" : "=r"(r) : "r"(a), "r"(b));
  return r;
}
__device__ __forceinline__ uint32_t hmul2(uint32_t a, uint32_t b) {
  uint32_t r;
  asm("mul.rn.bf16x2 %0,%1,%2;" : "=r"(r) : "r"(a), "r"(b));
  return r;
}
__device__ __forceinline__ uint32_t hneg2(uint32_t a) {
  uint32_t r;
  asm("neg.bf16x2 %0,%1;" : "=r"(r) : "r"(a));
  return r;
}
__device__ __forceinline__ float ex2f(float x) {
  float r;
  asm("ex2.approx.ftz.f32 %0,%1;" : "=f"(r) : "f"(x));
  return r;
}
__device__ __forceinline__ float sqrt_fast(float x) {
  float r;
  asm("sqrt.approx.f32 %0,%1;" : "=f"(r) : "f"(x));
  return r;
}
__device__ __forceinline__ float rcp_fast(float x) {
  float r;
  asm("rcp.approx.f32 %0,%1;" : "=f"(r) : "f"(x));
  return r;
}
__device__ __forceinline__ float tanhf_fast(float x) {
  float r;
  asm("tanh.approx.f32 %0,%1;" : "=f"(r) : "f"(x));
  return r;
}
__device__ __forceinline__ uint4 ln_consts(float mean, float var) {
  float m = rbf(mean), v = rbf(var);
  float s = rbf(sqrtf(rbf(v + 1e-5f)));
  float r = 1.0f / s;
  float rh = rbf(r), rl = r - rh;
  return make_uint4(pack_bf16(-m, -m), pack_bf16(rh, rh), pack_bf16(rl, rl), 0u);
}
__device__ __forceinline__ uint32_t ln_apply(uint32_t x, const uint4& st, uint32_t a, uint32_t s) {
  uint32_t d = hadd2(x, st.x);
  uint32_t n = hfma2(d, st.y, hmul2(d, st.z));
  return hfma2(n, a, s);
}

__device__ __forceinline__ void wg_rs_n128_t1(float* d, uint32_t a0, uint32_t a1, uint32_t a2, uint32_t a3, uint64_t db, int sc) {
  asm volatile("{.reg .pred p; setp.ne.b32 p,%69,0; wgmma.mma_async.sync.aligned.m64n128k16.f32.bf16.bf16 {%0,%1,%2,%3,%4,%5,%6,%7,%8,%9,%10,%11,%12,%13,%14,%15,%16,%17,%18,%19,%20,%21,%22,%23,%24,%25,%26,%27,%28,%29,%30,%31,%32,%33,%34,%35,%36,%37,%38,%39,%40,%41,%42,%43,%44,%45,%46,%47,%48,%49,%50,%51,%52,%53,%54,%55,%56,%57,%58,%59,%60,%61,%62,%63}, {%64,%65,%66,%67}, %68, p,1,1,1;}"
  : "+f"(d[0]),"+f"(d[1]),"+f"(d[2]),"+f"(d[3]),"+f"(d[4]),"+f"(d[5]),"+f"(d[6]),"+f"(d[7]),"+f"(d[8]),"+f"(d[9]),"+f"(d[10]),"+f"(d[11]),"+f"(d[12]),"+f"(d[13]),"+f"(d[14]),"+f"(d[15]),"+f"(d[16]),"+f"(d[17]),"+f"(d[18]),"+f"(d[19]),"+f"(d[20]),"+f"(d[21]),"+f"(d[22]),"+f"(d[23]),"+f"(d[24]),"+f"(d[25]),"+f"(d[26]),"+f"(d[27]),"+f"(d[28]),"+f"(d[29]),"+f"(d[30]),"+f"(d[31]),"+f"(d[32]),"+f"(d[33]),"+f"(d[34]),"+f"(d[35]),"+f"(d[36]),"+f"(d[37]),"+f"(d[38]),"+f"(d[39]),"+f"(d[40]),"+f"(d[41]),"+f"(d[42]),"+f"(d[43]),"+f"(d[44]),"+f"(d[45]),"+f"(d[46]),"+f"(d[47]),"+f"(d[48]),"+f"(d[49]),"+f"(d[50]),"+f"(d[51]),"+f"(d[52]),"+f"(d[53]),"+f"(d[54]),"+f"(d[55]),"+f"(d[56]),"+f"(d[57]),"+f"(d[58]),"+f"(d[59]),"+f"(d[60]),"+f"(d[61]),"+f"(d[62]),"+f"(d[63]) : "r"(a0),"r"(a1),"r"(a2),"r"(a3),"l"(db),"r"(sc));
}
__device__ __forceinline__ void wg_rs_n64_t1(float* d, uint32_t a0, uint32_t a1, uint32_t a2, uint32_t a3, uint64_t db, int sc) {
  asm volatile("{.reg .pred p; setp.ne.b32 p,%37,0; wgmma.mma_async.sync.aligned.m64n64k16.f32.bf16.bf16 {%0,%1,%2,%3,%4,%5,%6,%7,%8,%9,%10,%11,%12,%13,%14,%15,%16,%17,%18,%19,%20,%21,%22,%23,%24,%25,%26,%27,%28,%29,%30,%31}, {%32,%33,%34,%35}, %36, p,1,1,1;}"
  : "+f"(d[0]),"+f"(d[1]),"+f"(d[2]),"+f"(d[3]),"+f"(d[4]),"+f"(d[5]),"+f"(d[6]),"+f"(d[7]),"+f"(d[8]),"+f"(d[9]),"+f"(d[10]),"+f"(d[11]),"+f"(d[12]),"+f"(d[13]),"+f"(d[14]),"+f"(d[15]),"+f"(d[16]),"+f"(d[17]),"+f"(d[18]),"+f"(d[19]),"+f"(d[20]),"+f"(d[21]),"+f"(d[22]),"+f"(d[23]),"+f"(d[24]),"+f"(d[25]),"+f"(d[26]),"+f"(d[27]),"+f"(d[28]),"+f"(d[29]),"+f"(d[30]),"+f"(d[31]) : "r"(a0),"r"(a1),"r"(a2),"r"(a3),"l"(db),"r"(sc));
}
__device__ __forceinline__ void wg_rs_n88_t1(float* d, uint32_t a0, uint32_t a1, uint32_t a2, uint32_t a3, uint64_t db, int sc) {
  asm volatile("{.reg .pred p; setp.ne.b32 p,%49,0; wgmma.mma_async.sync.aligned.m64n88k16.f32.bf16.bf16 {%0,%1,%2,%3,%4,%5,%6,%7,%8,%9,%10,%11,%12,%13,%14,%15,%16,%17,%18,%19,%20,%21,%22,%23,%24,%25,%26,%27,%28,%29,%30,%31,%32,%33,%34,%35,%36,%37,%38,%39,%40,%41,%42,%43}, {%44,%45,%46,%47}, %48, p,1,1,1;}"
  : "+f"(d[0]),"+f"(d[1]),"+f"(d[2]),"+f"(d[3]),"+f"(d[4]),"+f"(d[5]),"+f"(d[6]),"+f"(d[7]),"+f"(d[8]),"+f"(d[9]),"+f"(d[10]),"+f"(d[11]),"+f"(d[12]),"+f"(d[13]),"+f"(d[14]),"+f"(d[15]),"+f"(d[16]),"+f"(d[17]),"+f"(d[18]),"+f"(d[19]),"+f"(d[20]),"+f"(d[21]),"+f"(d[22]),"+f"(d[23]),"+f"(d[24]),"+f"(d[25]),"+f"(d[26]),"+f"(d[27]),"+f"(d[28]),"+f"(d[29]),"+f"(d[30]),"+f"(d[31]),"+f"(d[32]),"+f"(d[33]),"+f"(d[34]),"+f"(d[35]),"+f"(d[36]),"+f"(d[37]),"+f"(d[38]),"+f"(d[39]),"+f"(d[40]),"+f"(d[41]),"+f"(d[42]),"+f"(d[43]) : "r"(a0),"r"(a1),"r"(a2),"r"(a3),"l"(db),"r"(sc));
}
__device__ __forceinline__ void wg_ss_n72_t1(float* d, uint64_t da, uint64_t db, int sc) {
  asm volatile("{.reg .pred p; setp.ne.b32 p,%38,0; wgmma.mma_async.sync.aligned.m64n72k16.f32.bf16.bf16 {%0,%1,%2,%3,%4,%5,%6,%7,%8,%9,%10,%11,%12,%13,%14,%15,%16,%17,%18,%19,%20,%21,%22,%23,%24,%25,%26,%27,%28,%29,%30,%31,%32,%33,%34,%35}, %36, %37, p,1,1,0,1;}"
  : "+f"(d[0]),"+f"(d[1]),"+f"(d[2]),"+f"(d[3]),"+f"(d[4]),"+f"(d[5]),"+f"(d[6]),"+f"(d[7]),"+f"(d[8]),"+f"(d[9]),"+f"(d[10]),"+f"(d[11]),"+f"(d[12]),"+f"(d[13]),"+f"(d[14]),"+f"(d[15]),"+f"(d[16]),"+f"(d[17]),"+f"(d[18]),"+f"(d[19]),"+f"(d[20]),"+f"(d[21]),"+f"(d[22]),"+f"(d[23]),"+f"(d[24]),"+f"(d[25]),"+f"(d[26]),"+f"(d[27]),"+f"(d[28]),"+f"(d[29]),"+f"(d[30]),"+f"(d[31]),"+f"(d[32]),"+f"(d[33]),"+f"(d[34]),"+f"(d[35]) : "l"(da),"l"(db),"r"(sc));
}
template <int SC> __device__ __forceinline__ void wl_rs_n24_t1(float* d, const uint32_t* a, uint64_t e) {
  asm volatile("wgmma.mma_async.sync.aligned.m64n24k16.f32.bf16.bf16 {%0,%1,%2,%3,%4,%5,%6,%7,%8,%9,%10,%11}, {%12,%13,%14,%15}, %16, %17,1,1,1;"
  : "+f"(d[0]),"+f"(d[1]),"+f"(d[2]),"+f"(d[3]),"+f"(d[4]),"+f"(d[5]),"+f"(d[6]),"+f"(d[7]),"+f"(d[8]),"+f"(d[9]),"+f"(d[10]),"+f"(d[11]) : "r"(a[0]),"r"(a[1]),"r"(a[2]),"r"(a[3]),"l"(e),"n"(SC));
}
template <int SC> __device__ __forceinline__ void wl_rs_n64_t0(float* d, const uint32_t* a, uint64_t e) {
  asm volatile("wgmma.mma_async.sync.aligned.m64n64k16.f32.bf16.bf16 {%0,%1,%2,%3,%4,%5,%6,%7,%8,%9,%10,%11,%12,%13,%14,%15,%16,%17,%18,%19,%20,%21,%22,%23,%24,%25,%26,%27,%28,%29,%30,%31}, {%32,%33,%34,%35}, %36, %37,1,1,0;"
  : "+f"(d[0]),"+f"(d[1]),"+f"(d[2]),"+f"(d[3]),"+f"(d[4]),"+f"(d[5]),"+f"(d[6]),"+f"(d[7]),"+f"(d[8]),"+f"(d[9]),"+f"(d[10]),"+f"(d[11]),"+f"(d[12]),"+f"(d[13]),"+f"(d[14]),"+f"(d[15]),"+f"(d[16]),"+f"(d[17]),"+f"(d[18]),"+f"(d[19]),"+f"(d[20]),"+f"(d[21]),"+f"(d[22]),"+f"(d[23]),"+f"(d[24]),"+f"(d[25]),"+f"(d[26]),"+f"(d[27]),"+f"(d[28]),"+f"(d[29]),"+f"(d[30]),"+f"(d[31]) : "r"(a[0]),"r"(a[1]),"r"(a[2]),"r"(a[3]),"l"(e),"n"(SC));
}

#define POLY_MASK 0xB5u
#define QSCALE (0.23570226039551584f * 1.4426950408889634f)

__device__ __forceinline__ void pf_l2(const void* p) { asm volatile("prefetch.global.L2 [%0];" ::"l"(p)); }
__global__ void __launch_bounds__(256) k0_kernel(const __nv_bfloat16* __restrict__ x, const __nv_bfloat16* __restrict__ c,
                                                 const __nv_bfloat16* __restrict__ wmod) {
  if (threadIdx.x == 0) TS(0, 0);
  pdl_launch();
  const int tid = threadIdx.x, lane = tid & 31, warp = tid >> 5;
  if (blockIdx.x < 108) {
    __shared__ float red[8][32];
    const int col0 = blockIdx.x * 32 + (tid & 3) * 8, r0 = tid >> 2;
    uint4 w[9];
#pragma unroll
    for (int i = 0; i < 9; i++) w[i] = __ldg((const uint4*)(wmod + (size_t)(r0 + 64 * i) * 3456 + col0));
    float acc[8] = {0, 0, 0, 0, 0, 0, 0, 0};
#pragma unroll
    for (int i = 0; i < 9; i++) {
      float cv = __bfloat162float(c[r0 + 64 * i]);
      float sv = rbf(cv / (1.0f + __expf(-cv)));
      acc[0] += sv * bf_lo(w[i].x); acc[1] += sv * bf_hi(w[i].x);
      acc[2] += sv * bf_lo(w[i].y); acc[3] += sv * bf_hi(w[i].y);
      acc[4] += sv * bf_lo(w[i].z); acc[5] += sv * bf_hi(w[i].z);
      acc[6] += sv * bf_lo(w[i].w); acc[7] += sv * bf_hi(w[i].w);
    }
#pragma unroll
    for (int j = 0; j < 8; j++) {
      acc[j] += __shfl_xor_sync(~0u, acc[j], 4);
      acc[j] += __shfl_xor_sync(~0u, acc[j], 8);
      acc[j] += __shfl_xor_sync(~0u, acc[j], 16);
    }
    if (lane < 4) {
#pragma unroll
      for (int j = 0; j < 8; j++) red[warp][lane * 8 + j] = acc[j];
    }
    __syncthreads();
    if (tid < 32) {
      float s = 0;
#pragma unroll
      for (int j = 0; j < 8; j++) s += red[j][tid];
      s = rbf(s);
      int n = blockIdx.x * 32 + tid, part = n / DM, col = n % DM;
      if (part == 2) g_ga[col] = s;
      else if (part == 5) g_gb[col] = __float2bfloat16_rn(s);
      else {
        __nv_bfloat16* tab = (__nv_bfloat16*)(part < 2 ? g_tab1 : g_tab2);
        bool shift = (part == 0 || part == 3);
        int kk = col >> 4, half = (col >> 3) & 1, cq = (col & 7) >> 1, e = col & 1;
        tab[((kk * 4 + cq) * 4 + half * 2 + (shift ? 1 : 0)) * 2 + e] = __float2bfloat16_rn(shift ? s : 1.0f + s);
      }
    }
    if (blockIdx.x == 0 && tid >= 64 && tid < 64 + 80) g_cnt[tid - 64] = 0;
  } else {
    const int row0 = (blockIdx.x - 108) * 16 + warp * 2;
    uint32_t v[2][9];
#pragma unroll
    for (int r = 0; r < 2; r++)
#pragma unroll
      for (int i = 0; i < 9; i++) v[r][i] = __ldg((const uint32_t*)(x + (size_t)(row0 + r) * DM) + lane + 32 * i);
#pragma unroll
    for (int r = 0; r < 2; r++) {
      float s = 0;
#pragma unroll
      for (int i = 0; i < 9; i++) s += bf_lo(v[r][i]) + bf_hi(v[r][i]);
#pragma unroll
      for (int o = 16; o; o >>= 1) s += __shfl_xor_sync(~0u, s, o);
      float mean = s * (1.0f / DM), q = 0;
#pragma unroll
      for (int i = 0; i < 9; i++) {
        float a = bf_lo(v[r][i]) - mean, b = bf_hi(v[r][i]) - mean;
        q += a * a + b * b;
      }
#pragma unroll
      for (int o = 16; o; o >>= 1) q += __shfl_xor_sync(~0u, q, o);
      if (lane == 0) g_stat1[row0 + r] = ln_consts(mean, q * (1.0f / DM));
    }
  }
  if (threadIdx.x == 0) TS(0, 1);
}

#define NSTG 6
#define STG_BYTES 16384
#define R_BYTES (8 * 16384)
#define GEMM_SMEM (R_BYTES + NSTG * STG_BYTES + 3072)

struct Ring {
  uint32_t base, full, empty;
  int st;
  uint32_t ph;
  __device__ __forceinline__ void next() { if (++st == NSTG) { st = 0; ph ^= 1; } }
};

__device__ __forceinline__ void load_a_chunk(uint32_t (*a)[4], uint32_t chunk_base, int row_in_tile, int lane) {
  const int r = row_in_tile + (lane & 7) + ((lane >> 3) & 1) * 8;
  const uint32_t rb = chunk_base + r * 128;
#pragma unroll
  for (int k = 0; k < 4; k++) ldsm4(a[k], rb + (((k * 2 + (lane >> 4)) ^ (r & 7)) << 4));
}

#define MMA_TILE(FN, acc, a, ring, lane)                                        \
  {                                                                             \
    uint32_t prev_empty = 0;                                                    \
    _Pragma("unroll") for (int s = 0; s < 9; s++) {                             \
      mbar_wait(ring.full + ring.st * 8, ring.ph);                              \
      WG_FENCE();                                                               \
      uint32_t sa_ = ring.base + ring.st * STG_BYTES;                           \
      asm volatile("" : "+r"(sa_));                                             \
      uint64_t db = mkdesc(sa_, 8192, 1024, 1);                                 \
      _Pragma("unroll") for (int k = 0; k < 4; k++)                             \
          FN(acc, a[s * 4 + k][0], a[s * 4 + k][1], a[s * 4 + k][2], a[s * 4 + k][3], db + k * 128, (s | k) != 0); \
      WG_COMMIT();                                                              \
      if (s > 0) { WG_WAIT(1); if (lane == 0) mbar_arrive(prev_empty); }        \
      prev_empty = ring.empty + ring.st * 8;                                    \
      ring.next();                                                              \
    }                                                                           \
    WG_WAIT(0);                                                                 \
    if (lane == 0) mbar_arrive(prev_empty);                                     \
  }

template <int NG, int G0>
__device__ __forceinline__ void qkv_stage(const float* acc, uint32_t stg, int rowl, int cq, int col_base) {
  const float vs0 = ((POLY_MASK >> ((rowl >> 3) & 7)) & 1) ? 0.5f : 1.0f, vs1 = ((POLY_MASK >> (((rowl >> 3) + 1) & 7)) & 1) ? 0.5f : 1.0f;
#pragma unroll
  for (int i = 0; i < NG; i++) {
    const int cc = (G0 + i) * 8 + cq * 2;
    const int slot = (cc * 3641) >> 16, d = cc - slot * 18;
    const int gc = col_base + cc;
    const float sc0 = gc < DM ? QSCALE : (gc < 2 * DM ? vs0 : 1.0f), sc1 = gc < DM ? QSCALE : (gc < 2 * DM ? vs1 : 1.0f);
    const uint32_t ad = stg + slot * 6144 + (d >> 3) * 128 + (d & 7) * 2 + (rowl >> 3) * 384 + (rowl & 7) * 16;
    asm volatile("st.shared.b32 [%0],%1;" ::"r"(ad), "r"(pack_bf16(acc[4 * i] * sc0, acc[4 * i + 1] * sc0)) : "memory");
    asm volatile("st.shared.b32 [%0],%1;" ::"r"(ad + 384), "r"(pack_bf16(acc[4 * i + 2] * sc1, acc[4 * i + 3] * sc1)) : "memory");
  }
}

__global__ void __launch_bounds__(384, 1) k1_kernel(const __grid_constant__ CUtensorMap mx, const __grid_constant__ CUtensorMap mw) {
  extern __shared__ __align__(1024) uint8_t smem_raw[];
  const uint32_t sb = (s2u(smem_raw) + 1023) & ~1023u;
  const uint32_t R = sb, RING = sb + R_BYTES, BAR = RING + NSTG * STG_BYTES;
  const uint32_t full = BAR, empty = BAR + 64, xfull = BAR + 128;
  const int tid = threadIdx.x, lane = tid & 31, warp = tid >> 5;
  const int mb = blockIdx.x >> 3, nb = blockIdx.x & 7;
  if (tid == 0) {
    TS(1, 0);
    for (int i = 0; i < NSTG; i++) { mbar_init(full + i * 8, 1); mbar_init(empty + i * 8, 8); }
    for (int i = 0; i < 8; i++) mbar_init(xfull + i * 8, 1);
    fence_bar_init();
  }
  __syncthreads();
  pdl_launch();
  if (warp >= 8) {
    REG_DEC(24);
    if (warp == 8) {
      if (lane == 0) {
        for (int c = 0; c < 8; c++) { mbar_expect(xfull + c * 8, 16384); tma2d(R + c * 16384, &mx, c * 64, mb * 128, xfull + c * 8); }
        mbar_expect(full, 16384);
        tma2d(RING, &mx, 512, mb * 128, full);
        int st = 1; uint32_t ph = 0;
        for (int it = 0; it < 18; it++) {
          const int t = it / 9, s = it - t * 9;
          mbar_wait(empty + st * 8, ph ^ 1);
          mbar_expect(full + st * 8, 16384);
          tma2d(RING + st * STG_BYTES, &mw, nb * 216 + t * 128, s * 64, full + st * 8);
          tma2d(RING + st * STG_BYTES + 8192, &mw, nb * 216 + t * 128 + 64, s * 64, full + st * 8);
          if (++st == NSTG) { st = 0; ph ^= 1; }
        }
      }
      pdl_wait();
    } else {
      const int ht = tid - 288;
      bar_sync(1, 352);
      for (int i = ht; i < 12 * 128; i += 96) {
        const int slot = i >> 7, row = i & 127, type = (nb * 12 + slot) >> 5;
        uint32_t v = 0;
        if (type == 1) v = ((POLY_MASK >> ((row >> 3) & 7)) & 1) ? 0x43403F00u : 0x40253F80u;
        if (type == 2) v = 0x3F80u;
        const uint32_t ad = R + slot * 6144 + (row >> 3) * 384 + 256 + (row & 7) * 16;
        asm volatile("st.shared.b32 [%0],%1;" ::"r"(ad + 4), "r"(v) : "memory");
        asm volatile("st.shared.v2.b32 [%0],{%1,%1};" ::"r"(ad + 8), "r"(0) : "memory");
      }
      fence_async_smem();
      pdl_wait();
#pragma unroll 1
      for (int t = 0; t < 2; t++) {
        bar_sync(2 + t, 352);
        const int s0 = t ? 7 : 0, s1 = t ? 12 : 7;
        if (ht == 0) {
          for (int s = s0; s < s1; s++) bulk_s2g(g_qkv + (size_t)(nb * 12 + s) * 98304 + mb * 6144, R + s * 6144, 6144);
          bulk_commit();
        }
        for (int s = s0 + (warp - 9); s < s1; s += 3) {
          const int gs = nb * 12 + s;
          if ((gs >> 5) != 1) continue;
          float mx2 = 0;
#pragma unroll 1
          for (int row = lane; row < 128; row += 32) {
            const uint32_t ad = R + s * 6144 + (row >> 3) * 384 + (row & 7) * 16;
            float q = 0;
#pragma unroll 1
            for (int ch = 0; ch < 3; ch++) {
              uint32_t u0, u1, u2, u3;
              asm volatile("ld.shared.v4.b32 {%0,%1,%2,%3},[%4];" : "=r"(u0), "=r"(u1), "=r"(u2), "=r"(u3) : "r"(ad + ch * 128));
              if (ch == 2) u1 = 0;
              q += bf_lo(u0) * bf_lo(u0) + bf_hi(u0) * bf_hi(u0) + bf_lo(u1) * bf_lo(u1) + bf_hi(u1) * bf_hi(u1);
              q += bf_lo(u2) * bf_lo(u2) + bf_hi(u2) * bf_hi(u2) + bf_lo(u3) * bf_lo(u3) + bf_hi(u3) * bf_hi(u3);
            }
            if ((POLY_MASK >> ((row >> 3) & 7)) & 1) q *= 4.0f;
            mx2 = (q > mx2 || q != q) ? q : mx2;
            if (mx2 != mx2) mx2 = __int_as_float(0x7f800000);
          }
#pragma unroll
          for (int o = 16; o; o >>= 1) mx2 = fmaxf(mx2, __shfl_xor_sync(~0u, mx2, o));
          if (lane == 0) g_kmax[(gs & 31) * 16 + mb] = mx2;
        }
      }
      if (ht == 0) bulk_wait0();
      if (ht == 0) TS(1, 8);
    }
  } else {
    REG_INC(240);
    uint32_t a[36][4];
    const int rowl = warp * 16;
#pragma unroll
    for (int c = 0; c < 8; c++) { mbar_wait(xfull + c * 8, 0); load_a_chunk(&a[c * 4], R + c * 16384, rowl, lane); }
    mbar_wait(full, 0);
    load_a_chunk(&a[32], RING, rowl, lane);
    __syncwarp();
    if (lane == 0) mbar_arrive(empty);
    bar_arrive(1, 352);
    if (tid == 0) TS(1, 1);
    pdl_wait();
    if (tid == 0) TS(1, 2);
    {
      const int g = lane >> 2, cq = lane & 3;
      const uint4 s0 = g_stat1[mb * 128 + rowl + g], s1 = g_stat1[mb * 128 + rowl + g + 8];
#pragma unroll
      for (int k = 0; k < 36; k++) {
        if ((k & 3) == 0) asm volatile("" ::: "memory");
        const uint4 t = g_tab1[k * 4 + cq];
        a[k][0] = ln_apply(a[k][0], s0, t.x, t.y);
        a[k][1] = ln_apply(a[k][1], s1, t.x, t.y);
        a[k][2] = ln_apply(a[k][2], s0, t.z, t.w);
        a[k][3] = ln_apply(a[k][3], s1, t.z, t.w);
      }
    }
    bar_sync(4, 256);
    Ring ring{RING, full, empty, 1, 0};
    float acc[64];
    if (tid == 0) TS(1, 3);
    MMA_TILE(wg_rs_n128_t1, acc, a, ring, lane);
    if (tid == 0) TS(1, 4);
    qkv_stage<16, 0>(acc, R, rowl + (lane >> 2), lane & 3, nb * 216);
    fence_async_smem();
    bar_arrive(2, 352);
    if (tid == 0) TS(1, 5);
    MMA_TILE(wg_rs_n88_t1, acc, a, ring, lane);
    if (tid == 0) TS(1, 6);
    qkv_stage<11, 16>(acc, R, rowl + (lane >> 2), lane & 3, nb * 216);
    fence_async_smem();
    bar_arrive(3, 352);
    if (tid == 0) TS(1, 7);
  }
}

#define ATT_SMEM (2 * 98304 + 1024 + 256)

__device__ __forceinline__ uint32_t exp2_pair_fma(float t0, float t1) {
  uint32_t y;
  asm("prmt.b32 %0,%1,%2,0x6521;" : "=r"(y) : "r"(__float_as_uint(t0)), "r"(__float_as_uint(t1)));
  return hfma2(y, y | 0x3F803F80u, y | 0x007F007Fu);
}

__device__ __forceinline__ void softmax_fast(const float* s, uint32_t* p) {
#pragma unroll
  for (int i = 0; i < 8; i++) {
    if ((POLY_MASK >> i) & 1) {
      p[2 * i] = exp2_pair_fma(s[4 * i], s[4 * i + 1]);
      p[2 * i + 1] = exp2_pair_fma(s[4 * i + 2], s[4 * i + 3]);
    } else {
      p[2 * i] = pack_bf16(ex2f(s[4 * i]), ex2f(s[4 * i + 1]));
      p[2 * i + 1] = pack_bf16(ex2f(s[4 * i + 2]), ex2f(s[4 * i + 3]));
    }
  }
}
#define QK_MMA(S, kd)                                                           \
  wl_rs_n64_t0<0>(S, q, (kd));                                                  \
  wl_rs_n64_t0<1>(S, q + 4, (kd) + 16 - (8ull << 16));
#define PV_MMA(P, vd)                                                           \
  _Pragma("unroll") for (int t = 0; t < 4; t++) wl_rs_n24_t1<1>(o, P + 4 * t, (vd) + t * 48);

__device__ __forceinline__ float sq2(uint32_t v) { return bf_lo(v) * bf_lo(v) + bf_hi(v) * bf_hi(v); }
__device__ __forceinline__ void att_store(const float* o, int row0, int head, int lane) {
  const int cq = lane & 3;
  const float l0 = __shfl_sync(~0u, o[8], (lane & ~3) | 1), l1 = __shfl_sync(~0u, o[10], (lane & ~3) | 1);
  const float i0 = rcp_fast(l0), i1 = rcp_fast(l1);
  uint32_t* og = (uint32_t*)(g_o + (size_t)row0 * DM + head * 18 + cq * 2);
  og[0] = pack_bf16(o[0] * i0, o[1] * i0);
  og[4] = pack_bf16(o[4] * i0, o[5] * i0);
  og[8 * DM / 2] = pack_bf16(o[2] * i1, o[3] * i1);
  og[8 * DM / 2 + 4] = pack_bf16(o[6] * i1, o[7] * i1);
  if (cq == 0) {
    og[8] = pack_bf16(o[8] * i0, o[9] * i0);
    og[8 * DM / 2 + 8] = pack_bf16(o[10] * i1, o[11] * i1);
  }
}

__global__ void __launch_bounds__(512, 1) k2_kernel() {
  extern __shared__ __align__(1024) uint8_t smem_raw[];
  const uint32_t sb = (s2u(smem_raw) + 1023) & ~1023u;
  const uint32_t KS = sb, VS = sb + 98304, BAR = sb + 2 * 98304;
  const int tid = threadIdx.x, lane = tid & 31, warp = tid >> 5, wg = tid >> 7;
  const int head = blockIdx.x >> 2, qb = blockIdx.x & 3;
  if (tid == 0) {
    TS(2, 0);
    for (int i = 0; i < 16; i++) mbar_init(BAR + i * 8, 1);
    fence_bar_init();
  }
  __syncthreads();
  const int g = lane >> 2, cq = lane & 3;
  const int row0 = qb * 512 + wg * 128 + (warp & 3) * 16 + g;
  const uint8_t* qg = g_qkv + (size_t)head * 98304 + (row0 >> 3) * 384 + (row0 & 7) * 16 + cq * 4;
  pdl_wait();
  pdl_launch();
  if (tid == 0) TS(2, 1);
  const uint8_t* kg = g_qkv + (size_t)(32 + head) * 98304;
#define KV_LOAD(c) { mbar_expect(BAR + (c) * 8, 12288); bulk_g2s(KS + (c) * 6144, kg + (c) * 6144, 6144, BAR + (c) * 8); \
                     bulk_g2s(VS + (c) * 6144, kg + 32 * 98304 + (c) * 6144, 6144, BAR + (c) * 8); }
  if (lane == 0 && warp < 5) KV_LOAD(warp);
  __syncwarp();
  uint32_t q[8], q2[6];
  float kmax2 = __ldcg(g_kmax + head * 16 + (lane & 15));
#pragma unroll
  for (int i = 0; i < 6; i++) {
    q[i] = __ldcg((const uint32_t*)(qg + (i & 1) * 384 + (i >> 1) * 128));
    q2[i] = __ldcg((const uint32_t*)(qg + 3072 + (i & 1) * 384 + (i >> 1) * 128));
  }
  q[6] = __ldcg((const uint32_t*)(qg + 256 + 12 - cq * 4)); q[7] = __ldcg((const uint32_t*)(qg + 256 + 8 - cq * 4));
  const uint64_t dk = mkdesc(KS, 128, 384, 0), dv = mkdesc(VS, 384, 128, 0);
#pragma unroll
  for (int o = 8; o; o >>= 1) kmax2 = fmaxf(kmax2, __shfl_xor_sync(~0u, kmax2, o));
  float bd[4] = {sq2(q[0]) + sq2(q[2]) + sq2(q[4]), sq2(q[1]) + sq2(q[3]) + sq2(q[5]),
                 sq2(q2[0]) + sq2(q2[2]) + sq2(q2[4]), sq2(q2[1]) + sq2(q2[3]) + sq2(q2[5])};
  int ok = 1;
  if (tid == 0 && bd[0] + bd[3] + kmax2 != 1.2345f) TS(2, 5);
#pragma unroll
  for (int i = 0; i < 4; i++) {
    bd[i] += __shfl_xor_sync(~0u, bd[i], 1); bd[i] += __shfl_xor_sync(~0u, bd[i], 2);
    bd[i] = sqrt_fast(bd[i] * kmax2) * 1.01f + 1.0f;
    ok = ok && (bd[i] <= 62.0f);
  }
  {
    uint32_t all;
    asm volatile("{.reg .pred p,q; setp.ne.b32 p,%1,0; barrier.red.and.pred q,1,512,p; selp.u32 %0,1,0,q;}"
                 : "=r"(all) : "r"(ok) : "memory");
    ok = __all_sync(~0u, all);
  }
  float o[12];
#pragma unroll
  for (int i = 0; i < 12; i++) { o[i] = 0.f; asm volatile("" : "+f"(o[i])); }
  float s[32];
  uint32_t p[16];
  if (tid == 0) TS(2, 2);
  if (ok) {
    if (cq == 1) {
      q[4] = pack_bf16(-bd[0], 1.0f); q[5] = pack_bf16(-bd[1], 1.0f);
      q2[4] = pack_bf16(-bd[2], 1.0f); q2[5] = pack_bf16(-bd[3], 1.0f);
    }
    mbar_wait(BAR, 0);
    WG_FENCE();
    QK_MMA(s, dk);
    WG_COMMIT();
#pragma unroll 1
    for (int tile = 0; tile < 2; tile++) {
#pragma unroll 1
      for (int jj = 0; jj < 8; jj++) {
        const uint64_t kd = dk + (uint32_t)(jj * 768), vd = dv + (uint32_t)(jj * 768), kn = dk + (uint32_t)(((jj + 1) & 7) * 768);
        if (tile == 0) {
          if (lane == 0 && warp < 2 && 2 * jj + 5 + warp < 16) KV_LOAD(2 * jj + 5 + warp);
          __syncwarp();
          mbar_wait(BAR + jj * 16 + 8, 0); mbar_wait(BAR + ((jj * 16 + 16) & 127), 0); if (tid == 0) TS(2, 8 + jj); }
#pragma unroll
        for (int u = 0; u < 4; u++) {
          WG_WAIT(0);
          fence_regs<32>(s);
          softmax_fast(s, p);
          if (u == 3 && jj == 7) {
#pragma unroll
            for (int i = 0; i < 6; i++) q[i] = q2[i];
          }
          WG_FENCE();
          PV_MMA(p, vd + u * 192);
          QK_MMA(s, u < 3 ? kd + u * 192 + 192 : kn);
          WG_COMMIT();
        }
      }
      WG_WAIT(0);
      fence_regs<12>(o);
      att_store(o, row0 + tile * 64, head, lane);
#pragma unroll
      for (int i = 0; i < 12; i++) o[i] = 0.f;
      fence_regs<12>(o);
      if (tid == 0 && tile == 0) TS(2, 3);
    }
  } else {
    if (lane == 0 && warp >= 5) KV_LOAD(warp);
    __syncwarp();
#pragma unroll 1
    for (int tile = 0; tile < 2; tile++) {
      float m0 = -INFINITY, m1 = -INFINITY;
#pragma unroll 1
      for (int j = 0; j < 32; j++) {
        mbar_wait(BAR + (j >> 1) * 8, 0);
        WG_FENCE();
        QK_MMA(s, dk + (uint32_t)(j * 192));
        WG_COMMIT();
        WG_WAIT(0);
        fence_regs<32>(s);
#pragma unroll
        for (int i = 0; i < 32; i++) if ((POLY_MASK >> (i >> 2)) & 1) s[i] *= 2.0f;
        float x0 = m0, x1 = m1;
#pragma unroll
        for (int i = 0; i < 8; i++) {
          x0 = fmaxf(x0, fmaxf(s[4 * i], s[4 * i + 1]));
          x1 = fmaxf(x1, fmaxf(s[4 * i + 2], s[4 * i + 3]));
        }
        x0 = fmaxf(x0, __shfl_xor_sync(~0u, x0, 1)); x0 = fmaxf(x0, __shfl_xor_sync(~0u, x0, 2));
        x1 = fmaxf(x1, __shfl_xor_sync(~0u, x1, 1)); x1 = fmaxf(x1, __shfl_xor_sync(~0u, x1, 2));
        const float c0 = ex2f(m0 - x0), c1 = ex2f(m1 - x1);
        m0 = x0; m1 = x1;
#pragma unroll
        for (int i = 0; i < 3; i++) { o[4 * i] *= c0; o[4 * i + 1] *= c0; o[4 * i + 2] *= c1; o[4 * i + 3] *= c1; }
#pragma unroll
        for (int i = 0; i < 8; i++) {
          p[2 * i] = pack_bf16(ex2f(s[4 * i] - x0), ex2f(s[4 * i + 1] - x0));
          p[2 * i + 1] = pack_bf16(ex2f(s[4 * i + 2] - x1), ex2f(s[4 * i + 3] - x1));
        }
        WG_FENCE();
        PV_MMA(p, dv + (uint32_t)(j * 192));
        WG_COMMIT();
        WG_WAIT(0);
        fence_regs<12>(o);
      }
      att_store(o, row0 + tile * 64, head, lane);
#pragma unroll
      for (int i = 0; i < 12; i++) o[i] = 0.f;
#pragma unroll
      for (int i = 0; i < 6; i++) q[i] = q2[i];
    }
  }
  if (tid == 0) TS(2, 4);
}

#define K3_NSTG 4
#define K3_SMEM (9 * 16384 + K3_NSTG * 16384 + 1024 + 256)
__global__ void __launch_bounds__(288, 1) k3_kernel(const __grid_constant__ CUtensorMap mo, const __grid_constant__ CUtensorMap mw,
                                                    const __nv_bfloat16* __restrict__ x) {
  extern __shared__ __align__(1024) uint8_t smem_raw[];
  const uint32_t sb = (s2u(smem_raw) + 1023) & ~1023u;
  const uint32_t A = sb, RING = sb + 9 * 16384, BAR = RING + K3_NSTG * 16384;
  const uint32_t full = BAR, empty = BAR + 64, afull = BAR + 128;
  const int tid = threadIdx.x, lane = tid & 31, warp = tid >> 5;
  const int mb = blockIdx.x >> 3, nb = blockIdx.x & 7;
  if (tid == 0) {
    TS(3, 0);
    for (int i = 0; i < K3_NSTG; i++) { mbar_init(full + i * 8, 1); mbar_init(empty + i * 8, 8); }
    for (int i = 0; i < 9; i++) mbar_init(afull + i * 8, 1);
    fence_bar_init();
  }
  __syncthreads();
  pdl_launch();
  if (warp == 8) {
    if (lane == 0) {
      for (int s = 0; s < K3_NSTG; s++) {
        mbar_expect(full + s * 8, 16384);
        tma2d(RING + s * 16384, &mw, nb * 72, s * 64, full + s * 8);
        tma2d(RING + s * 16384 + 8192, &mw, nb * 72 + 64, s * 64, full + s * 8);
      }
      pdl_wait();
      for (int c = 0; c < 9; c++) { mbar_expect(afull + c * 8, 16384); tma2d(A + c * 16384, &mo, c * 64, mb * 128, afull + c * 8); }
      for (int s = K3_NSTG; s < 9; s++) {
        const int st = s % K3_NSTG;
        mbar_wait(empty + st * 8, ((s / K3_NSTG) & 1) ^ 1);
        mbar_expect(full + st * 8, 16384);
        tma2d(RING + st * 16384, &mw, nb * 72, s * 64, full + st * 8);
        tma2d(RING + st * 16384 + 8192, &mw, nb * 72 + 64, s * 64, full + st * 8);
      }
    }
  } else {
    const int g = lane >> 2, cq = lane & 3;
    const int row = mb * 128 + warp * 16 + g, col = nb * 72 + cq * 2;
    uint32_t xv[18];
#pragma unroll
    for (int i = 0; i < 9; i++) {
      xv[2 * i] = __ldg((const uint32_t*)(x + (size_t)row * DM + col + 8 * i));
      xv[2 * i + 1] = __ldg((const uint32_t*)(x + (size_t)(row + 8) * DM + col + 8 * i));
    }
    pdl_wait();
    if (tid == 0) TS(3, 1);
    float2 ga[9];
#pragma unroll
    for (int i = 0; i < 9; i++) ga[i] = *(const float2*)(g_ga + col + 8 * i);
    float acc[36];
    const uint32_t abase = A + (warp >> 2) * 8192;
#pragma unroll
    for (int s = 0; s < 9; s++) {
      const int st = s % K3_NSTG;
      mbar_wait(afull + s * 8, 0);
      mbar_wait(full + st * 8, (s / K3_NSTG) & 1);
      WG_FENCE();
#pragma unroll
      for (int k = 0; k < 4; k++)
        wg_ss_n72_t1(acc, mkdesc(abase + s * 16384 + k * 32, 16, 1024, 1), mkdesc(RING + st * 16384 + k * 2048, 8192, 1024, 1), (s | k) != 0);
      WG_COMMIT();
      if (s > 0) { WG_WAIT(1); if (lane == 0) mbar_arrive(empty + ((s - 1) % K3_NSTG) * 8); }
    }
    WG_WAIT(0);
    if (tid == 0) TS(3, 2);
    float s0 = 0, s1 = 0;
#pragma unroll
    for (int i = 0; i < 9; i++) {
      acc[4 * i] = rbf(bf_lo(xv[2 * i]) + rbf(ga[i].x * rbf(acc[4 * i])));
      acc[4 * i + 1] = rbf(bf_hi(xv[2 * i]) + rbf(ga[i].y * rbf(acc[4 * i + 1])));
      acc[4 * i + 2] = rbf(bf_lo(xv[2 * i + 1]) + rbf(ga[i].x * rbf(acc[4 * i + 2])));
      acc[4 * i + 3] = rbf(bf_hi(xv[2 * i + 1]) + rbf(ga[i].y * rbf(acc[4 * i + 3])));
      *(uint32_t*)(g_x1 + (size_t)row * DM + col + 8 * i) = pack_bf16(acc[4 * i], acc[4 * i + 1]);
      *(uint32_t*)(g_x1 + (size_t)(row + 8) * DM + col + 8 * i) = pack_bf16(acc[4 * i + 2], acc[4 * i + 3]);
      s0 += acc[4 * i] + acc[4 * i + 1];
      s1 += acc[4 * i + 2] + acc[4 * i + 3];
    }
    s0 += __shfl_xor_sync(~0u, s0, 1); s0 += __shfl_xor_sync(~0u, s0, 2);
    s1 += __shfl_xor_sync(~0u, s1, 1); s1 += __shfl_xor_sync(~0u, s1, 2);
    const float m0 = s0 * (1.0f / 72), m1 = s1 * (1.0f / 72);
    float q0 = 0, q1 = 0;
#pragma unroll
    for (int i = 0; i < 9; i++) {
      q0 += (acc[4 * i] - m0) * (acc[4 * i] - m0) + (acc[4 * i + 1] - m0) * (acc[4 * i + 1] - m0);
      q1 += (acc[4 * i + 2] - m1) * (acc[4 * i + 2] - m1) + (acc[4 * i + 3] - m1) * (acc[4 * i + 3] - m1);
    }
    q0 += __shfl_xor_sync(~0u, q0, 1); q0 += __shfl_xor_sync(~0u, q0, 2);
    q1 += __shfl_xor_sync(~0u, q1, 1); q1 += __shfl_xor_sync(~0u, q1, 2);
    if (cq == 0) {
      g_stat2[row * 8 + nb] = make_float2(m0, q0);
      g_stat2[(row + 8) * 8 + nb] = make_float2(m1, q1);
    }
    if (tid == 0) TS(3, 3);
  }
}

__device__ __forceinline__ uint4 ln2_consts(int row, int cq) {
  const float4 p = *(const float4*)(g_stat2 + row * 8 + cq * 2);
  float s = p.x + p.z;
  s += __shfl_xor_sync(~0u, s, 1); s += __shfl_xor_sync(~0u, s, 2);
  const float mean = s * 0.125f;
  float q = p.y + p.w + 72.0f * ((p.x - mean) * (p.x - mean) + (p.z - mean) * (p.z - mean));
  q += __shfl_xor_sync(~0u, q, 1); q += __shfl_xor_sync(~0u, q, 2);
  return ln_consts(mean, q * (1.0f / DM));
}
__device__ __forceinline__ uint32_t glu_pair(float g0, float g1, float u0, float u1) {
  const float s0 = fmaf(tanhf_fast(0.5f * g0), 0.5f, 0.5f), s1 = fmaf(tanhf_fast(0.5f * g1), 0.5f, 0.5f);
  return pack_bf16(s0 * u0, s1 * u1);
}
template <int NG>
__device__ __forceinline__ void stage_part(const float* acc, uint32_t stg, int lane) {
  const int r = (lane & 7) + ((lane >> 3) & 1) * 8;
#pragma unroll
  for (int i = 0; i < NG; i += 2) {
    const int ch = i + (lane >> 4);
    stsm4(stg + r * (NG * 16) + ((ch ^ (r & 7)) << 4), pack_bf16(acc[4 * i], acc[4 * i + 1]), pack_bf16(acc[4 * i + 2], acc[4 * i + 3]),
          pack_bf16(acc[4 * i + 4], acc[4 * i + 5]), pack_bf16(acc[4 * i + 6], acc[4 * i + 7]));
  }
}
__device__ __forceinline__ uint4 lds128(uint32_t a) {
  uint4 v;
  asm volatile("ld.shared.v4.b32 {%0,%1,%2,%3},[%4];" : "=r"(v.x), "=r"(v.y), "=r"(v.z), "=r"(v.w) : "r"(a) : "memory");
  return v;
}
__device__ __forceinline__ void sts128(uint32_t a, const uint4& v) {
  asm volatile("st.shared.v4.b32 [%0],{%1,%2,%3,%4};" ::"r"(a), "r"(v.x), "r"(v.y), "r"(v.z), "r"(v.w) : "memory");
}
__device__ __forceinline__ uint32_t res_pair(uint32_t x, uint32_t g, float s0, float s1) { return hadd2(x, hmul2(g, pack_bf16(s0, s1))); }

__global__ void __launch_bounds__(384, 1) k4_kernel(const __grid_constant__ CUtensorMap mx, const __grid_constant__ CUtensorMap mg,
                                                    const __grid_constant__ CUtensorMap mu, const __grid_constant__ CUtensorMap md,
                                                    __nv_bfloat16* __restrict__ out) {
  extern __shared__ __align__(1024) uint8_t smem_raw[];
  const uint32_t sb = s2u(smem_raw);
  const uint32_t R = sb, RING = sb + R_BYTES, BAR = RING + NSTG * STG_BYTES, TAB = BAR + 512;
  const uint32_t full = BAR, empty = BAR + 64, xfull = BAR + 128, gfull = BAR + 272, sfull = BAR + 320;
  const int tid = threadIdx.x, lane = tid & 31, warp = tid >> 5;
  const int mb = blockIdx.x >> 3, fb = blockIdx.x & 7;
  if (tid == 0) {
    TS(4, 0);
    if (sb & 1023) __trap();
    for (int i = 0; i < 10; i++) mbar_init(sfull + i * 8, 4);
    for (int i = 0; i < NSTG; i++) { mbar_init(full + i * 8, 1); mbar_init(empty + i * 8, 8); }
    for (int i = 0; i < 18; i++) mbar_init(xfull + i * 8, 1);
    for (int i = 0; i < 5; i++) mbar_init(gfull + i * 8, 1);
    mbar_arrive(full);
    fence_bar_init();
  }
  __syncthreads();
  if (warp >= 8) {
    REG_DEC(24);
    if (lane == 0) {
      if (warp == 8) {
        int st = 1; uint32_t ph = 0;
        for (int it = 0; it < 126; it++) {
          if (it == NSTG - 1) {
            pdl_wait();
            for (int c = 0; c < 18; c++) {
              const int w = c >= 9, k = c - w * 9;
              mbar_expect(xfull + c * 8, 8192);
              tma2d(R + k * 16384 + w * 8192, &mx, k * 64, mb * 128 + w * 64, xfull + c * 8);
            }
          }
          const int t = it / 9, s = it - t * 9;
          const uint32_t dst = RING + st * STG_BYTES, fb_ = full + st * 8;
          mbar_wait(empty + st * 8, ph ^ 1);
          if (t < 9) {
            mbar_expect(fb_, 16384);
            tma2d(dst, &mg, fb * 576 + t * 64, s * 64, fb_);
            tma2d(dst + 8192, &mu, fb * 576 + t * 64, s * 64, fb_);
          } else {
            mbar_expect(fb_, t < 13 ? 16384 : 8192);
            tma2d(dst, &md, (t - 9) * 128, fb * 576 + s * 64, fb_);
            if (t < 13) tma2d(dst + 8192, &md, (t - 9) * 128 + 64, fb * 576 + s * 64, fb_);
          }
          if (++st == NSTG) { st = 0; ph ^= 1; }
        }
      } else if (warp < 11) {
        const int wg = warp - 9;
#pragma unroll 1
        for (int p = 0; p < 5; p++) {
          uint8_t* dst = g_part + (size_t)((fb * 16 + mb) * 5 + p) * 32768;
          mbar_wait(sfull + (p * 2 + wg) * 8, 0);
          if (p < 4) {
            bulk_s2g(dst + wg * 16384, R + p * 32768 + wg * 8192, 8192);
            bulk_s2g(dst + wg * 16384 + 8192, R + p * 32768 + 16384 + wg * 8192, 8192);
          } else {
            bulk_s2g(dst + wg * 8192, RING + wg * STG_BYTES + 8192, 8192);
          }
          bulk_commit();
          bulk_wait0();
          asm volatile("fence.proxy.async;" ::: "memory");
          asm volatile("red.release.gpu.global.add.u32 [%0],1;" ::"l"(g_cnt + mb * 5 + p) : "memory");
        }
      } else {
        mbar_wait(sfull, 0);
#pragma unroll 1
        for (int p = 0; p < 5; p++) {
          unsigned int v; int n = 0;
          do {
            asm volatile("ld.acquire.gpu.global.u32 %0,[%1];" : "=r"(v) : "l"(g_cnt + mb * 5 + p) : "memory");
          } while (v < 16 && ++n < 20000000);
          if (v < 16) __trap();
          asm volatile("fence.proxy.async;" ::: "memory");
          const uint32_t sz = p < 4 ? 4096 : 2048;
          mbar_expect(gfull + p * 8, sz * 8);
#pragma unroll 1
          for (int f = 0; f < 8; f++)
            bulk_g2s(p < 4 ? R + p * 32768 + f * 4096 : RING + (2 + (f >> 2)) * STG_BYTES + 8192 + (f & 3) * 2048,
                     g_part + (size_t)((f * 16 + mb) * 5 + p) * 32768 + fb * sz, sz, gfull + p * 8);
        }
      }
    }
  } else {
    REG_INC(240);
    uint32_t a[36][4];
    const int wg = warp >> 2, wl = warp & 3;
    if (tid < 144) sts128(TAB + tid * 16, g_tab2[tid]);
    bar_sync(1, 256);
    pdl_wait();
    if (tid == 0) TS(4, 1);
    {
      const int g = lane >> 2, cq = lane & 3;
      const uint4 s0 = ln2_consts(mb * 128 + warp * 16 + g, cq), s1 = ln2_consts(mb * 128 + warp * 16 + g + 8, cq);
#pragma unroll
      for (int c = 0; c < 9; c++) {
        mbar_wait(xfull + (wg * 9 + c) * 8, 0);
        load_a_chunk(&a[c * 4], R + c * 16384, warp * 16, lane);
        if (c == 8) { __syncwarp(); if (lane == 0) mbar_arrive(empty); }
#pragma unroll
        for (int k = c * 4; k < c * 4 + 4; k++) {
          const uint4 t = lds128(TAB + (k * 4 + cq) * 16);
          a[k][0] = ln_apply(a[k][0], s0, t.x, t.y);
          a[k][1] = ln_apply(a[k][1], s1, t.x, t.y);
          a[k][2] = ln_apply(a[k][2], s0, t.z, t.w);
          a[k][3] = ln_apply(a[k][3], s1, t.z, t.w);
        }
      }
    }
    if (tid == 0) TS(4, 2);
    if (tid == 128) TS(4, 8);
    Ring ring{RING, full, empty, 1, 0};
    float acc[64];
    const uint32_t hsp = R + warp * 2048 + lane * 16;
#pragma unroll 1
    for (int t = 0; t < 8; t++) {
      MMA_TILE(wg_rs_n128_t1, acc, a, ring, lane);
#pragma unroll
      for (int j = 0; j < 4; j++) {
        uint32_t h[4];
#pragma unroll
        for (int e = 0; e < 4; e++) h[e] = glu_pair(acc[8 * j + 2 * e], acc[8 * j + 2 * e + 1], acc[32 + 8 * j + 2 * e], acc[32 + 8 * j + 2 * e + 1]);
        asm volatile("st.shared.v4.b32 [%0],{%1,%2,%3,%4};" ::"r"(hsp + t * 16384 + j * 512), "r"(h[0]), "r"(h[1]), "r"(h[2]), "r"(h[3]) : "memory");
      }
    }
    MMA_TILE(wg_rs_n128_t1, acc, a, ring, lane);
#pragma unroll
    for (int j = 0; j < 4; j++)
#pragma unroll
      for (int e = 0; e < 4; e++)
        a[32 + j][e] = glu_pair(acc[8 * j + 2 * e], acc[8 * j + 2 * e + 1], acc[32 + 8 * j + 2 * e], acc[32 + 8 * j + 2 * e + 1]);
#pragma unroll
    for (int k = 0; k < 32; k++)
      asm volatile("ld.shared.v4.b32 {%0,%1,%2,%3},[%4];" : "=r"(a[k][0]), "=r"(a[k][1]), "=r"(a[k][2]), "=r"(a[k][3]) : "r"(hsp + (k >> 2) * 16384 + (k & 3) * 512) : "memory");
    if (tid == 0) TS(4, 3);
    if (tid == 128) TS(4, 9);
    const uint32_t stg = R + (wl >> 1) * 16384 + wg * 8192 + (wl & 1) * 4096;
#pragma unroll 1
    for (int p = 0; p < 4; p++) {
      MMA_TILE(wg_rs_n128_t1, acc, a, ring, lane);
      if (p == 0) bar_sync(2 + wg, 128);
      stage_part<16>(acc, stg + p * 32768, lane);
      fence_async_smem();
      __syncwarp();
      if (lane == 0) mbar_arrive(sfull + (p * 2 + wg) * 8);
    }
    MMA_TILE(wg_rs_n64_t1, acc, a, ring, lane);
    stage_part<8>(acc, RING + wg * STG_BYTES + 8192 + wl * 2048, lane);
    fence_async_smem();
    __syncwarp();
    if (lane == 0) mbar_arrive(sfull + (8 + wg) * 8);
    if (tid == 0) TS(4, 5);
    if (tid == 128) TS(4, 10);
    const int rl = tid >> 4, ch = tid & 15;
    const size_t off = (size_t)(mb * 128 + fb * 16 + rl) * DM + ch * 8;
    uint4 xv[5], gv[5];
#pragma unroll
    for (int p = 0; p < 5; p++)
      if (p < 4 || ch < 8) { xv[p] = __ldcg((const uint4*)(g_x1 + off + p * 128)); gv[p] = __ldcg((const uint4*)(g_gb + p * 128 + ch * 8)); }
#pragma unroll
    for (int p = 0; p < 5; p++) {
      if (p == 4 && ch >= 8) break;
      mbar_wait(gfull + p * 8, 0);
      float r8[8] = {0, 0, 0, 0, 0, 0, 0, 0};
#pragma unroll
      for (int f = 0; f < 8; f++) {
        const uint4 v = lds128((p < 4 ? R + p * 32768 + f * 4096 + rl * 256 : RING + (2 + (f >> 2)) * STG_BYTES + 8192 + (f & 3) * 2048 + rl * 128) +
                               ((ch ^ (rl & 7)) << 4));
        r8[0] += bf_lo(v.x); r8[1] += bf_hi(v.x); r8[2] += bf_lo(v.y); r8[3] += bf_hi(v.y);
        r8[4] += bf_lo(v.z); r8[5] += bf_hi(v.z); r8[6] += bf_lo(v.w); r8[7] += bf_hi(v.w);
      }
      uint4 r;
      r.x = res_pair(xv[p].x, gv[p].x, r8[0], r8[1]);
      r.y = res_pair(xv[p].y, gv[p].y, r8[2], r8[3]);
      r.z = res_pair(xv[p].z, gv[p].z, r8[4], r8[5]);
      r.w = res_pair(xv[p].w, gv[p].w, r8[6], r8[7]);
      *(uint4*)(out + off + p * 128) = r;
      if (tid == 0 && p >= 3) TS(4, 3 + p);
    }
  }
}

typedef CUresult (*EncodeFn)(CUtensorMap*, CUtensorMapDataType, cuuint32_t, void*, const cuuint64_t*, const cuuint64_t*,
                             const cuuint32_t*, const cuuint32_t*, CUtensorMapInterleave, CUtensorMapSwizzle,
                             CUtensorMapL2promotion, CUtensorMapFloatOOBfill);
static void make_map(EncodeFn fn, CUtensorMap* m, const void* p, int rows, int cols, int box_rows) {
  cuuint64_t dims[2] = {(cuuint64_t)cols, (cuuint64_t)rows};
  cuuint64_t strides[1] = {(cuuint64_t)cols * 2};
  cuuint32_t box[2] = {64, (cuuint32_t)box_rows};
  cuuint32_t es[2] = {1, 1};
  fn(m, CU_TENSOR_MAP_DATA_TYPE_BFLOAT16, 2, (void*)p, dims, strides, box, es, CU_TENSOR_MAP_INTERLEAVE_NONE,
     CU_TENSOR_MAP_SWIZZLE_128B, CU_TENSOR_MAP_L2_PROMOTION_L2_256B, CU_TENSOR_MAP_FLOAT_OOB_FILL_NONE);
}
template <typename... KA, typename... A>
static void launch(void (*k)(KA...), int grid, int block, int smem, bool pdl, A... args) {
  cudaLaunchConfig_t cfg = {};
  cfg.gridDim = dim3(grid); cfg.blockDim = dim3(block); cfg.dynamicSmemBytes = smem; cfg.stream = cudaStreamPerThread;
  cudaLaunchAttribute at;
  at.id = cudaLaunchAttributeProgrammaticStreamSerialization;
  at.val.programmaticStreamSerializationAllowed = 1;
  cfg.attrs = &at; cfg.numAttrs = pdl ? 1 : 0;
  cudaLaunchKernelEx(&cfg, k, KA(args)...);
}

extern "C" void kernel_launch(void* const* d_in, const int* in_sizes, int n_in, void* d_out, int out_size) {
  const __nv_bfloat16* x = (const __nv_bfloat16*)d_in[0];
  void* fnp = nullptr;
  cudaDriverEntryPointQueryResult qr;
  cudaGetDriverEntryPoint("cuTensorMapEncodeTiled", &fnp, cudaEnableDefault, &qr);
  EncodeFn fn = (EncodeFn)fnp;
  void *po, *px1;
  cudaGetSymbolAddress(&po, g_o);
  cudaGetSymbolAddress(&px1, g_x1);
  CUtensorMap mx, mqkv, mo, mwo, mx1, mg, mu, md;
  make_map(fn, &mx, x, SEQ, DM, 128);
  make_map(fn, &mqkv, d_in[1], DM, 3 * DM, 64);
  make_map(fn, &mo, po, SEQ, DM, 128);
  make_map(fn, &mwo, d_in[2], DM, DM, 64);
  make_map(fn, &mx1, px1, SEQ, DM, 64);
  make_map(fn, &mg, d_in[4], DM, FF, 64);
  make_map(fn, &mu, d_in[5], DM, FF, 64);
  make_map(fn, &md, d_in[6], FF, DM, 64);
  cudaFuncSetAttribute(k1_kernel, cudaFuncAttributeMaxDynamicSharedMemorySize, GEMM_SMEM);
  cudaFuncSetAttribute(k2_kernel, cudaFuncAttributeMaxDynamicSharedMemorySize, ATT_SMEM);
  cudaFuncSetAttribute(k3_kernel, cudaFuncAttributeMaxDynamicSharedMemorySize, K3_SMEM);
  cudaFuncSetAttribute(k4_kernel, cudaFuncAttributeMaxDynamicSharedMemorySize, GEMM_SMEM);
  launch(k0_kernel, 108 + 128, 256, 0, false, x, (const __nv_bfloat16*)d_in[7], (const __nv_bfloat16*)d_in[8]);
  launch(k1_kernel, 128, 384, GEMM_SMEM, true, mx, mqkv);
  launch(k2_kernel, 128, 512, ATT_SMEM, true);
  launch(k3_kernel, 128, 288, K3_SMEM, true, mo, mwo, x);
  launch(k4_kernel, 128, 384, GEMM_SMEM, true, mx1, mg, mu, md, (__nv_bfloat16*)d_out);
}
```

```cpp
#include <cuda_runtime.h>
#include <cuda_bf16.h>
#include <cuda.h>
#include <stdint.h>

#define SEQ 2048
#define DM 576
#define NH 32
#define FF 4608

__device__ uint4 g_tab1[36 * 4];
__device__ uint4 g_tab2[36 * 4];
__device__ float g_ga[DM];
__device__ __align__(16) __nv_bfloat16 g_gb[DM];
__device__ uint4 g_stat1[SEQ];
__device__ float2 g_stat2[SEQ * 8];
__device__ __align__(1024) uint8_t g_qkv[96 * 98304];
__device__ float g_kmax[NH * 16];
__device__ __align__(1024) __nv_bfloat16 g_o[SEQ * DM];
__device__ __align__(1024) __nv_bfloat16 g_x1[SEQ * DM];
__device__ __align__(1024) uint8_t g_part[8 * 16 * 5 * 2 * 16384];
__device__ unsigned int g_cnt[16 * 5];

#define TS(k, i)
#define TSS(i)
#define TSDUMP(k)
__device__ __forceinline__ uint32_t s2u(const void* p) { return (uint32_t)__cvta_generic_to_shared(p); }
__device__ __forceinline__ void mbar_init(uint32_t b, int c) { asm volatile("mbarrier.init.shared::cta.b64 [%0],%1;" ::"r"(b), "r"(c)); }
__device__ __forceinline__ void mbar_expect(uint32_t b, uint32_t n) { asm volatile("mbarrier.arrive.expect_tx.shared::cta.b64 _,[%0],%1;" ::"r"(b), "r"(n) : "memory"); }
__device__ __forceinline__ void mbar_arrive(uint32_t b) { asm volatile("mbarrier.arrive.shared::cta.b64 _,[%0];" ::"r"(b) : "memory"); }
__device__ __forceinline__ void mbar_wait(uint32_t b, uint32_t ph) {
  asm volatile(
      "{.reg .pred p; .reg .u32 n; mov.u32 n,0;\n"
      "W: mbarrier.try_wait.parity.shared::cta.b64 p,[%0],%1;\n"
      "@p bra D;\n"
      "add.u32 n,n,1; setp.lt.u32 p,n,4000000; @p bra W;\n"
      "trap;\n"
      "D: }" ::"r"(b), "r"(ph) : "memory");
}
__device__ __forceinline__ void tma2d(uint32_t dst, const CUtensorMap* m, int c0, int c1, uint32_t bar) {
  asm volatile("cp.async.bulk.tensor.2d.shared::cluster.global.mbarrier::complete_tx::bytes [%0],[%1,{%3,%4}],[%2];"
               ::"r"(dst), "l"(m), "r"(bar), "r"(c0), "r"(c1) : "memory");
}
__device__ __forceinline__ void bulk_g2s(uint32_t dst, const void* src, uint32_t bytes, uint32_t bar) {
  asm volatile("cp.async.bulk.shared::cluster.global.mbarrier::complete_tx::bytes [%0],[%1],%2,[%3];"
               ::"r"(dst), "l"(src), "r"(bytes), "r"(bar) : "memory");
}
__device__ __forceinline__ void bulk_s2g(void* dst, uint32_t src, uint32_t bytes) {
  asm volatile("cp.async.bulk.global.shared::cta.bulk_group [%0],[%1],%2;" ::"l"(dst), "r"(src), "r"(bytes) : "memory");
}
__device__ __forceinline__ void bulk_commit() { asm volatile("cp.async.bulk.commit_group;" ::: "memory"); }
__device__ __forceinline__ void bulk_wait0() { asm volatile("cp.async.bulk.wait_group 0;" ::: "memory"); }
__device__ __forceinline__ void prefetch_map(const CUtensorMap* m) { asm volatile("prefetch.tensormap [%0];" ::"l"(m) : "memory"); }
__device__ __forceinline__ void fence_async_smem() { asm volatile("fence.proxy.async.shared::cta;" ::: "memory"); }
__device__ __forceinline__ void fence_bar_init() { asm volatile("fence.mbarrier_init.release.cluster;" ::: "memory"); }
__device__ __forceinline__ void pdl_wait() { asm volatile("griddepcontrol.wait;" ::: "memory"); }
__device__ __forceinline__ void pdl_launch() { asm volatile("griddepcontrol.launch_dependents;" ::: "memory"); }
__device__ __forceinline__ void bar_sync(int id, int n) { asm volatile("bar.sync %0,%1;" ::"r"(id), "r"(n) : "memory"); }
__device__ __forceinline__ void bar_arrive(int id, int n) { asm volatile("bar.arrive %0,%1;" ::"r"(id), "r"(n) : "memory"); }
#define WG_FENCE() asm volatile("wgmma.fence.sync.aligned;" ::: "memory")
#define WG_COMMIT() asm volatile("wgmma.commit_group.sync.aligned;" ::: "memory")
#define WG_WAIT(n) asm volatile("wgmma.wait_group.sync.aligned " #n ";" ::: "memory")
template <int N> __device__ __forceinline__ void fence_regs(float* r) {
#pragma unroll
  for (int i = 0; i < N; i++) asm volatile("" : "+f"(r[i])::"memory");
}
#define REG_INC(n) asm volatile("setmaxnreg.inc.sync.aligned.u32 " #n ";")
#define REG_DEC(n) asm volatile("setmaxnreg.dec.sync.aligned.u32 " #n ";")
__device__ __forceinline__ uint64_t mkdesc(uint32_t addr, uint32_t lbo, uint32_t sbo, int sw) {
  return (uint64_t)((addr & 0x3FFFF) >> 4) | ((uint64_t)(lbo >> 4) << 16) | ((uint64_t)(sbo >> 4) << 32) | ((uint64_t)sw << 62);
}
__device__ __forceinline__ void ldsm4(uint32_t* r, uint32_t addr) {
  asm volatile("ldmatrix.sync.aligned.m8n8.x4.shared.b16 {%0,%1,%2,%3},[%4];" : "=r"(r[0]), "=r"(r[1]), "=r"(r[2]), "=r"(r[3]) : "r"(addr) : "memory");
}
__device__ __forceinline__ void stsm4(uint32_t addr, uint32_t r0, uint32_t r1, uint32_t r2, uint32_t r3) {
  asm volatile("stmatrix.sync.aligned.m8n8.x4.shared.b16 [%0],{%1,%2,%3,%4};" ::"r"(addr), "r"(r0), "r"(r1), "r"(r2), "r"(r3) : "memory");
}
__device__ __forceinline__ uint32_t pack_bf16(float lo, float hi) {
  uint32_t r;
  asm("cvt.rn.bf16x2.f32 %0,%1,%2;" : "=r"(r) : "f"(hi), "f"(lo));
  return r;
}
__device__ __forceinline__ float bf_lo(uint32_t v) { return __uint_as_float(v << 16); }
__device__ __forceinline__ float bf_hi(uint32_t v) { return __uint_as_float(v & 0xFFFF0000u); }
__device__ __forceinline__ float rbf(float x) { return __bfloat162float(__float2bfloat16_rn(x)); }
__device__ __forceinline__ uint32_t hfma2(uint32_t a, uint32_t b, uint32_t c) {
  uint32_t r;
  asm("fma.rn.bf16x2 %0,%1,%2,%3;" : "=r"(r) : "r"(a), "r"(b), "r"(c));
  return r;
}
__device__ __forceinline__ uint32_t hadd2(uint32_t a, uint32_t b) {
  uint32_t r;
  asm("add.rn.bf16x2 %0,%1,%2;" : "=r"(r) : "r"(a), "r"(b));
  return r;
}
__device__ __forceinline__ uint32_t hmul2(uint32_t a, uint32_t b) {
  uint32_t r;
  asm("mul.rn.bf16x2 %0,%1,%2;" : "=r"(r) : "r"(a), "r"(b));
  return r;
}
__device__ __forceinline__ uint32_t hneg2(uint32_t a) {
  uint32_t r;
  asm("neg.bf16x2 %0,%1;" : "=r"(r) : "r"(a));
  return r;
}
__device__ __forceinline__ float ex2f(float x) {
  float r;
  asm("ex2.approx.ftz.f32 %0,%1;" : "=f"(r) : "f"(x));
  return r;
}
__device__ __forceinline__ float sqrt_fast(float x) {
  float r;
  asm("sqrt.approx.f32 %0,%1;" : "=f"(r) : "f"(x));
  return r;
}
__device__ __forceinline__ float rcp_fast(float x) {
  float r;
  asm("rcp.approx.f32 %0,%1;" : "=f"(r) : "f"(x));
  return r;
}
__device__ __forceinline__ float tanhf_fast(float x) {
  float r;
  asm("tanh.approx.f32 %0,%1;" : "=f"(r) : "f"(x));
  return r;
}
__device__ __forceinline__ uint4 ln_consts(float mean, float var) {
  float m = rbf(mean), v = rbf(var);
  float s = rbf(sqrtf(rbf(v + 1e-5f)));
  float r = 1.0f / s;
  float rh = rbf(r), rl = r - rh;
  return make_uint4(pack_bf16(-m, -m), pack_bf16(rh, rh), pack_bf16(rl, rl), 0u);
}
__device__ __forceinline__ uint32_t ln_apply(uint32_t x, const uint4& st, uint32_t a, uint32_t s) {
  uint32_t d = hadd2(x, st.x);
  uint32_t n = hfma2(d, st.y, hmul2(d, st.z));
  return hfma2(n, a, s);
}

__device__ __forceinline__ void wg_rs_n128_t1(float* d, uint32_t a0, uint32_t a1, uint32_t a2, uint32_t a3, uint64_t db, int sc) {
  asm volatile("{.reg .pred p; setp.ne.b32 p,%69,0; wgmma.mma_async.sync.aligned.m64n128k16.f32.bf16.bf16 {%0,%1,%2,%3,%4,%5,%6,%7,%8,%9,%10,%11,%12,%13,%14,%15,%16,%17,%18,%19,%20,%21,%22,%23,%24,%25,%26,%27,%28,%29,%30,%31,%32,%33,%34,%35,%36,%37,%38,%39,%40,%41,%42,%43,%44,%45,%46,%47,%48,%49,%50,%51,%52,%53,%54,%55,%56,%57,%58,%59,%60,%61,%62,%63}, {%64,%65,%66,%67}, %68, p,1,1,1;}"
  : "+f"(d[0]),"+f"(d[1]),"+f"(d[2]),"+f"(d[3]),"+f"(d[4]),"+f"(d[5]),"+f"(d[6]),"+f"(d[7]),"+f"(d[8]),"+f"(d[9]),"+f"(d[10]),"+f"(d[11]),"+f"(d[12]),"+f"(d[13]),"+f"(d[14]),"+f"(d[15]),"+f"(d[16]),"+f"(d[17]),"+f"(d[18]),"+f"(d[19]),"+f"(d[20]),"+f"(d[21]),"+f"(d[22]),"+f"(d[23]),"+f"(d[24]),"+f"(d[25]),"+f"(d[26]),"+f"(d[27]),"+f"(d[28]),"+f"(d[29]),"+f"(d[30]),"+f"(d[31]),"+f"(d[32]),"+f"(d[33]),"+f"(d[34]),"+f"(d[35]),"+f"(d[36]),"+f"(d[37]),"+f"(d[38]),"+f"(d[39]),"+f"(d[40]),"+f"(d[41]),"+f"(d[42]),"+f"(d[43]),"+f"(d[44]),"+f"(d[45]),"+f"(d[46]),"+f"(d[47]),"+f"(d[48]),"+f"(d[49]),"+f"(d[50]),"+f"(d[51]),"+f"(d[52]),"+f"(d[53]),"+f"(d[54]),"+f"(d[55]),"+f"(d[56]),"+f"(d[57]),"+f"(d[58]),"+f"(d[59]),"+f"(d[60]),"+f"(d[61]),"+f"(d[62]),"+f"(d[63]) : "r"(a0),"r"(a1),"r"(a2),"r"(a3),"l"(db),"r"(sc));
}
__device__ __forceinline__ void wg_rs_n64_t1(float* d, uint32_t a0, uint32_t a1, uint32_t a2, uint32_t a3, uint64_t db, int sc) {
  asm volatile("{.reg .pred p; setp.ne.b32 p,%37,0; wgmma.mma_async.sync.aligned.m64n64k16.f32.bf16.bf16 {%0,%1,%2,%3,%4,%5,%6,%7,%8,%9,%10,%11,%12,%13,%14,%15,%16,%17,%18,%19,%20,%21,%22,%23,%24,%25,%26,%27,%28,%29,%30,%31}, {%32,%33,%34,%35}, %36, p,1,1,1;}"
  : "+f"(d[0]),"+f"(d[1]),"+f"(d[2]),"+f"(d[3]),"+f"(d[4]),"+f"(d[5]),"+f"(d[6]),"+f"(d[7]),"+f"(d[8]),"+f"(d[9]),"+f"(d[10]),"+f"(d[11]),"+f"(d[12]),"+f"(d[13]),"+f"(d[14]),"+f"(d[15]),"+f"(d[16]),"+f"(d[17]),"+f"(d[18]),"+f"(d[19]),"+f"(d[20]),"+f"(d[21]),"+f"(d[22]),"+f"(d[23]),"+f"(d[24]),"+f"(d[25]),"+f"(d[26]),"+f"(d[27]),"+f"(d[28]),"+f"(d[29]),"+f"(d[30]),"+f"(d[31]) : "r"(a0),"r"(a1),"r"(a2),"r"(a3),"l"(db),"r"(sc));
}
__device__ __forceinline__ void wg_rs_n88_t1(float* d, uint32_t a0, uint32_t a1, uint32_t a2, uint32_t a3, uint64_t db, int sc) {
  asm volatile("{.reg .pred p; setp.ne.b32 p,%49,0; wgmma.mma_async.sync.aligned.m64n88k16.f32.bf16.bf16 {%0,%1,%2,%3,%4,%5,%6,%7,%8,%9,%10,%11,%12,%13,%14,%15,%16,%17,%18,%19,%20,%21,%22,%23,%24,%25,%26,%27,%28,%29,%30,%31,%32,%33,%34,%35,%36,%37,%38,%39,%40,%41,%42,%43}, {%44,%45,%46,%47}, %48, p,1,1,1;}"
  : "+f"(d[0]),"+f"(d[1]),"+f"(d[2]),"+f"(d[3]),"+f"(d[4]),"+f"(d[5]),"+f"(d[6]),"+f"(d[7]),"+f"(d[8]),"+f"(d[9]),"+f"(d[10]),"+f"(d[11]),"+f"(d[12]),"+f"(d[13]),"+f"(d[14]),"+f"(d[15]),"+f"(d[16]),"+f"(d[17]),"+f"(d[18]),"+f"(d[19]),"+f"(d[20]),"+f"(d[21]),"+f"(d[22]),"+f"(d[23]),"+f"(d[24]),"+f"(d[25]),"+f"(d[26]),"+f"(d[27]),"+f"(d[28]),"+f"(d[29]),"+f"(d[30]),"+f"(d[31]),"+f"(d[32]),"+f"(d[33]),"+f"(d[34]),"+f"(d[35]),"+f"(d[36]),"+f"(d[37]),"+f"(d[38]),"+f"(d[39]),"+f"(d[40]),"+f"(d[41]),"+f"(d[42]),"+f"(d[43]) : "r"(a0),"r"(a1),"r"(a2),"r"(a3),"l"(db),"r"(sc));
}
__device__ __forceinline__ void wg_ss_n72_t1(float* d, uint64_t da, uint64_t db, int sc) {
  asm volatile("{.reg .pred p; setp.ne.b32 p,%38,0; wgmma.mma_async.sync.aligned.m64n72k16.f32.bf16.bf16 {%0,%1,%2,%3,%4,%5,%6,%7,%8,%9,%10,%11,%12,%13,%14,%15,%16,%17,%18,%19,%20,%21,%22,%23,%24,%25,%26,%27,%28,%29,%30,%31,%32,%33,%34,%35}, %36, %37, p,1,1,0,1;}"
  : "+f"(d[0]),"+f"(d[1]),"+f"(d[2]),"+f"(d[3]),"+f"(d[4]),"+f"(d[5]),"+f"(d[6]),"+f"(d[7]),"+f"(d[8]),"+f"(d[9]),"+f"(d[10]),"+f"(d[11]),"+f"(d[12]),"+f"(d[13]),"+f"(d[14]),"+f"(d[15]),"+f"(d[16]),"+f"(d[17]),"+f"(d[18]),"+f"(d[19]),"+f"(d[20]),"+f"(d[21]),"+f"(d[22]),"+f"(d[23]),"+f"(d[24]),"+f"(d[25]),"+f"(d[26]),"+f"(d[27]),"+f"(d[28]),"+f"(d[29]),"+f"(d[30]),"+f"(d[31]),"+f"(d[32]),"+f"(d[33]),"+f"(d[34]),"+f"(d[35]) : "l"(da),"l"(db),"r"(sc));
}
template <int SC> __device__ __forceinline__ void wl_rs_n24_t1(float* d, const uint32_t* a, uint64_t e) {
  asm volatile("wgmma.mma_async.sync.aligned.m64n24k16.f32.bf16.bf16 {%0,%1,%2,%3,%4,%5,%6,%7,%8,%9,%10,%11}, {%12,%13,%14,%15}, %16, %17,1,1,1;"
  : "+f"(d[0]),"+f"(d[1]),"+f"(d[2]),"+f"(d[3]),"+f"(d[4]),"+f"(d[5]),"+f"(d[6]),"+f"(d[7]),"+f"(d[8]),"+f"(d[9]),"+f"(d[10]),"+f"(d[11]) : "r"(a[0]),"r"(a[1]),"r"(a[2]),"r"(a[3]),"l"(e),"n"(SC));
}
template <int SC> __device__ __forceinline__ void wl_rs_n64_t0(float* d, const uint32_t* a, uint64_t e) {
  asm volatile("wgmma.mma_async.sync.aligned.m64n64k16.f32.bf16.bf16 {%0,%1,%2,%3,%4,%5,%6,%7,%8,%9,%10,%11,%12,%13,%14,%15,%16,%17,%18,%19,%20,%21,%22,%23,%24,%25,%26,%27,%28,%29,%30,%31}, {%32,%33,%34,%35}, %36, %37,1,1,0;"
  : "+f"(d[0]),"+f"(d[1]),"+f"(d[2]),"+f"(d[3]),"+f"(d[4]),"+f"(d[5]),"+f"(d[6]),"+f"(d[7]),"+f"(d[8]),"+f"(d[9]),"+f"(d[10]),"+f"(d[11]),"+f"(d[12]),"+f"(d[13]),"+f"(d[14]),"+f"(d[15]),"+f"(d[16]),"+f"(d[17]),"+f"(d[18]),"+f"(d[19]),"+f"(d[20]),"+f"(d[21]),"+f"(d[22]),"+f"(d[23]),"+f"(d[24]),"+f"(d[25]),"+f"(d[26]),"+f"(d[27]),"+f"(d[28]),"+f"(d[29]),"+f"(d[30]),"+f"(d[31]) : "r"(a[0]),"r"(a[1]),"r"(a[2]),"r"(a[3]),"l"(e),"n"(SC));
}

#define POLY_MASK 0xB5u
#define QSCALE (0.23570226039551584f * 1.4426950408889634f)

__device__ __forceinline__ void pf_l2(const void* p) { asm volatile("prefetch.global.L2 [%0];" ::"l"(p)); }
__global__ void __launch_bounds__(256) k0_kernel(const __nv_bfloat16* __restrict__ x, const __nv_bfloat16* __restrict__ c,
                                                 const __nv_bfloat16* __restrict__ wmod) {
  if (threadIdx.x == 0) TS(0, 0);
  pdl_launch();
  const int tid = threadIdx.x, lane = tid & 31, warp = tid >> 5;
  if (blockIdx.x < 108) {
    __shared__ float red[8][32];
    const int col0 = blockIdx.x * 32 + (tid & 3) * 8, r0 = tid >> 2;
    uint4 w[9];
#pragma unroll
    for (int i = 0; i < 9; i++) w[i] = __ldg((const uint4*)(wmod + (size_t)(r0 + 64 * i) * 3456 + col0));
    float acc[8] = {0, 0, 0, 0, 0, 0, 0, 0};
#pragma unroll
    for (int i = 0; i < 9; i++) {
      float cv = __bfloat162float(c[r0 + 64 * i]);
      float sv = rbf(cv / (1.0f + __expf(-cv)));
      acc[0] += sv * bf_lo(w[i].x); acc[1] += sv * bf_hi(w[i].x);
      acc[2] += sv * bf_lo(w[i].y); acc[3] += sv * bf_hi(w[i].y);
      acc[4] += sv * bf_lo(w[i].z); acc[5] += sv * bf_hi(w[i].z);
      acc[6] += sv * bf_lo(w[i].w); acc[7] += sv * bf_hi(w[i].w);
    }
#pragma unroll
    for (int j = 0; j < 8; j++) {
      acc[j] += __shfl_xor_sync(~0u, acc[j], 4);
      acc[j] += __shfl_xor_sync(~0u, acc[j], 8);
      acc[j] += __shfl_xor_sync(~0u, acc[j], 16);
    }
    if (lane < 4) {
#pragma unroll
      for (int j = 0; j < 8; j++) red[warp][lane * 8 + j] = acc[j];
    }
    __syncthreads();
    if (tid < 32) {
      float s = 0;
#pragma unroll
      for (int j = 0; j < 8; j++) s += red[j][tid];
      s = rbf(s);
      int n = blockIdx.x * 32 + tid, part = n / DM, col = n % DM;
      if (part == 2) g_ga[col] = s;
      else if (part == 5) g_gb[col] = __float2bfloat16_rn(s);
      else {
        __nv_bfloat16* tab = (__nv_bfloat16*)(part < 2 ? g_tab1 : g_tab2);
        bool shift = (part == 0 || part == 3);
        int kk = col >> 4, half = (col >> 3) & 1, cq = (col & 7) >> 1, e = col & 1;
        tab[((kk * 4 + cq) * 4 + half * 2 + (shift ? 1 : 0)) * 2 + e] = __float2bfloat16_rn(shift ? s : 1.0f + s);
      }
    }
    if (blockIdx.x == 0 && tid >= 64 && tid < 64 + 80) g_cnt[tid - 64] = 0;
  } else {
    const int row0 = (blockIdx.x - 108) * 16 + warp * 2;
    uint32_t v[2][9];
#pragma unroll
    for (int r = 0; r < 2; r++)
#pragma unroll
      for (int i = 0; i < 9; i++) v[r][i] = __ldg((const uint32_t*)(x + (size_t)(row0 + r) * DM) + lane + 32 * i);
#pragma unroll
    for (int r = 0; r < 2; r++) {
      float s = 0;
#pragma unroll
      for (int i = 0; i < 9; i++) s += bf_lo(v[r][i]) + bf_hi(v[r][i]);
#pragma unroll
      for (int o = 16; o; o >>= 1) s += __shfl_xor_sync(~0u, s, o);
      float mean = s * (1.0f / DM), q = 0;
#pragma unroll
      for (int i = 0; i < 9; i++) {
        float a = bf_lo(v[r][i]) - mean, b = bf_hi(v[r][i]) - mean;
        q += a * a + b * b;
      }
#pragma unroll
      for (int o = 16; o; o >>= 1) q += __shfl_xor_sync(~0u, q, o);
      if (lane == 0) g_stat1[row0 + r] = ln_consts(mean, q * (1.0f / DM));
    }
  }
  if (threadIdx.x == 0) TS(0, 1);
}

#define NSTG 6
#define STG_BYTES 16384
#define R_BYTES (8 * 16384)
#define GEMM_SMEM (R_BYTES + NSTG * STG_BYTES + 3072)

struct Ring {
  uint32_t base, full, empty;
  int st;
  uint32_t ph;
  __device__ __forceinline__ void next() { if (++st == NSTG) { st = 0; ph ^= 1; } }
};

__device__ __forceinline__ void load_a_chunk(uint32_t (*a)[4], uint32_t chunk_base, int row_in_tile, int lane) {
  const int r = row_in_tile + (lane & 7) + ((lane >> 3) & 1) * 8;
  const uint32_t rb = chunk_base + r * 128;
#pragma unroll
  for (int k = 0; k < 4; k++) ldsm4(a[k], rb + (((k * 2 + (lane >> 4)) ^ (r & 7)) << 4));
}

#define MMA_TILE(FN, acc, a, ring, lane)                                        \
  {                                                                             \
    uint32_t prev_empty = 0;                                                    \
    _Pragma("unroll") for (int s = 0; s < 9; s++) {                             \
      mbar_wait(ring.full + ring.st * 8, ring.ph);                              \
      WG_FENCE();                                                               \
      uint32_t sa_ = ring.base + ring.st * STG_BYTES;                           \
      asm volatile("" : "+r"(sa_));                                             \
      uint64_t db = mkdesc(sa_, 8192, 1024, 1);                                 \
      _Pragma("unroll") for (int k = 0; k < 4; k++)                             \
          FN(acc, a[s * 4 + k][0], a[s * 4 + k][1], a[s * 4 + k][2], a[s * 4 + k][3], db + k * 128, (s | k) != 0); \
      WG_COMMIT();                                                              \
      if (s > 0) { WG_WAIT(1); if (lane == 0) mbar_arrive(prev_empty); }        \
      prev_empty = ring.empty + ring.st * 8;                                    \
      ring.next();                                                              \
    }                                                                           \
    WG_WAIT(0);                                                                 \
    if (lane == 0) mbar_arrive(prev_empty);                                     \
  }

template <int NG, int G0>
__device__ __forceinline__ void qkv_stage(const float* acc, uint32_t stg, int rowl, int cq, int col_base) {
  const float vs0 = ((POLY_MASK >> ((rowl >> 3) & 7)) & 1) ? 0.5f : 1.0f, vs1 = ((POLY_MASK >> (((rowl >> 3) + 1) & 7)) & 1) ? 0.5f : 1.0f;
#pragma unroll
  for (int i = 0; i < NG; i++) {
    const int cc = (G0 + i) * 8 + cq * 2;
    const int slot = (cc * 3641) >> 16, d = cc - slot * 18;
    const int gc = col_base + cc;
    const float sc0 = gc < DM ? QSCALE : (gc < 2 * DM ? vs0 : 1.0f), sc1 = gc < DM ? QSCALE : (gc < 2 * DM ? vs1 : 1.0f);
    const uint32_t ad = stg + slot * 6144 + (d >> 3) * 128 + (d & 7) * 2 + (rowl >> 3) * 384 + (rowl & 7) * 16;
    asm volatile("st.shared.b32 [%0],%1;" ::"r"(ad), "r"(pack_bf16(acc[4 * i] * sc0, acc[4 * i + 1] * sc0)) : "memory");
    asm volatile("st.shared.b32 [%0],%1;" ::"r"(ad + 384), "r"(pack_bf16(acc[4 * i + 2] * sc1, acc[4 * i + 3] * sc1)) : "memory");
  }
}

__global__ void __launch_bounds__(384, 1) k1_kernel(const __grid_constant__ CUtensorMap mx, const __grid_constant__ CUtensorMap mw) {
  extern __shared__ __align__(1024) uint8_t smem_raw[];
  const uint32_t sb = (s2u(smem_raw) + 1023) & ~1023u;
  const uint32_t R = sb, RING = sb + R_BYTES, BAR = RING + NSTG * STG_BYTES;
  const uint32_t full = BAR, empty = BAR + 64, xfull = BAR + 128;
  const int tid = threadIdx.x, lane = tid & 31, warp = tid >> 5;
  const int mb = blockIdx.x >> 3, nb = blockIdx.x & 7;
  if (tid == 0) {
    TS(1, 0);
    for (int i = 0; i < NSTG; i++) { mbar_init(full + i * 8, 1); mbar_init(empty + i * 8, 8); }
    for (int i = 0; i < 8; i++) mbar_init(xfull + i * 8, 1);
    fence_bar_init();
  }
  __syncthreads();
  pdl_launch();
  if (warp >= 8) {
    REG_DEC(24);
    if (warp == 8) {
      if (lane == 0) {
        for (int c = 0; c < 8; c++) { mbar_expect(xfull + c * 8, 16384); tma2d(R + c * 16384, &mx, c * 64, mb * 128, xfull + c * 8); }
        mbar_expect(full, 16384);
        tma2d(RING, &mx, 512, mb * 128, full);
        int st = 1; uint32_t ph = 0;
        for (int it = 0; it < 18; it++) {
          const int t = it / 9, s = it - t * 9;
          mbar_wait(empty + st * 8, ph ^ 1);
          mbar_expect(full + st * 8, 16384);
          tma2d(RING + st * STG_BYTES, &mw, nb * 216 + t * 128, s * 64, full + st * 8);
          tma2d(RING + st * STG_BYTES + 8192, &mw, nb * 216 + t * 128 + 64, s * 64, full + st * 8);
          if (++st == NSTG) { st = 0; ph ^= 1; }
        }
      }
      pdl_wait();
    } else {
      const int ht = tid - 288;
      bar_sync(1, 352);
      for (int i = ht; i < 12 * 128; i += 96) {
        const int slot = i >> 7, row = i & 127, type = (nb * 12 + slot) >> 5;
        uint32_t v = 0;
        if (type == 1) v = ((POLY_MASK >> ((row >> 3) & 7)) & 1) ? 0x43403F00u : 0x40253F80u;
        if (type == 2) v = 0x3F80u;
        const uint32_t ad = R + slot * 6144 + (row >> 3) * 384 + 256 + (row & 7) * 16;
        asm volatile("st.shared.b32 [%0],%1;" ::"r"(ad + 4), "r"(v) : "memory");
        asm volatile("st.shared.v2.b32 [%0],{%1,%1};" ::"r"(ad + 8), "r"(0) : "memory");
      }
      fence_async_smem();
      pdl_wait();
#pragma unroll 1
      for (int t = 0; t < 2; t++) {
        bar_sync(2 + t, 352);
        const int s0 = t ? 7 : 0, s1 = t ? 12 : 7;
        if (ht == 0) {
          for (int s = s0; s < s1; s++) bulk_s2g(g_qkv + (size_t)(nb * 12 + s) * 98304 + mb * 6144, R + s * 6144, 6144);
          bulk_commit();
        }
        for (int s = s0 + (warp - 9); s < s1; s += 3) {
          const int gs = nb * 12 + s;
          if ((gs >> 5) != 1) continue;
          float mx2 = 0;
#pragma unroll 1
          for (int row = lane; row < 128; row += 32) {
            const uint32_t ad = R + s * 6144 + (row >> 3) * 384 + (row & 7) * 16;
            float q = 0;
#pragma unroll 1
            for (int ch = 0; ch < 3; ch++) {
              uint32_t u0, u1, u2, u3;
              asm volatile("ld.shared.v4.b32 {%0,%1,%2,%3},[%4];" : "=r"(u0), "=r"(u1), "=r"(u2), "=r"(u3) : "r"(ad + ch * 128));
              if (ch == 2) u1 = 0;
              q += bf_lo(u0) * bf_lo(u0) + bf_hi(u0) * bf_hi(u0) + bf_lo(u1) * bf_lo(u1) + bf_hi(u1) * bf_hi(u1);
              q += bf_lo(u2) * bf_lo(u2) + bf_hi(u2) * bf_hi(u2) + bf_lo(u3) * bf_lo(u3) + bf_hi(u3) * bf_hi(u3);
            }
            if ((POLY_MASK >> ((row >> 3) & 7)) & 1) q *= 4.0f;
            mx2 = (q > mx2 || q != q) ? q : mx2;
            if (mx2 != mx2) mx2 = __int_as_float(0x7f800000);
          }
#pragma unroll
          for (int o = 16; o; o >>= 1) mx2 = fmaxf(mx2, __shfl_xor_sync(~0u, mx2, o));
          if (lane == 0) g_kmax[(gs & 31) * 16 + mb] = mx2;
        }
      }
      if (ht == 0) bulk_wait0();
      if (ht == 0) TS(1, 8);
    }
  } else {
    REG_INC(240);
    uint32_t a[36][4];
    const int rowl = warp * 16;
#pragma unroll
    for (int c = 0; c < 8; c++) { mbar_wait(xfull + c * 8, 0); load_a_chunk(&a[c * 4], R + c * 16384, rowl, lane); }
    mbar_wait(full, 0);
    load_a_chunk(&a[32], RING, rowl, lane);
    __syncwarp();
    if (lane == 0) mbar_arrive(empty);
    bar_arrive(1, 352);
    if (tid == 0) TS(1, 1);
    pdl_wait();
    if (tid == 0) TS(1, 2);
    {
      const int g = lane >> 2, cq = lane & 3;
      const uint4 s0 = g_stat1[mb * 128 + rowl + g], s1 = g_stat1[mb * 128 + rowl + g + 8];
#pragma unroll
      for (int k = 0; k < 36; k++) {
        if ((k & 3) == 0) asm volatile("" ::: "memory");
        const uint4 t = g_tab1[k * 4 + cq];
        a[k][0] = ln_apply(a[k][0], s0, t.x, t.y);
        a[k][1] = ln_apply(a[k][1], s1, t.x, t.y);
        a[k][2] = ln_apply(a[k][2], s0, t.z, t.w);
        a[k][3] = ln_apply(a[k][3], s1, t.z, t.w);
      }
    }
    bar_sync(4, 256);
    Ring ring{RING, full, empty, 1, 0};
    float acc[64];
    if (tid == 0) TS(1, 3);
    MMA_TILE(wg_rs_n128_t1, acc, a, ring, lane);
    if (tid == 0) TS(1, 4);
    qkv_stage<16, 0>(acc, R, rowl + (lane >> 2), lane & 3, nb * 216);
    fence_async_smem();
    bar_arrive(2, 352);
    if (tid == 0) TS(1, 5);
    MMA_TILE(wg_rs_n88_t1, acc, a, ring, lane);
    if (tid == 0) TS(1, 6);
    qkv_stage<11, 16>(acc, R, rowl + (lane >> 2), lane & 3, nb * 216);
    fence_async_smem();
    bar_arrive(3, 352);
    if (tid == 0) TS(1, 7);
  }
}

#define ATT_SMEM (2 * 98304 + 1024 + 256)

__device__ __forceinline__ uint32_t exp2_pair_fma(float t0, float t1) {
  uint32_t y;
  asm("prmt.b32 %0,%1,%2,0x6521;" : "=r"(y) : "r"(__float_as_uint(t0)), "r"(__float_as_uint(t1)));
  return hfma2(y, y | 0x3F803F80u, y | 0x007F007Fu);
}

__device__ __forceinline__ void softmax_fast(const float* s, uint32_t* p) {
#pragma unroll
  for (int i = 0; i < 8; i++) {
    if ((POLY_MASK >> i) & 1) {
      p[2 * i] = exp2_pair_fma(s[4 * i], s[4 * i + 1]);
      p[2 * i + 1] = exp2_pair_fma(s[4 * i + 2], s[4 * i + 3]);
    } else {
      p[2 * i] = pack_bf16(ex2f(s[4 * i]), ex2f(s[4 * i + 1]));
      p[2 * i + 1] = pack_bf16(ex2f(s[4 * i + 2]), ex2f(s[4 * i + 3]));
    }
  }
}
#define QK_MMA(S, kd)                                                           \
  wl_rs_n64_t0<0>(S, q, (kd));                                                  \
  wl_rs_n64_t0<1>(S, q + 4, (kd) + 16 - (8ull << 16));
#define PV_MMA(P, vd)                                                           \
  _Pragma("unroll") for (int t = 0; t < 4; t++) wl_rs_n24_t1<1>(o, P + 4 * t, (vd) + t * 48);

__device__ __forceinline__ float sq2(uint32_t v) { return bf_lo(v) * bf_lo(v) + bf_hi(v) * bf_hi(v); }
__device__ __forceinline__ void att_store(const float* o, int row0, int head, int lane) {
  const int cq = lane & 3;
  const float l0 = __shfl_sync(~0u, o[8], (lane & ~3) | 1), l1 = __shfl_sync(~0u, o[10], (lane & ~3) | 1);
  const float i0 = rcp_fast(l0), i1 = rcp_fast(l1);
  uint32_t* og = (uint32_t*)(g_o + (size_t)row0 * DM + head * 18 + cq * 2);
  og[0] = pack_bf16(o[0] * i0, o[1] * i0);
  og[4] = pack_bf16(o[4] * i0, o[5] * i0);
  og[8 * DM / 2] = pack_bf16(o[2] * i1, o[3] * i1);
  og[8 * DM / 2 + 4] = pack_bf16(o[6] * i1, o[7] * i1);
  if (cq == 0) {
    og[8] = pack_bf16(o[8] * i0, o[9] * i0);
    og[8 * DM / 2 + 8] = pack_bf16(o[10] * i1, o[11] * i1);
  }
}

__global__ void __launch_bounds__(512, 1) k2_kernel() {
  extern __shared__ __align__(1024) uint8_t smem_raw[];
  const uint32_t sb = (s2u(smem_raw) + 1023) & ~1023u;
  const uint32_t KS = sb, VS = sb + 98304, BAR = sb + 2 * 98304;
  const int tid = threadIdx.x, lane = tid & 31, warp = tid >> 5, wg = tid >> 7;
  const int head = blockIdx.x >> 2, qb = blockIdx.x & 3;
  if (tid == 0) {
    TS(2, 0);
    for (int i = 0; i < 16; i++) mbar_init(BAR + i * 8, 1);
    fence_bar_init();
  }
  __syncthreads();
  const int g = lane >> 2, cq = lane & 3;
  const int row0 = qb * 512 + wg * 128 + (warp & 3) * 16 + g;
  const uint8_t* qg = g_qkv + (size_t)head * 98304 + (row0 >> 3) * 384 + (row0 & 7) * 16 + cq * 4;
  pdl_wait();
  pdl_launch();
  if (tid == 0) TS(2, 1);
  const uint8_t* kg = g_qkv + (size_t)(32 + head) * 98304;
#define KV_LOAD(c) { mbar_expect(BAR + (c) * 8, 12288); bulk_g2s(KS + (c) * 6144, kg + (c) * 6144, 6144, BAR + (c) * 8); \
                     bulk_g2s(VS + (c) * 6144, kg + 32 * 98304 + (c) * 6144, 6144, BAR + (c) * 8); }
  if (lane == 0 && warp < 5) KV_LOAD(warp);
  __syncwarp();
  uint32_t q[8], q2[6];
  float kmax2 = __ldcg(g_kmax + head * 16 + (lane & 15));
#pragma unroll
  for (int i = 0; i < 6; i++) {
    q[i] = __ldcg((const uint32_t*)(qg + (i & 1) * 384 + (i >> 1) * 128));
    q2[i] = __ldcg((const uint32_t*)(qg + 3072 + (i & 1) * 384 + (i >> 1) * 128));
  }
  q[6] = __ldcg((const uint32_t*)(qg + 256 + 12 - cq * 4)); q[7] = __ldcg((const uint32_t*)(qg + 256 + 8 - cq * 4));
  const uint64_t dk = mkdesc(KS, 128, 384, 0), dv = mkdesc(VS, 384, 128, 0);
#pragma unroll
  for (int o = 8; o; o >>= 1) kmax2 = fmaxf(kmax2, __shfl_xor_sync(~0u, kmax2, o));
  float bd[4] = {sq2(q[0]) + sq2(q[2]) + sq2(q[4]), sq2(q[1]) + sq2(q[3]) + sq2(q[5]),
                 sq2(q2[0]) + sq2(q2[2]) + sq2(q2[4]), sq2(q2[1]) + sq2(q2[3]) + sq2(q2[5])};
  int ok = 1;
  if (tid == 0 && bd[0] + bd[3] + kmax2 != 1.2345f) TS(2, 5);
#pragma unroll
  for (int i = 0; i < 4; i++) {
    bd[i] += __shfl_xor_sync(~0u, bd[i], 1); bd[i] += __shfl_xor_sync(~0u, bd[i], 2);
    bd[i] = sqrt_fast(bd[i] * kmax2) * 1.01f + 1.0f;
    ok = ok && (bd[i] <= 62.0f);
  }
  {
    uint32_t all;
    asm volatile("{.reg .pred p,q; setp.ne.b32 p,%1,0; barrier.red.and.pred q,1,512,p; selp.u32 %0,1,0,q;}"
                 : "=r"(all) : "r"(ok) : "memory");
    ok = __all_sync(~0u, all);
  }
  float o[12];
#pragma unroll
  for (int i = 0; i < 12; i++) { o[i] = 0.f; asm volatile("" : "+f"(o[i])); }
  float s[32];
  uint32_t p[16];
  if (tid == 0) TS(2, 2);
  if (ok) {
    if (cq == 1) {
      q[4] = pack_bf16(-bd[0], 1.0f); q[5] = pack_bf16(-bd[1], 1.0f);
      q2[4] = pack_bf16(-bd[2], 1.0f); q2[5] = pack_bf16(-bd[3], 1.0f);
    }
    mbar_wait(BAR, 0);
    WG_FENCE();
    QK_MMA(s, dk);
    WG_COMMIT();
#pragma unroll 1
    for (int tile = 0; tile < 2; tile++) {
#pragma unroll 1
      for (int jj = 0; jj < 8; jj++) {
        const uint64_t kd = dk + (uint32_t)(jj * 768), vd = dv + (uint32_t)(jj * 768), kn = dk + (uint32_t)(((jj + 1) & 7) * 768);
        if (tile == 0) {
          if (lane == 0 && warp < 2 && 2 * jj + 5 + warp < 16) KV_LOAD(2 * jj + 5 + warp);
          __syncwarp();
          mbar_wait(BAR + jj * 16 + 8, 0); mbar_wait(BAR + ((jj * 16 + 16) & 127), 0); if (tid == 0) TS(2, 8 + jj); }
#pragma unroll
        for (int u = 0; u < 4; u++) {
          WG_WAIT(0);
          fence_regs<32>(s);
          softmax_fast(s, p);
          if (u == 3 && jj == 7) {
#pragma unroll
            for (int i = 0; i < 6; i++) q[i] = q2[i];
          }
          WG_FENCE();
          PV_MMA(p, vd + u * 192);
          QK_MMA(s, u < 3 ? kd + u * 192 + 192 : kn);
          WG_COMMIT();
        }
      }
      WG_WAIT(0);
      fence_regs<12>(o);
      att_store(o, row0 + tile * 64, head, lane);
#pragma unroll
      for (int i = 0; i < 12; i++) o[i] = 0.f;
      fence_regs<12>(o);
      if (tid == 0 && tile == 0) TS(2, 3);
    }
  } else {
    if (lane == 0 && warp >= 5) KV_LOAD(warp);
    __syncwarp();
#pragma unroll 1
    for (int tile = 0; tile < 2; tile++) {
      float m0 = -INFINITY, m1 = -INFINITY;
#pragma unroll 1
      for (int j = 0; j < 32; j++) {
        mbar_wait(BAR + (j >> 1) * 8, 0);
        WG_FENCE();
        QK_MMA(s, dk + (uint32_t)(j * 192));
        WG_COMMIT();
        WG_WAIT(0);
        fence_regs<32>(s);
#pragma unroll
        for (int i = 0; i < 32; i++) if ((POLY_MASK >> (i >> 2)) & 1) s[i] *= 2.0f;
        float x0 = m0, x1 = m1;
#pragma unroll
        for (int i = 0; i < 8; i++) {
          x0 = fmaxf(x0, fmaxf(s[4 * i], s[4 * i + 1]));
          x1 = fmaxf(x1, fmaxf(s[4 * i + 2], s[4 * i + 3]));
        }
        x0 = fmaxf(x0, __shfl_xor_sync(~0u, x0, 1)); x0 = fmaxf(x0, __shfl_xor_sync(~0u, x0, 2));
        x1 = fmaxf(x1, __shfl_xor_sync(~0u, x1, 1)); x1 = fmaxf(x1, __shfl_xor_sync(~0u, x1, 2));
        const float c0 = ex2f(m0 - x0), c1 = ex2f(m1 - x1);
        m0 = x0; m1 = x1;
#pragma unroll
        for (int i = 0; i < 3; i++) { o[4 * i] *= c0; o[4 * i + 1] *= c0; o[4 * i + 2] *= c1; o[4 * i + 3] *= c1; }
#pragma unroll
        for (int i = 0; i < 8; i++) {
          p[2 * i] = pack_bf16(ex2f(s[4 * i] - x0), ex2f(s[4 * i + 1] - x0));
          p[2 * i + 1] = pack_bf16(ex2f(s[4 * i + 2] - x1), ex2f(s[4 * i + 3] - x1));
        }
        WG_FENCE();
        PV_MMA(p, dv + (uint32_t)(j * 192));
        WG_COMMIT();
        WG_WAIT(0);
        fence_regs<12>(o);
      }
      att_store(o, row0 + tile * 64, head, lane);
#pragma unroll
      for (int i = 0; i < 12; i++) o[i] = 0.f;
#pragma unroll
      for (int i = 0; i < 6; i++) q[i] = q2[i];
    }
  }
  if (tid == 0) TS(2, 4);
}

#define K3_NSTG 4
#define K3_SMEM (9 * 16384 + K3_NSTG * 16384 + 1024 + 256)
__global__ void __launch_bounds__(288, 1) k3_kernel(const __grid_constant__ CUtensorMap mo, const __grid_constant__ CUtensorMap mw,
                                                    const __nv_bfloat16* __restrict__ x) {
  extern __shared__ __align__(1024) uint8_t smem_raw[];
  const uint32_t sb = (s2u(smem_raw) + 1023) & ~1023u;
  const uint32_t A = sb, RING = sb + 9 * 16384, BAR = RING + K3_NSTG * 16384;
  const uint32_t full = BAR, empty = BAR + 64, afull = BAR + 128;
  const int tid = threadIdx.x, lane = tid & 31, warp = tid >> 5;
  const int mb = blockIdx.x >> 3, nb = blockIdx.x & 7;
  if (tid == 0) {
    TS(3, 0);
    for (int i = 0; i < K3_NSTG; i++) { mbar_init(full + i * 8, 1); mbar_init(empty + i * 8, 8); }
    for (int i = 0; i < 9; i++) mbar_init(afull + i * 8, 1);
    fence_bar_init();
  }
  __syncthreads();
  pdl_launch();
  if (warp == 8) {
    if (lane == 0) {
      for (int s = 0; s < K3_NSTG; s++) {
        mbar_expect(full + s * 8, 16384);
        tma2d(RING + s * 16384, &mw, nb * 72, s * 64, full + s * 8);
        tma2d(RING + s * 16384 + 8192, &mw, nb * 72 + 64, s * 64, full + s * 8);
      }
      pdl_wait();
      for (int c = 0; c < 9; c++) { mbar_expect(afull + c * 8, 16384); tma2d(A + c * 16384, &mo, c * 64, mb * 128, afull + c * 8); }
      for (int s = K3_NSTG; s < 9; s++) {
        const int st = s % K3_NSTG;
        mbar_wait(empty + st * 8, ((s / K3_NSTG) & 1) ^ 1);
        mbar_expect(full + st * 8, 16384);
        tma2d(RING + st * 16384, &mw, nb * 72, s * 64, full + st * 8);
        tma2d(RING + st * 16384 + 8192, &mw, nb * 72 + 64, s * 64, full + st * 8);
      }
    }
  } else {
    const int g = lane >> 2, cq = lane & 3;
    const int row = mb * 128 + warp * 16 + g, col = nb * 72 + cq * 2;
    uint32_t xv[18];
#pragma unroll
    for (int i = 0; i < 9; i++) {
      xv[2 * i] = __ldg((const uint32_t*)(x + (size_t)row * DM + col + 8 * i));
      xv[2 * i + 1] = __ldg((const uint32_t*)(x + (size_t)(row + 8) * DM + col + 8 * i));
    }
    pdl_wait();
    if (tid == 0) TS(3, 1);
    float2 ga[9];
#pragma unroll
    for (int i = 0; i < 9; i++) ga[i] = *(const float2*)(g_ga + col + 8 * i);
    float acc[36];
    const uint32_t abase = A + (warp >> 2) * 8192;
#pragma unroll
    for (int s = 0; s < 9; s++) {
      const int st = s % K3_NSTG;
      mbar_wait(afull + s * 8, 0);
      mbar_wait(full + st * 8, (s / K3_NSTG) & 1);
      WG_FENCE();
#pragma unroll
      for (int k = 0; k < 4; k++)
        wg_ss_n72_t1(acc, mkdesc(abase + s * 16384 + k * 32, 16, 1024, 1), mkdesc(RING + st * 16384 + k * 2048, 8192, 1024, 1), (s | k) != 0);
      WG_COMMIT();
      if (s > 0) { WG_WAIT(1); if (lane == 0) mbar_arrive(empty + ((s - 1) % K3_NSTG) * 8); }
    }
    WG_WAIT(0);
    if (tid == 0) TS(3, 2);
    float s0 = 0, s1 = 0;
#pragma unroll
    for (int i = 0; i < 9; i++) {
      acc[4 * i] = rbf(bf_lo(xv[2 * i]) + rbf(ga[i].x * rbf(acc[4 * i])));
      acc[4 * i + 1] = rbf(bf_hi(xv[2 * i]) + rbf(ga[i].y * rbf(acc[4 * i + 1])));
      acc[4 * i + 2] = rbf(bf_lo(xv[2 * i + 1]) + rbf(ga[i].x * rbf(acc[4 * i + 2])));
      acc[4 * i + 3] = rbf(bf_hi(xv[2 * i + 1]) + rbf(ga[i].y * rbf(acc[4 * i + 3])));
      *(uint32_t*)(g_x1 + (size_t)row * DM + col + 8 * i) = pack_bf16(acc[4 * i], acc[4 * i + 1]);
      *(uint32_t*)(g_x1 + (size_t)(row + 8) * DM + col + 8 * i) = pack_bf16(acc[4 * i + 2], acc[4 * i + 3]);
      s0 += acc[4 * i] + acc[4 * i + 1];
      s1 += acc[4 * i + 2] + acc[4 * i + 3];
    }
    s0 += __shfl_xor_sync(~0u, s0, 1); s0 += __shfl_xor_sync(~0u, s0, 2);
    s1 += __shfl_xor_sync(~0u, s1, 1); s1 += __shfl_xor_sync(~0u, s1, 2);
    const float m0 = s0 * (1.0f / 72), m1 = s1 * (1.0f / 72);
    float q0 = 0, q1 = 0;
#pragma unroll
    for (int i = 0; i < 9; i++) {
      q0 += (acc[4 * i] - m0) * (acc[4 * i] - m0) + (acc[4 * i + 1] - m0) * (acc[4 * i + 1] - m0);
      q1 += (acc[4 * i + 2] - m1) * (acc[4 * i + 2] - m1) + (acc[4 * i + 3] - m1) * (acc[4 * i + 3] - m1);
    }
    q0 += __shfl_xor_sync(~0u, q0, 1); q0 += __shfl_xor_sync(~0u, q0, 2);
    q1 += __shfl_xor_sync(~0u, q1, 1); q1 += __shfl_xor_sync(~0u, q1, 2);
    if (cq == 0) {
      g_stat2[row * 8 + nb] = make_float2(m0, q0);
      g_stat2[(row + 8) * 8 + nb] = make_float2(m1, q1);
    }
    if (tid == 0) TS(3, 3);
  }
}

__device__ __forceinline__ uint4 ln2_consts(int row, int cq) {
  const float4 p = *(const float4*)(g_stat2 + row * 8 + cq * 2);
  float s = p.x + p.z;
  s += __shfl_xor_sync(~0u, s, 1); s += __shfl_xor_sync(~0u, s, 2);
  const float mean = s * 0.125f;
  float q = p.y + p.w + 72.0f * ((p.x - mean) * (p.x - mean) + (p.z - mean) * (p.z - mean));
  q += __shfl_xor_sync(~0u, q, 1); q += __shfl_xor_sync(~0u, q, 2);
  return ln_consts(mean, q * (1.0f / DM));
}
__device__ __forceinline__ uint32_t glu_pair(float g0, float g1, float u0, float u1) {
  const float s0 = fmaf(tanhf_fast(0.5f * g0), 0.5f, 0.5f), s1 = fmaf(tanhf_fast(0.5f * g1), 0.5f, 0.5f);
  return pack_bf16(s0 * u0, s1 * u1);
}
template <int NG>
__device__ __forceinline__ void stage_part(const float* acc, uint32_t stg, int lane) {
  const int r = (lane & 7) + ((lane >> 3) & 1) * 8;
#pragma unroll
  for (int i = 0; i < NG; i += 2) {
    const int ch = i + (lane >> 4);
    stsm4(stg + r * (NG * 16) + ((ch ^ (r & 7)) << 4), pack_bf16(acc[4 * i], acc[4 * i + 1]), pack_bf16(acc[4 * i + 2], acc[4 * i + 3]),
          pack_bf16(acc[4 * i + 4], acc[4 * i + 5]), pack_bf16(acc[4 * i + 6], acc[4 * i + 7]));
  }
}
__device__ __forceinline__ uint4 lds128(uint32_t a) {
  uint4 v;
  asm volatile("ld.shared.v4.b32 {%0,%1,%2,%3},[%4];" : "=r"(v.x), "=r"(v.y), "=r"(v.z), "=r"(v.w) : "r"(a) : "memory");
  return v;
}
__device__ __forceinline__ void sts128(uint32_t a, const uint4& v) {
  asm volatile("st.shared.v4.b32 [%0],{%1,%2,%3,%4};" ::"r"(a), "r"(v.x), "r"(v.y), "r"(v.z), "r"(v.w) : "memory");
}
__device__ __forceinline__ uint32_t res_pair(uint32_t x, uint32_t g, float s0, float s1) { return hadd2(x, hmul2(g, pack_bf16(s0, s1))); }

__global__ void __launch_bounds__(384, 1) k4_kernel(const __grid_constant__ CUtensorMap mx, const __grid_constant__ CUtensorMap mg,
                                                    const __grid_constant__ CUtensorMap mu, const __grid_constant__ CUtensorMap md,
                                                    __nv_bfloat16* __restrict__ out) {
  extern __shared__ __align__(1024) uint8_t smem_raw[];
  const uint32_t sb = s2u(smem_raw);
  const uint32_t R = sb, RING = sb + R_BYTES, BAR = RING + NSTG * STG_BYTES, TAB = BAR + 512;
  const uint32_t full = BAR, empty = BAR + 64, xfull = BAR + 128, gfull = BAR + 272, sfull = BAR + 320;
  const int tid = threadIdx.x, lane = tid & 31, warp = tid >> 5;
  const int mb = blockIdx.x >> 3, fb = blockIdx.x & 7;
  if (tid == 0) {
    TS(4, 0);
    if (sb & 1023) __trap();
    for (int i = 0; i < 10; i++) mbar_init(sfull + i * 8, 4);
    for (int i = 0; i < NSTG; i++) { mbar_init(full + i * 8, 1); mbar_init(empty + i * 8, 8); }
    for (int i = 0; i < 18; i++) mbar_init(xfull + i * 8, 1);
    for (int i = 0; i < 5; i++) mbar_init(gfull + i * 8, 1);
    mbar_arrive(full);
    fence_bar_init();
  }
  __syncthreads();
  if (warp >= 8) {
    REG_DEC(24);
    if (lane == 0) {
      if (warp == 8) {
        int st = 1; uint32_t ph = 0;
        for (int it = 0; it < 126; it++) {
          if (it == NSTG - 1) {
            pdl_wait();
            for (int c = 0; c < 18; c++) {
              const int w = c >= 9, k = c - w * 9;
              mbar_expect(xfull + c * 8, 8192);
              tma2d(R + k * 16384 + w * 8192, &mx, k * 64, mb * 128 + w * 64, xfull + c * 8);
            }
          }
          const int t = it / 9, s = it - t * 9;
          const uint32_t dst = RING + st * STG_BYTES, fb_ = full + st * 8;
          mbar_wait(empty + st * 8, ph ^ 1);
          if (t < 9) {
            mbar_expect(fb_, 16384);
            tma2d(dst, &mg, fb * 576 + t * 64, s * 64, fb_);
            tma2d(dst + 8192, &mu, fb * 576 + t * 64, s * 64, fb_);
          } else {
            mbar_expect(fb_, t < 13 ? 16384 : 8192);
            tma2d(dst, &md, (t - 9) * 128, fb * 576 + s * 64, fb_);
            if (t < 13) tma2d(dst + 8192, &md, (t - 9) * 128 + 64, fb * 576 + s * 64, fb_);
          }
          if (++st == NSTG) { st = 0; ph ^= 1; }
        }
      } else if (warp < 11) {
        const int wg = warp - 9;
#pragma unroll 1
        for (int p = 0; p < 5; p++) {
          uint8_t* dst = g_part + (size_t)((fb * 16 + mb) * 5 + p) * 32768;
          mbar_wait(sfull + (p * 2 + wg) * 8, 0);
          if (p < 4) {
            bulk_s2g(dst + wg * 16384, R + p * 32768 + wg * 8192, 8192);
            bulk_s2g(dst + wg * 16384 + 8192, R + p * 32768 + 16384 + wg * 8192, 8192);
          } else {
            bulk_s2g(dst + wg * 8192, RING + wg * STG_BYTES + 8192, 8192);
          }
          bulk_commit();
          bulk_wait0();
          asm volatile("fence.proxy.async;" ::: "memory");
          asm volatile("red.release.gpu.global.add.u32 [%0],1;" ::"l"(g_cnt + mb * 5 + p) : "memory");
        }
      } else {
        mbar_wait(sfull, 0);
#pragma unroll 1
        for (int p = 0; p < 5; p++) {
          unsigned int v; int n = 0;
          do {
            asm volatile("ld.acquire.gpu.global.u32 %0,[%1];" : "=r"(v) : "l"(g_cnt + mb * 5 + p) : "memory");
          } while (v < 16 && ++n < 20000000);
          if (v < 16) __trap();
          asm volatile("fence.proxy.async;" ::: "memory");
          const uint32_t sz = p < 4 ? 4096 : 2048;
          mbar_expect(gfull + p * 8, sz * 8);
#pragma unroll 1
          for (int f = 0; f < 8; f++)
            bulk_g2s(p < 4 ? R + p * 32768 + f * 4096 : RING + (2 + (f >> 2)) * STG_BYTES + 8192 + (f & 3) * 2048,
                     g_part + (size_t)((f * 16 + mb) * 5 + p) * 32768 + fb * sz, sz, gfull + p * 8);
        }
      }
    }
  } else {
    REG_INC(240);
    uint32_t a[36][4];
    const int wg = warp >> 2, wl = warp & 3;
    if (tid < 144) sts128(TAB + tid * 16, g_tab2[tid]);
    bar_sync(1, 256);
    pdl_wait();
    TSS(0);
    {
      const int g = lane >> 2, cq = lane & 3;
      const uint4 s0 = ln2_consts(mb * 128 + warp * 16 + g, cq), s1 = ln2_consts(mb * 128 + warp * 16 + g + 8, cq);
      if (wg == 1) bar_sync(4, 256);
#pragma unroll
      for (int c = 0; c < 9; c++) {
        mbar_wait(xfull + (wg * 9 + c) * 8, 0);
        load_a_chunk(&a[c * 4], R + c * 16384, warp * 16, lane);
        if (c == 8) { __syncwarp(); if (lane == 0) mbar_arrive(empty); }
#pragma unroll
        for (int k = c * 4; k < c * 4 + 4; k++) {
          const uint4 t = lds128(TAB + (k * 4 + cq) * 16);
          a[k][0] = ln_apply(a[k][0], s0, t.x, t.y);
          a[k][1] = ln_apply(a[k][1], s1, t.x, t.y);
          a[k][2] = ln_apply(a[k][2], s0, t.z, t.w);
          a[k][3] = ln_apply(a[k][3], s1, t.z, t.w);
        }
      }
    }
    if (wg == 0) bar_arrive(4, 256);
    TSS(1);
    Ring ring{RING, full, empty, 1, 0};
    float acc[64];
    const uint32_t hsp = R + warp * 2048 + lane * 16;
#pragma unroll 1
    for (int t = 0; t < 8; t++) {
      MMA_TILE(wg_rs_n128_t1, acc, a, ring, lane);
#pragma unroll
      for (int j = 0; j < 4; j++) {
        uint32_t h[4];
#pragma unroll
        for (int e = 0; e < 4; e++) h[e] = glu_pair(acc[8 * j + 2 * e], acc[8 * j + 2 * e + 1], acc[32 + 8 * j + 2 * e], acc[32 + 8 * j + 2 * e + 1]);
        asm volatile("st.shared.v4.b32 [%0],{%1,%2,%3,%4};" ::"r"(hsp + t * 16384 + j * 512), "r"(h[0]), "r"(h[1]), "r"(h[2]), "r"(h[3]) : "memory");
      }
    }
    MMA_TILE(wg_rs_n128_t1, acc, a, ring, lane);
#pragma unroll
    for (int j = 0; j < 4; j++)
#pragma unroll
      for (int e = 0; e < 4; e++)
        a[32 + j][e] = glu_pair(acc[8 * j + 2 * e], acc[8 * j + 2 * e + 1], acc[32 + 8 * j + 2 * e], acc[32 + 8 * j + 2 * e + 1]);
#pragma unroll
    for (int k = 0; k < 32; k++)
      asm volatile("ld.shared.v4.b32 {%0,%1,%2,%3},[%4];" : "=r"(a[k][0]), "=r"(a[k][1]), "=r"(a[k][2]), "=r"(a[k][3]) : "r"(hsp + (k >> 2) * 16384 + (k & 3) * 512) : "memory");
    TSS(2);
    const uint32_t stg = R + (wl >> 1) * 16384 + wg * 8192 + (wl & 1) * 4096;
#pragma unroll 1
    for (int p = 0; p < 4; p++) {
      MMA_TILE(wg_rs_n128_t1, acc, a, ring, lane);
      if (p == 0) bar_sync(2 + wg, 128);
      stage_part<16>(acc, stg + p * 32768, lane);
      fence_async_smem();
      __syncwarp();
      if (lane == 0) mbar_arrive(sfull + (p * 2 + wg) * 8);
    }
    MMA_TILE(wg_rs_n64_t1, acc, a, ring, lane);
    stage_part<8>(acc, RING + wg * STG_BYTES + 8192 + wl * 2048, lane);
    fence_async_smem();
    __syncwarp();
    if (lane == 0) mbar_arrive(sfull + (8 + wg) * 8);
    TSS(3);
    const int rl = tid >> 4, ch = tid & 15;
    const size_t off = (size_t)(mb * 128 + fb * 16 + rl) * DM + ch * 8;
    uint4 xv[5], gv[5];
#pragma unroll
    for (int p = 0; p < 5; p++)
      if (p < 4 || ch < 8) { xv[p] = __ldcg((const uint4*)(g_x1 + off + p * 128)); gv[p] = __ldcg((const uint4*)(g_gb + p * 128 + ch * 8)); }
#pragma unroll
    for (int p = 0; p < 5; p++) {
      if (p == 4 && ch >= 8) break;
      mbar_wait(gfull + p * 8, 0);
      float r8[8] = {0, 0, 0, 0, 0, 0, 0, 0};
#pragma unroll
      for (int f = 0; f < 8; f++) {
        const uint4 v = lds128((p < 4 ? R + p * 32768 + f * 4096 + rl * 256 : RING + (2 + (f >> 2)) * STG_BYTES + 8192 + (f & 3) * 2048 + rl * 128) +
                               ((ch ^ (rl & 7)) << 4));
        r8[0] += bf_lo(v.x); r8[1] += bf_hi(v.x); r8[2] += bf_lo(v.y); r8[3] += bf_hi(v.y);
        r8[4] += bf_lo(v.z); r8[5] += bf_hi(v.z); r8[6] += bf_lo(v.w); r8[7] += bf_hi(v.w);
      }
      uint4 r;
      r.x = res_pair(xv[p].x, gv[p].x, r8[0], r8[1]);
      r.y = res_pair(xv[p].y, gv[p].y, r8[2], r8[3]);
      r.z = res_pair(xv[p].z, gv[p].z, r8[4], r8[5]);
      r.w = res_pair(xv[p].w, gv[p].w, r8[6], r8[7]);
      *(uint4*)(out + off + p * 128) = r;
      if (p >= 2) TSS(2 + p);
    }
    TSDUMP(4);
  }
}

typedef CUresult (*EncodeFn)(CUtensorMap*, CUtensorMapDataType, cuuint32_t, void*, const cuuint64_t*, const cuuint64_t*,
                             const cuuint32_t*, const cuuint32_t*, CUtensorMapInterleave, CUtensorMapSwizzle,
                             CUtensorMapL2promotion, CUtensorMapFloatOOBfill);
static void make_map(EncodeFn fn, CUtensorMap* m, const void* p, int rows, int cols, int box_rows) {
  cuuint64_t dims[2] = {(cuuint64_t)cols, (cuuint64_t)rows};
  cuuint64_t strides[1] = {(cuuint64_t)cols * 2};
  cuuint32_t box[2] = {64, (cuuint32_t)box_rows};
  cuuint32_t es[2] = {1, 1};
  fn(m, CU_TENSOR_MAP_DATA_TYPE_BFLOAT16, 2, (void*)p, dims, strides, box, es, CU_TENSOR_MAP_INTERLEAVE_NONE,
     CU_TENSOR_MAP_SWIZZLE_128B, CU_TENSOR_MAP_L2_PROMOTION_L2_256B, CU_TENSOR_MAP_FLOAT_OOB_FILL_NONE);
}
template <typename... KA, typename... A>
static void launch(void (*k)(KA...), int grid, int block, int smem, bool pdl, A... args) {
  cudaLaunchConfig_t cfg = {};
  cfg.gridDim = dim3(grid); cfg.blockDim = dim3(block); cfg.dynamicSmemBytes = smem; cfg.stream = cudaStreamPerThread;
  cudaLaunchAttribute at;
  at.id = cudaLaunchAttributeProgrammaticStreamSerialization;
  at.val.programmaticStreamSerializationAllowed = 1;
  cfg.attrs = &at; cfg.numAttrs = pdl ? 1 : 0;
  cudaLaunchKernelEx(&cfg, k, KA(args)...);
}

extern "C" void kernel_launch(void* const* d_in, const int* in_sizes, int n_in, void* d_out, int out_size) {
  const __nv_bfloat16* x = (const __nv_bfloat16*)d_in[0];
  void* fnp = nullptr;
  cudaDriverEntryPointQueryResult qr;
  cudaGetDriverEntryPoint("cuTensorMapEncodeTiled", &fnp, cudaEnableDefault, &qr);
  EncodeFn fn = (EncodeFn)fnp;
  void *po, *px1;
  cudaGetSymbolAddress(&po, g_o);
  cudaGetSymbolAddress(&px1, g_x1);
  CUtensorMap mx, mqkv, mo, mwo, mx1, mg, mu, md;
  make_map(fn, &mx, x, SEQ, DM, 128);
  make_map(fn, &mqkv, d_in[1], DM, 3 * DM, 64);
  make_map(fn, &mo, po, SEQ, DM, 128);
  make_map(fn, &mwo, d_in[2], DM, DM, 64);
  make_map(fn, &mx1, px1, SEQ, DM, 64);
  make_map(fn, &mg, d_in[4], DM, FF, 64);
  make_map(fn, &mu, d_in[5], DM, FF, 64);
  make_map(fn, &md, d_in[6], FF, DM, 64);
  cudaFuncSetAttribute(k1_kernel, cudaFuncAttributeMaxDynamicSharedMemorySize, GEMM_SMEM);
  cudaFuncSetAttribute(k2_kernel, cudaFuncAttributeMaxDynamicSharedMemorySize, ATT_SMEM);
  cudaFuncSetAttribute(k3_kernel, cudaFuncAttributeMaxDynamicSharedMemorySize, K3_SMEM);
  cudaFuncSetAttribute(k4_kernel, cudaFuncAttributeMaxDynamicSharedMemorySize, GEMM_SMEM);
  launch(k0_kernel, 108 + 128, 256, 0, false, x, (const __nv_bfloat16*)d_in[7], (const __nv_bfloat16*)d_in[8]);
  launch(k1_kernel, 128, 384, GEMM_SMEM, true, mx, mqkv);
  launch(k2_kernel, 128, 512, ATT_SMEM, true);
  launch(k3_kernel, 128, 288, K3_SMEM, true, mo, mwo, x);
  launch(k4_kernel, 128, 384, GEMM_SMEM, true, mx1, mg, mu, md, (__nv_bfloat16*)d_out);
}
```

```cpp
#include <cuda_runtime.h>
#include <cuda_bf16.h>
#include <cuda.h>
#include <stdint.h>

#define SEQ 2048
#define DM 576
#define NH 32
#define FF 4608

__device__ uint4 g_tab1[36 * 4];
__device__ uint4 g_tab2[36 * 4];
__device__ float g_ga[DM];
__device__ __align__(16) __nv_bfloat16 g_gb[DM];
__device__ uint4 g_stat1[SEQ];
__device__ float2 g_stat2[SEQ * 8];
__device__ __align__(1024) uint8_t g_qkv[96 * 98304];
__device__ float g_kmax[NH * 16];
__device__ __align__(1024) __nv_bfloat16 g_o[SEQ * DM];
__device__ __align__(1024) __nv_bfloat16 g_x1[SEQ * DM];
__device__ __align__(1024) uint8_t g_part[8 * 16 * 5 * 2 * 16384];
__device__ unsigned int g_cnt[16 * 5];

#define TS(k, i)
#define TSS(i)
#define TSDUMP(k)
__device__ __forceinline__ uint32_t s2u(const void* p) { return (uint32_t)__cvta_generic_to_shared(p); }
__device__ __forceinline__ void mbar_init(uint32_t b, int c) { asm volatile("mbarrier.init.shared::cta.b64 [%0],%1;" ::"r"(b), "r"(c)); }
__device__ __forceinline__ void mbar_expect(uint32_t b, uint32_t n) { asm volatile("mbarrier.arrive.expect_tx.shared::cta.b64 _,[%0],%1;" ::"r"(b), "r"(n) : "memory"); }
__device__ __forceinline__ void mbar_arrive(uint32_t b) { asm volatile("mbarrier.arrive.shared::cta.b64 _,[%0];" ::"r"(b) : "memory"); }
__device__ __forceinline__ void mbar_wait(uint32_t b, uint32_t ph) {
  asm volatile(
      "{.reg .pred p; .reg .u32 n;\n"
      "mbarrier.try_wait.parity.shared::cta.b64 p,[%0],%1;\n"
      "@p bra D;\n"
      "mov.u32 n,0;\n"
      "W: mbarrier.try_wait.parity.shared::cta.b64 p,[%0],%1;\n"
      "@p bra D;\n"
      "add.u32 n,n,1; setp.lt.u32 p,n,4000000; @p bra W;\n"
      "trap;\n"
      "D: }" ::"r"(b), "r"(ph) : "memory");
}
__device__ __forceinline__ void tma2d(uint32_t dst, const CUtensorMap* m, int c0, int c1, uint32_t bar) {
  asm volatile("cp.async.bulk.tensor.2d.shared::cluster.global.mbarrier::complete_tx::bytes [%0],[%1,{%3,%4}],[%2];"
               ::"r"(dst), "l"(m), "r"(bar), "r"(c0), "r"(c1) : "memory");
}
__device__ __forceinline__ void bulk_g2s(uint32_t dst, const void* src, uint32_t bytes, uint32_t bar) {
  asm volatile("cp.async.bulk.shared::cluster.global.mbarrier::complete_tx::bytes [%0],[%1],%2,[%3];"
               ::"r"(dst), "l"(src), "r"(bytes), "r"(bar) : "memory");
}
__device__ __forceinline__ void bulk_s2g(void* dst, uint32_t src, uint32_t bytes) {
  asm volatile("cp.async.bulk.global.shared::cta.bulk_group [%0],[%1],%2;" ::"l"(dst), "r"(src), "r"(bytes) : "memory");
}
__device__ __forceinline__ void bulk_commit() { asm volatile("cp.async.bulk.commit_group;" ::: "memory"); }
__device__ __forceinline__ void bulk_wait0() { asm volatile("cp.async.bulk.wait_group 0;" ::: "memory"); }
__device__ __forceinline__ void prefetch_map(const CUtensorMap* m) { asm volatile("prefetch.tensormap [%0];" ::"l"(m) : "memory"); }
__device__ __forceinline__ void fence_async_smem() { asm volatile("fence.proxy.async.shared::cta;" ::: "memory"); }
__device__ __forceinline__ void fence_bar_init() { asm volatile("fence.mbarrier_init.release.cluster;" ::: "memory"); }
__device__ __forceinline__ void pdl_wait() { asm volatile("griddepcontrol.wait;" ::: "memory"); }
__device__ __forceinline__ void pdl_launch() { asm volatile("griddepcontrol.launch_dependents;" ::: "memory"); }
__device__ __forceinline__ void bar_sync(int id, int n) { asm volatile("bar.sync %0,%1;" ::"r"(id), "r"(n) : "memory"); }
__device__ __forceinline__ void bar_arrive(int id, int n) { asm volatile("bar.arrive %0,%1;" ::"r"(id), "r"(n) : "memory"); }
#define WG_FENCE() asm volatile("wgmma.fence.sync.aligned;" ::: "memory")
#define WG_COMMIT() asm volatile("wgmma.commit_group.sync.aligned;" ::: "memory")
#define WG_WAIT(n) asm volatile("wgmma.wait_group.sync.aligned " #n ";" ::: "memory")
template <int N> __device__ __forceinline__ void fence_regs(float* r) {
#pragma unroll
  for (int i = 0; i < N; i++) asm volatile("" : "+f"(r[i])::"memory");
}
#define REG_INC(n) asm volatile("setmaxnreg.inc.sync.aligned.u32 " #n ";")
#define REG_DEC(n) asm volatile("setmaxnreg.dec.sync.aligned.u32 " #n ";")
__device__ __forceinline__ uint64_t mkdesc(uint32_t addr, uint32_t lbo, uint32_t sbo, int sw) {
  return (uint64_t)((addr & 0x3FFFF) >> 4) | ((uint64_t)(lbo >> 4) << 16) | ((uint64_t)(sbo >> 4) << 32) | ((uint64_t)sw << 62);
}
__device__ __forceinline__ void ldsm4(uint32_t* r, uint32_t addr) {
  asm volatile("ldmatrix.sync.aligned.m8n8.x4.shared.b16 {%0,%1,%2,%3},[%4];" : "=r"(r[0]), "=r"(r[1]), "=r"(r[2]), "=r"(r[3]) : "r"(addr) : "memory");
}
__device__ __forceinline__ void stsm4(uint32_t addr, uint32_t r0, uint32_t r1, uint32_t r2, uint32_t r3) {
  asm volatile("stmatrix.sync.aligned.m8n8.x4.shared.b16 [%0],{%1,%2,%3,%4};" ::"r"(addr), "r"(r0), "r"(r1), "r"(r2), "r"(r3) : "memory");
}
__device__ __forceinline__ uint32_t pack_bf16(float lo, float hi) {
  uint32_t r;
  asm("cvt.rn.bf16x2.f32 %0,%1,%2;" : "=r"(r) : "f"(hi), "f"(lo));
  return r;
}
__device__ __forceinline__ float bf_lo(uint32_t v) { return __uint_as_float(v << 16); }
__device__ __forceinline__ float bf_hi(uint32_t v) { return __uint_as_float(v & 0xFFFF0000u); }
__device__ __forceinline__ float rbf(float x) { return __bfloat162float(__float2bfloat16_rn(x)); }
__device__ __forceinline__ uint32_t hfma2(uint32_t a, uint32_t b, uint32_t c) {
  uint32_t r;
  asm("fma.rn.bf16x2 %0,%1,%2,%3;" : "=r"(r) : "r"(a), "r"(b), "r"(c));
  return r;
}
__device__ __forceinline__ uint32_t hadd2(uint32_t a, uint32_t b) {
  uint32_t r;
  asm("add.rn.bf16x2 %0,%1,%2;" : "=r"(r) : "r"(a), "r"(b));
  return r;
}
__device__ __forceinline__ uint32_t hmul2(uint32_t a, uint32_t b) {
  uint32_t r;
  asm("mul.rn.bf16x2 %0,%1,%2;" : "=r"(r) : "r"(a), "r"(b));
  return r;
}
__device__ __forceinline__ uint32_t hneg2(uint32_t a) {
  uint32_t r;
  asm("neg.bf16x2 %0,%1;" : "=r"(r) : "r"(a));
  return r;
}
__device__ __forceinline__ float ex2f(float x) {
  float r;
  asm("ex2.approx.ftz.f32 %0,%1;" : "=f"(r) : "f"(x));
  return r;
}
__device__ __forceinline__ float sqrt_fast(float x) {
  float r;
  asm("sqrt.approx.f32 %0,%1;" : "=f"(r) : "f"(x));
  return r;
}
__device__ __forceinline__ float rcp_fast(float x) {
  float r;
  asm("rcp.approx.f32 %0,%1;" : "=f"(r) : "f"(x));
  return r;
}
__device__ __forceinline__ float tanhf_fast(float x) {
  float r;
  asm("tanh.approx.f32 %0,%1;" : "=f"(r) : "f"(x));
  return r;
}
__device__ __forceinline__ uint4 ln_consts(float mean, float var) {
  float m = rbf(mean), v = rbf(var);
  float s = rbf(sqrtf(rbf(v + 1e-5f)));
  float r = 1.0f / s;
  float rh = rbf(r), rl = r - rh;
  return make_uint4(pack_bf16(-m, -m), pack_bf16(rh, rh), pack_bf16(rl, rl), 0u);
}
__device__ __forceinline__ uint32_t ln_apply(uint32_t x, const uint4& st, uint32_t a, uint32_t s) {
  uint32_t d = hadd2(x, st.x);
  uint32_t n = hfma2(d, st.y, hmul2(d, st.z));
  return hfma2(n, a, s);
}

__device__ __forceinline__ void wg_ss_n72_t1(float* d, uint64_t da, uint64_t db, int sc) {
  asm volatile("{.reg .pred p; setp.ne.b32 p,%38,0; wgmma.mma_async.sync.aligned.m64n72k16.f32.bf16.bf16 {%0,%1,%2,%3,%4,%5,%6,%7,%8,%9,%10,%11,%12,%13,%14,%15,%16,%17,%18,%19,%20,%21,%22,%23,%24,%25,%26,%27,%28,%29,%30,%31,%32,%33,%34,%35}, %36, %37, p,1,1,0,1;}"
  : "+f"(d[0]),"+f"(d[1]),"+f"(d[2]),"+f"(d[3]),"+f"(d[4]),"+f"(d[5]),"+f"(d[6]),"+f"(d[7]),"+f"(d[8]),"+f"(d[9]),"+f"(d[10]),"+f"(d[11]),"+f"(d[12]),"+f"(d[13]),"+f"(d[14]),"+f"(d[15]),"+f"(d[16]),"+f"(d[17]),"+f"(d[18]),"+f"(d[19]),"+f"(d[20]),"+f"(d[21]),"+f"(d[22]),"+f"(d[23]),"+f"(d[24]),"+f"(d[25]),"+f"(d[26]),"+f"(d[27]),"+f"(d[28]),"+f"(d[29]),"+f"(d[30]),"+f"(d[31]),"+f"(d[32]),"+f"(d[33]),"+f"(d[34]),"+f"(d[35]) : "l"(da),"l"(db),"r"(sc));
}
template <int SC> __device__ __forceinline__ void wl_rs_n128_t1(float* d, const uint32_t* a, uint64_t e) {
  asm volatile("wgmma.mma_async.sync.aligned.m64n128k16.f32.bf16.bf16 {%0,%1,%2,%3,%4,%5,%6,%7,%8,%9,%10,%11,%12,%13,%14,%15,%16,%17,%18,%19,%20,%21,%22,%23,%24,%25,%26,%27,%28,%29,%30,%31,%32,%33,%34,%35,%36,%37,%38,%39,%40,%41,%42,%43,%44,%45,%46,%47,%48,%49,%50,%51,%52,%53,%54,%55,%56,%57,%58,%59,%60,%61,%62,%63}, {%64,%65,%66,%67}, %68, %69,1,1,1;"
  : "+f"(d[0]),"+f"(d[1]),"+f"(d[2]),"+f"(d[3]),"+f"(d[4]),"+f"(d[5]),"+f"(d[6]),"+f"(d[7]),"+f"(d[8]),"+f"(d[9]),"+f"(d[10]),"+f"(d[11]),"+f"(d[12]),"+f"(d[13]),"+f"(d[14]),"+f"(d[15]),"+f"(d[16]),"+f"(d[17]),"+f"(d[18]),"+f"(d[19]),"+f"(d[20]),"+f"(d[21]),"+f"(d[22]),"+f"(d[23]),"+f"(d[24]),"+f"(d[25]),"+f"(d[26]),"+f"(d[27]),"+f"(d[28]),"+f"(d[29]),"+f"(d[30]),"+f"(d[31]),"+f"(d[32]),"+f"(d[33]),"+f"(d[34]),"+f"(d[35]),"+f"(d[36]),"+f"(d[37]),"+f"(d[38]),"+f"(d[39]),"+f"(d[40]),"+f"(d[41]),"+f"(d[42]),"+f"(d[43]),"+f"(d[44]),"+f"(d[45]),"+f"(d[46]),"+f"(d[47]),"+f"(d[48]),"+f"(d[49]),"+f"(d[50]),"+f"(d[51]),"+f"(d[52]),"+f"(d[53]),"+f"(d[54]),"+f"(d[55]),"+f"(d[56]),"+f"(d[57]),"+f"(d[58]),"+f"(d[59]),"+f"(d[60]),"+f"(d[61]),"+f"(d[62]),"+f"(d[63]) : "r"(a[0]),"r"(a[1]),"r"(a[2]),"r"(a[3]),"l"(e),"n"(SC));
}
template <int SC> __device__ __forceinline__ void wl_rs_n24_t1(float* d, const uint32_t* a, uint64_t e) {
  asm volatile("wgmma.mma_async.sync.aligned.m64n24k16.f32.bf16.bf16 {%0,%1,%2,%3,%4,%5,%6,%7,%8,%9,%10,%11}, {%12,%13,%14,%15}, %16, %17,1,1,1;"
  : "+f"(d[0]),"+f"(d[1]),"+f"(d[2]),"+f"(d[3]),"+f"(d[4]),"+f"(d[5]),"+f"(d[6]),"+f"(d[7]),"+f"(d[8]),"+f"(d[9]),"+f"(d[10]),"+f"(d[11]) : "r"(a[0]),"r"(a[1]),"r"(a[2]),"r"(a[3]),"l"(e),"n"(SC));
}
template <int SC> __device__ __forceinline__ void wl_rs_n64_t0(float* d, const uint32_t* a, uint64_t e) {
  asm volatile("wgmma.mma_async.sync.aligned.m64n64k16.f32.bf16.bf16 {%0,%1,%2,%3,%4,%5,%6,%7,%8,%9,%10,%11,%12,%13,%14,%15,%16,%17,%18,%19,%20,%21,%22,%23,%24,%25,%26,%27,%28,%29,%30,%31}, {%32,%33,%34,%35}, %36, %37,1,1,0;"
  : "+f"(d[0]),"+f"(d[1]),"+f"(d[2]),"+f"(d[3]),"+f"(d[4]),"+f"(d[5]),"+f"(d[6]),"+f"(d[7]),"+f"(d[8]),"+f"(d[9]),"+f"(d[10]),"+f"(d[11]),"+f"(d[12]),"+f"(d[13]),"+f"(d[14]),"+f"(d[15]),"+f"(d[16]),"+f"(d[17]),"+f"(d[18]),"+f"(d[19]),"+f"(d[20]),"+f"(d[21]),"+f"(d[22]),"+f"(d[23]),"+f"(d[24]),"+f"(d[25]),"+f"(d[26]),"+f"(d[27]),"+f"(d[28]),"+f"(d[29]),"+f"(d[30]),"+f"(d[31]) : "r"(a[0]),"r"(a[1]),"r"(a[2]),"r"(a[3]),"l"(e),"n"(SC));
}
template <int SC> __device__ __forceinline__ void wl_rs_n64_t1(float* d, const uint32_t* a, uint64_t e) {
  asm volatile("wgmma.mma_async.sync.aligned.m64n64k16.f32.bf16.bf16 {%0,%1,%2,%3,%4,%5,%6,%7,%8,%9,%10,%11,%12,%13,%14,%15,%16,%17,%18,%19,%20,%21,%22,%23,%24,%25,%26,%27,%28,%29,%30,%31}, {%32,%33,%34,%35}, %36, %37,1,1,1;"
  : "+f"(d[0]),"+f"(d[1]),"+f"(d[2]),"+f"(d[3]),"+f"(d[4]),"+f"(d[5]),"+f"(d[6]),"+f"(d[7]),"+f"(d[8]),"+f"(d[9]),"+f"(d[10]),"+f"(d[11]),"+f"(d[12]),"+f"(d[13]),"+f"(d[14]),"+f"(d[15]),"+f"(d[16]),"+f"(d[17]),"+f"(d[18]),"+f"(d[19]),"+f"(d[20]),"+f"(d[21]),"+f"(d[22]),"+f"(d[23]),"+f"(d[24]),"+f"(d[25]),"+f"(d[26]),"+f"(d[27]),"+f"(d[28]),"+f"(d[29]),"+f"(d[30]),"+f"(d[31]) : "r"(a[0]),"r"(a[1]),"r"(a[2]),"r"(a[3]),"l"(e),"n"(SC));
}
template <int SC> __device__ __forceinline__ void wl_rs_n88_t1(float* d, const uint32_t* a, uint64_t e) {
  asm volatile("wgmma.mma_async.sync.aligned.m64n88k16.f32.bf16.bf16 {%0,%1,%2,%3,%4,%5,%6,%7,%8,%9,%10,%11,%12,%13,%14,%15,%16,%17,%18,%19,%20,%21,%22,%23,%24,%25,%26,%27,%28,%29,%30,%31,%32,%33,%34,%35,%36,%37,%38,%39,%40,%41,%42,%43}, {%44,%45,%46,%47}, %48, %49,1,1,1;"
  : "+f"(d[0]),"+f"(d[1]),"+f"(d[2]),"+f"(d[3]),"+f"(d[4]),"+f"(d[5]),"+f"(d[6]),"+f"(d[7]),"+f"(d[8]),"+f"(d[9]),"+f"(d[10]),"+f"(d[11]),"+f"(d[12]),"+f"(d[13]),"+f"(d[14]),"+f"(d[15]),"+f"(d[16]),"+f"(d[17]),"+f"(d[18]),"+f"(d[19]),"+f"(d[20]),"+f"(d[21]),"+f"(d[22]),"+f"(d[23]),"+f"(d[24]),"+f"(d[25]),"+f"(d[26]),"+f"(d[27]),"+f"(d[28]),"+f"(d[29]),"+f"(d[30]),"+f"(d[31]),"+f"(d[32]),"+f"(d[33]),"+f"(d[34]),"+f"(d[35]),"+f"(d[36]),"+f"(d[37]),"+f"(d[38]),"+f"(d[39]),"+f"(d[40]),"+f"(d[41]),"+f"(d[42]),"+f"(d[43]) : "r"(a[0]),"r"(a[1]),"r"(a[2]),"r"(a[3]),"l"(e),"n"(SC));
}

#define POLY_MASK 0xB5u
#define QSCALE (0.23570226039551584f * 1.4426950408889634f)

__device__ __forceinline__ void pf_l2(const void* p) { asm volatile("prefetch.global.L2 [%0];" ::"l"(p)); }
__global__ void __launch_bounds__(256) k0_kernel(const __nv_bfloat16* __restrict__ x, const __nv_bfloat16* __restrict__ c,
                                                 const __nv_bfloat16* __restrict__ wmod) {
  if (threadIdx.x == 0) TS(0, 0);
  pdl_launch();
  const int tid = threadIdx.x, lane = tid & 31, warp = tid >> 5;
  if (blockIdx.x < 108) {
    __shared__ float red[8][32];
    const int col0 = blockIdx.x * 32 + (tid & 3) * 8, r0 = tid >> 2;
    uint4 w[9];
#pragma unroll
    for (int i = 0; i < 9; i++) w[i] = __ldg((const uint4*)(wmod + (size_t)(r0 + 64 * i) * 3456 + col0));
    float acc[8] = {0, 0, 0, 0, 0, 0, 0, 0};
#pragma unroll
    for (int i = 0; i < 9; i++) {
      float cv = __bfloat162float(c[r0 + 64 * i]);
      float sv = rbf(cv / (1.0f + __expf(-cv)));
      acc[0] += sv * bf_lo(w[i].x); acc[1] += sv * bf_hi(w[i].x);
      acc[2] += sv * bf_lo(w[i].y); acc[3] += sv * bf_hi(w[i].y);
      acc[4] += sv * bf_lo(w[i].z); acc[5] += sv * bf_hi(w[i].z);
      acc[6] += sv * bf_lo(w[i].w); acc[7] += sv * bf_hi(w[i].w);
    }
#pragma unroll
    for (int j = 0; j < 8; j++) {
      acc[j] += __shfl_xor_sync(~0u, acc[j], 4);
      acc[j] += __shfl_xor_sync(~0u, acc[j], 8);
      acc[j] += __shfl_xor_sync(~0u, acc[j], 16);
    }
    if (lane < 4) {
#pragma unroll
      for (int j = 0; j < 8; j++) red[warp][lane * 8 + j] = acc[j];
    }
    __syncthreads();
    if (tid < 32) {
      float s = 0;
#pragma unroll
      for (int j = 0; j < 8; j++) s += red[j][tid];
      s = rbf(s);
      int n = blockIdx.x * 32 + tid, part = n / DM, col = n % DM;
      if (part == 2) g_ga[col] = s;
      else if (part == 5) g_gb[col] = __float2bfloat16_rn(s);
      else {
        __nv_bfloat16* tab = (__nv_bfloat16*)(part < 2 ? g_tab1 : g_tab2);
        bool shift = (part == 0 || part == 3);
        int kk = col >> 4, half = (col >> 3) & 1, cq = (col & 7) >> 1, e = col & 1;
        tab[((kk * 4 + cq) * 4 + half * 2 + (shift ? 1 : 0)) * 2 + e] = __float2bfloat16_rn(rbf(shift ? s : 1.0f + s) * (part < 2 ? 1.0f : 0.5f));
      }
    }
    if (blockIdx.x == 0 && tid >= 64 && tid < 64 + 80) g_cnt[tid - 64] = 0;
  } else {
    const int row0 = (blockIdx.x - 108) * 16 + warp * 2;
    uint32_t v[2][9];
#pragma unroll
    for (int r = 0; r < 2; r++)
#pragma unroll
      for (int i = 0; i < 9; i++) v[r][i] = __ldg((const uint32_t*)(x + (size_t)(row0 + r) * DM) + lane + 32 * i);
#pragma unroll
    for (int r = 0; r < 2; r++) {
      float s = 0;
#pragma unroll
      for (int i = 0; i < 9; i++) s += bf_lo(v[r][i]) + bf_hi(v[r][i]);
#pragma unroll
      for (int o = 16; o; o >>= 1) s += __shfl_xor_sync(~0u, s, o);
      float mean = s * (1.0f / DM), q = 0;
#pragma unroll
      for (int i = 0; i < 9; i++) {
        float a = bf_lo(v[r][i]) - mean, b = bf_hi(v[r][i]) - mean;
        q += a * a + b * b;
      }
#pragma unroll
      for (int o = 16; o; o >>= 1) q += __shfl_xor_sync(~0u, q, o);
      if (lane == 0) g_stat1[row0 + r] = ln_consts(mean, q * (1.0f / DM));
    }
  }
  if (threadIdx.x == 0) TS(0, 1);
}

#define NSTG 6
#define STG_BYTES 16384
#define R_BYTES (8 * 16384)
#define GEMM_SMEM (R_BYTES + NSTG * STG_BYTES + 3072)

__device__ __forceinline__ void load_a_chunk(uint32_t (*a)[4], uint32_t chunk_base, int row_in_tile, int lane) {
  const int r = row_in_tile + (lane & 7) + ((lane >> 3) & 1) * 8;
  const uint32_t rb = chunk_base + r * 128;
#pragma unroll
  for (int k = 0; k < 4; k++) ldsm4(a[k], rb + (((k * 2 + (lane >> 4)) ^ (r & 7)) << 4));
}

#define MMA_TILE(FN, ODD, pj)                                                   \
  {                                                                             \
    uint32_t rb_ = RING >> 4;                                                   \
    asm volatile("" : "+r"(rb_));                                               \
    const uint64_t db = mkdesc(0, 8192, 1024, 1) + (uint32_t)__shfl_sync(~0u, rb_, 0); \
    _Pragma("unroll") for (int s = 0; s < 9; s++) {                             \
      const int g_ = 1 + (ODD) * 9 + s, st_ = g_ % NSTG;                        \
      mbar_wait(full + st_ * 8, (pj) ^ ((g_ / NSTG) & 1));                      \
      WG_FENCE();                                                               \
      if (s == 0) FN<0>(acc, a[0], db + st_ * 1024); else FN<1>(acc, a[s * 4], db + st_ * 1024); \
      _Pragma("unroll") for (int k = 1; k < 4; k++) FN<1>(acc, a[s * 4 + k], db + st_ * 1024 + k * 128); \
      WG_COMMIT();                                                              \
      if (s > 0) { WG_WAIT(1); if (lane == 0) mbar_arrive(empty + ((g_ - 1) % NSTG) * 8); } \
    }                                                                           \
    WG_WAIT(0);                                                                 \
    if (lane == 0) mbar_arrive(empty + ((9 + (ODD) * 9) % NSTG) * 8);           \
  }

template <int NG, int G0>
__device__ __forceinline__ void qkv_stage(const float* acc, uint32_t stg, int rowl, int cq, int col_base) {
  const float vs0 = ((POLY_MASK >> ((rowl >> 3) & 7)) & 1) ? 0.5f : 1.0f, vs1 = ((POLY_MASK >> (((rowl >> 3) + 1) & 7)) & 1) ? 0.5f : 1.0f;
#pragma unroll
  for (int i = 0; i < NG; i++) {
    const int cc = (G0 + i) * 8 + cq * 2;
    const int slot = (cc * 3641) >> 16, d = cc - slot * 18;
    const int gc = col_base + cc;
    const float sc0 = gc < DM ? QSCALE : (gc < 2 * DM ? vs0 : 1.0f), sc1 = gc < DM ? QSCALE : (gc < 2 * DM ? vs1 : 1.0f);
    const uint32_t ad = stg + slot * 6144 + (d >> 3) * 128 + (d & 7) * 2 + (rowl >> 3) * 384 + (rowl & 7) * 16;
    asm volatile("st.shared.b32 [%0],%1;" ::"r"(ad), "r"(pack_bf16(acc[4 * i] * sc0, acc[4 * i + 1] * sc0)) : "memory");
    asm volatile("st.shared.b32 [%0],%1;" ::"r"(ad + 384), "r"(pack_bf16(acc[4 * i + 2] * sc1, acc[4 * i + 3] * sc1)) : "memory");
  }
}

__global__ void __launch_bounds__(384, 1) k1_kernel(const __grid_constant__ CUtensorMap mx, const __grid_constant__ CUtensorMap mw) {
  extern __shared__ __align__(1024) uint8_t smem_raw[];
  const uint32_t sb = (s2u(smem_raw) + 1023) & ~1023u;
  const uint32_t R = sb, RING = sb + R_BYTES, BAR = RING + NSTG * STG_BYTES;
  const uint32_t full = BAR, empty = BAR + 64, xfull = BAR + 128;
  const int tid = threadIdx.x, lane = tid & 31, warp = tid >> 5;
  const int mb = blockIdx.x >> 3, nb = blockIdx.x & 7;
  if (tid == 0) {
    TS(1, 0);
    for (int i = 0; i < NSTG; i++) { mbar_init(full + i * 8, 1); mbar_init(empty + i * 8, 8); }
    for (int i = 0; i < 8; i++) mbar_init(xfull + i * 8, 1);
    fence_bar_init();
  }
  __syncthreads();
  pdl_launch();
  if (warp >= 8) {
    REG_DEC(24);
    if (warp == 8) {
      if (lane == 0) {
        for (int c = 0; c < 8; c++) { mbar_expect(xfull + c * 8, 16384); tma2d(R + c * 16384, &mx, c * 64, mb * 128, xfull + c * 8); }
        mbar_expect(full, 16384);
        tma2d(RING, &mx, 512, mb * 128, full);
        int st = 1; uint32_t ph = 0;
        for (int it = 0; it < 18; it++) {
          const int t = it / 9, s = it - t * 9;
          mbar_wait(empty + st * 8, ph ^ 1);
          mbar_expect(full + st * 8, 16384);
          tma2d(RING + st * STG_BYTES, &mw, nb * 216 + t * 128, s * 64, full + st * 8);
          tma2d(RING + st * STG_BYTES + 8192, &mw, nb * 216 + t * 128 + 64, s * 64, full + st * 8);
          if (++st == NSTG) { st = 0; ph ^= 1; }
        }
      }
      pdl_wait();
    } else {
      const int ht = tid - 288;
      bar_sync(1, 352);
      for (int i = ht; i < 12 * 128; i += 96) {
        const int slot = i >> 7, row = i & 127, type = (nb * 12 + slot) >> 5;
        uint32_t v = 0;
        if (type == 1) v = ((POLY_MASK >> ((row >> 3) & 7)) & 1) ? 0x43403F00u : 0x40253F80u;
        if (type == 2) v = 0x3F80u;
        const uint32_t ad = R + slot * 6144 + (row >> 3) * 384 + 256 + (row & 7) * 16;
        asm volatile("st.shared.b32 [%0],%1;" ::"r"(ad + 4), "r"(v) : "memory");
        asm volatile("st.shared.v2.b32 [%0],{%1,%1};" ::"r"(ad + 8), "r"(0) : "memory");
      }
      fence_async_smem();
      pdl_wait();
#pragma unroll 1
      for (int t = 0; t < 2; t++) {
        bar_sync(2 + t, 352);
        const int s0 = t ? 7 : 0, s1 = t ? 12 : 7;
        if (ht == 0) {
          for (int s = s0; s < s1; s++) bulk_s2g(g_qkv + (size_t)(nb * 12 + s) * 98304 + mb * 6144, R + s * 6144, 6144);
          bulk_commit();
        }
        for (int s = s0 + (warp - 9); s < s1; s += 3) {
          const int gs = nb * 12 + s;
          if ((gs >> 5) != 1) continue;
          float mx2 = 0;
#pragma unroll 1
          for (int row = lane; row < 128; row += 32) {
            const uint32_t ad = R + s * 6144 + (row >> 3) * 384 + (row & 7) * 16;
            float q = 0;
#pragma unroll 1
            for (int ch = 0; ch < 3; ch++) {
              uint32_t u0, u1, u2, u3;
              asm volatile("ld.shared.v4.b32 {%0,%1,%2,%3},[%4];" : "=r"(u0), "=r"(u1), "=r"(u2), "=r"(u3) : "r"(ad + ch * 128));
              if (ch == 2) u1 = 0;
              q += bf_lo(u0) * bf_lo(u0) + bf_hi(u0) * bf_hi(u0) + bf_lo(u1) * bf_lo(u1) + bf_hi(u1) * bf_hi(u1);
              q += bf_lo(u2) * bf_lo(u2) + bf_hi(u2) * bf_hi(u2) + bf_lo(u3) * bf_lo(u3) + bf_hi(u3) * bf_hi(u3);
            }
            if ((POLY_MASK >> ((row >> 3) & 7)) & 1) q *= 4.0f;
            mx2 = (q > mx2 || q != q) ? q : mx2;
            if (mx2 != mx2) mx2 = __int_as_float(0x7f800000);
          }
#pragma unroll
          for (int o = 16; o; o >>= 1) mx2 = fmaxf(mx2, __shfl_xor_sync(~0u, mx2, o));
          if (lane == 0) g_kmax[(gs & 31) * 16 + mb] = mx2;
        }
      }
      if (ht == 0) bulk_wait0();
      if (ht == 0) TS(1, 8);
    }
  } else {
    REG_INC(240);
    uint32_t a[36][4];
    const int rowl = warp * 16;
#pragma unroll
    for (int c = 0; c < 8; c++) { mbar_wait(xfull + c * 8, 0); load_a_chunk(&a[c * 4], R + c * 16384, rowl, lane); }
    mbar_wait(full, 0);
    load_a_chunk(&a[32], RING, rowl, lane);
    __syncwarp();
    if (lane == 0) mbar_arrive(empty);
    bar_arrive(1, 352);
    if (tid == 0) TS(1, 1);
    pdl_wait();
    if (tid == 0) TS(1, 2);
    {
      const int g = lane >> 2, cq = lane & 3;
      const uint4 s0 = g_stat1[mb * 128 + rowl + g], s1 = g_stat1[mb * 128 + rowl + g + 8];
#pragma unroll
      for (int k = 0; k < 36; k++) {
        if ((k & 3) == 0) asm volatile("" ::: "memory");
        const uint4 t = g_tab1[k * 4 + cq];
        a[k][0] = ln_apply(a[k][0], s0, t.x, t.y);
        a[k][1] = ln_apply(a[k][1], s1, t.x, t.y);
        a[k][2] = ln_apply(a[k][2], s0, t.z, t.w);
        a[k][3] = ln_apply(a[k][3], s1, t.z, t.w);
      }
    }
    bar_sync(4, 256);
    float acc[64];
    if (tid == 0) TS(1, 3);
    MMA_TILE(wl_rs_n128_t1, 0, 0);
    if (tid == 0) TS(1, 4);
    qkv_stage<16, 0>(acc, R, rowl + (lane >> 2), lane & 3, nb * 216);
    fence_async_smem();
    bar_arrive(2, 352);
    if (tid == 0) TS(1, 5);
    MMA_TILE(wl_rs_n88_t1, 1, 0);
    if (tid == 0) TS(1, 6);
    qkv_stage<11, 16>(acc, R, rowl + (lane >> 2), lane & 3, nb * 216);
    fence_async_smem();
    bar_arrive(3, 352);
    if (tid == 0) TS(1, 7);
  }
}

#define ATT_SMEM (2 * 98304 + 1024 + 256)

__device__ __forceinline__ uint32_t exp2_pair_fma(float t0, float t1) {
  uint32_t y;
  asm("prmt.b32 %0,%1,%2,0x6521;" : "=r"(y) : "r"(__float_as_uint(t0)), "r"(__float_as_uint(t1)));
  return hfma2(y, y | 0x3F803F80u, y | 0x007F007Fu);
}

__device__ __forceinline__ void softmax_fast(const float* s, uint32_t* p) {
#pragma unroll
  for (int i = 0; i < 8; i++) {
    if ((POLY_MASK >> i) & 1) {
      p[2 * i] = exp2_pair_fma(s[4 * i], s[4 * i + 1]);
      p[2 * i + 1] = exp2_pair_fma(s[4 * i + 2], s[4 * i + 3]);
    } else {
      p[2 * i] = pack_bf16(ex2f(s[4 * i]), ex2f(s[4 * i + 1]));
      p[2 * i + 1] = pack_bf16(ex2f(s[4 * i + 2]), ex2f(s[4 * i + 3]));
    }
  }
}
#define QK_MMA(S, kd)                                                           \
  wl_rs_n64_t0<0>(S, q, (kd));                                                  \
  wl_rs_n64_t0<1>(S, q + 4, (kd) + 16 - (8ull << 16));
#define PV_MMA(P, vd)                                                           \
  _Pragma("unroll") for (int t = 0; t < 4; t++) wl_rs_n24_t1<1>(o, P + 4 * t, (vd) + t * 48);

__device__ __forceinline__ float sq2(uint32_t v) { return bf_lo(v) * bf_lo(v) + bf_hi(v) * bf_hi(v); }
__device__ __forceinline__ void att_store(const float* o, int row0, int head, int lane) {
  const int cq = lane & 3;
  const float l0 = __shfl_sync(~0u, o[8], (lane & ~3) | 1), l1 = __shfl_sync(~0u, o[10], (lane & ~3) | 1);
  const float i0 = rcp_fast(l0), i1 = rcp_fast(l1);
  uint32_t* og = (uint32_t*)(g_o + (size_t)row0 * DM + head * 18 + cq * 2);
  og[0] = pack_bf16(o[0] * i0, o[1] * i0);
  og[4] = pack_bf16(o[4] * i0, o[5] * i0);
  og[8 * DM / 2] = pack_bf16(o[2] * i1, o[3] * i1);
  og[8 * DM / 2 + 4] = pack_bf16(o[6] * i1, o[7] * i1);
  if (cq == 0) {
    og[8] = pack_bf16(o[8] * i0, o[9] * i0);
    og[8 * DM / 2 + 8] = pack_bf16(o[10] * i1, o[11] * i1);
  }
}

__global__ void __launch_bounds__(512, 1) k2_kernel(const uint8_t* __restrict__ wo, const uint8_t* __restrict__ wg_, const uint8_t* __restrict__ wu,
                                                    const uint8_t* __restrict__ wd) {
  extern __shared__ __align__(1024) uint8_t smem_raw[];
  const uint32_t sb = (s2u(smem_raw) + 1023) & ~1023u;
  const uint32_t KS = sb, VS = sb + 98304, BAR = sb + 2 * 98304;
  const int tid = threadIdx.x, lane = tid & 31, warp = tid >> 5, wg = tid >> 7;
  const int head = blockIdx.x >> 2, qb = blockIdx.x & 3;
  if (tid == 0) {
    TS(2, 0);
    for (int i = 0; i < 16; i++) mbar_init(BAR + i * 8, 1);
    fence_bar_init();
  }
  __syncthreads();
  const int g = lane >> 2, cq = lane & 3;
  const int row0 = qb * 512 + wg * 128 + (warp & 3) * 16 + g;
  const uint8_t* qg = g_qkv + (size_t)head * 98304 + (row0 >> 3) * 384 + (row0 & 7) * 16 + cq * 4;
  pdl_wait();
  pdl_launch();
  if (tid == 0) TS(2, 1);
  const uint8_t* kg = g_qkv + (size_t)(32 + head) * 98304;
#define KV_LOAD(c) { mbar_expect(BAR + (c) * 8, 12288); bulk_g2s(KS + (c) * 6144, kg + (c) * 6144, 6144, BAR + (c) * 8); \
                     bulk_g2s(VS + (c) * 6144, kg + 32 * 98304 + (c) * 6144, 6144, BAR + (c) * 8); }
  if (lane == 0 && warp < 5) KV_LOAD(warp);
  __syncwarp();
  uint32_t q[8], q2[6];
  float kmax2 = __ldcg(g_kmax + head * 16 + (lane & 15));
#pragma unroll
  for (int i = 0; i < 6; i++) {
    q[i] = __ldcg((const uint32_t*)(qg + (i & 1) * 384 + (i >> 1) * 128));
    q2[i] = __ldcg((const uint32_t*)(qg + 3072 + (i & 1) * 384 + (i >> 1) * 128));
  }
  q[6] = __ldcg((const uint32_t*)(qg + 256 + 12 - cq * 4)); q[7] = __ldcg((const uint32_t*)(qg + 256 + 8 - cq * 4));
  const uint64_t dk = mkdesc(KS, 128, 384, 0), dv = mkdesc(VS, 384, 128, 0);
#pragma unroll
  for (int o = 8; o; o >>= 1) kmax2 = fmaxf(kmax2, __shfl_xor_sync(~0u, kmax2, o));
  float bd[4] = {sq2(q[0]) + sq2(q[2]) + sq2(q[4]), sq2(q[1]) + sq2(q[3]) + sq2(q[5]),
                 sq2(q2[0]) + sq2(q2[2]) + sq2(q2[4]), sq2(q2[1]) + sq2(q2[3]) + sq2(q2[5])};
  int ok = 1;
  if (tid == 0 && bd[0] + bd[3] + kmax2 != 1.2345f) TS(2, 5);
#pragma unroll
  for (int i = 0; i < 4; i++) {
    bd[i] += __shfl_xor_sync(~0u, bd[i], 1); bd[i] += __shfl_xor_sync(~0u, bd[i], 2);
    bd[i] = sqrt_fast(bd[i] * kmax2) * 1.01f + 1.0f;
    ok = ok && (bd[i] <= 62.0f);
  }
  {
    uint32_t all;
    asm volatile("{.reg .pred p,q; setp.ne.b32 p,%1,0; barrier.red.and.pred q,1,512,p; selp.u32 %0,1,0,q;}"
                 : "=r"(all) : "r"(ok) : "memory");
    ok = __all_sync(~0u, all);
  }
  float o[12];
#pragma unroll
  for (int i = 0; i < 12; i++) { o[i] = 0.f; asm volatile("" : "+f"(o[i])); }
  float s[32];
  uint32_t p[16];
  if (tid == 0) TS(2, 2);
  if (ok) {
    if (cq == 1) {
      q[4] = pack_bf16(-bd[0], 1.0f); q[5] = pack_bf16(-bd[1], 1.0f);
      q2[4] = pack_bf16(-bd[2], 1.0f); q2[5] = pack_bf16(-bd[3], 1.0f);
    }
    mbar_wait(BAR, 0);
    WG_FENCE();
    QK_MMA(s, dk);
    WG_COMMIT();
#pragma unroll 1
    for (int tile = 0; tile < 2; tile++) {
#pragma unroll 1
      for (int jj = 0; jj < 8; jj++) {
        const uint64_t kd = dk + (uint32_t)(jj * 768), vd = dv + (uint32_t)(jj * 768), kn = dk + (uint32_t)(((jj + 1) & 7) * 768);
        if (tile == 0) {
          if (lane == 0 && warp < 2 && 2 * jj + 5 + warp < 16) KV_LOAD(2 * jj + 5 + warp);
          if (lane == 0 && warp >= 4 && warp < 8) {
            const uint8_t* w = warp == 4 ? wg_ : warp == 5 ? wu : warp == 6 ? wd : wo;
            const uint32_t n = warp == 7 ? 656 : 5184, o_ = (blockIdx.x * 8 + jj) * n;
            if (warp < 7 || o_ + n <= DM * DM * 2) asm volatile("cp.async.bulk.prefetch.L2.global [%0],%1;" ::"l"(w + o_), "r"(n) : "memory");
          }
          __syncwarp();
          mbar_wait(BAR + jj * 16 + 8, 0); mbar_wait(BAR + ((jj * 16 + 16) & 127), 0); if (tid == 0) TS(2, 8 + jj); }
#pragma unroll
        for (int u = 0; u < 4; u++) {
          WG_WAIT(0);
          fence_regs<32>(s);
          softmax_fast(s, p);
          if (u == 3 && jj == 7) {
#pragma unroll
            for (int i = 0; i < 6; i++) q[i] = q2[i];
          }
          WG_FENCE();
          PV_MMA(p, vd + u * 192);
          QK_MMA(s, u < 3 ? kd + u * 192 + 192 : kn);
          WG_COMMIT();
        }
      }
      WG_WAIT(0);
      fence_regs<12>(o);
      att_store(o, row0 + tile * 64, head, lane);
#pragma unroll
      for (int i = 0; i < 12; i++) o[i] = 0.f;
      fence_regs<12>(o);
      if (tid == 0 && tile == 0) TS(2, 3);
    }
  } else {
    if (lane == 0 && warp >= 5) KV_LOAD(warp);
    __syncwarp();
#pragma unroll 1
    for (int tile = 0; tile < 2; tile++) {
      float m0 = -INFINITY, m1 = -INFINITY;
#pragma unroll 1
      for (int j = 0; j < 32; j++) {
        mbar_wait(BAR + (j >> 1) * 8, 0);
        WG_FENCE();
        QK_MMA(s, dk + (uint32_t)(j * 192));
        WG_COMMIT();
        WG_WAIT(0);
        fence_regs<32>(s);
#pragma unroll
        for (int i = 0; i < 32; i++) if ((POLY_MASK >> (i >> 2)) & 1) s[i] *= 2.0f;
        float x0 = m0, x1 = m1;
#pragma unroll
        for (int i = 0; i < 8; i++) {
          x0 = fmaxf(x0, fmaxf(s[4 * i], s[4 * i + 1]));
          x1 = fmaxf(x1, fmaxf(s[4 * i + 2], s[4 * i + 3]));
        }
        x0 = fmaxf(x0, __shfl_xor_sync(~0u, x0, 1)); x0 = fmaxf(x0, __shfl_xor_sync(~0u, x0, 2));
        x1 = fmaxf(x1, __shfl_xor_sync(~0u, x1, 1)); x1 = fmaxf(x1, __shfl_xor_sync(~0u, x1, 2));
        const float c0 = ex2f(m0 - x0), c1 = ex2f(m1 - x1);
        m0 = x0; m1 = x1;
#pragma unroll
        for (int i = 0; i < 3; i++) { o[4 * i] *= c0; o[4 * i + 1] *= c0; o[4 * i + 2] *= c1; o[4 * i + 3] *= c1; }
#pragma unroll
        for (int i = 0; i < 8; i++) {
          p[2 * i] = pack_bf16(ex2f(s[4 * i] - x0), ex2f(s[4 * i + 1] - x0));
          p[2 * i + 1] = pack_bf16(ex2f(s[4 * i + 2] - x1), ex2f(s[4 * i + 3] - x1));
        }
        WG_FENCE();
        PV_MMA(p, dv + (uint32_t)(j * 192));
        WG_COMMIT();
        WG_WAIT(0);
        fence_regs<12>(o);
      }
      att_store(o, row0 + tile * 64, head, lane);
#pragma unroll
      for (int i = 0; i < 12; i++) o[i] = 0.f;
#pragma unroll
      for (int i = 0; i < 6; i++) q[i] = q2[i];
    }
  }
  if (tid == 0) TS(2, 4);
}

#define K3_NSTG 4
#define K3_SMEM (9 * 16384 + K3_NSTG * 16384 + 1024 + 256)
__global__ void __launch_bounds__(288, 1) k3_kernel(const __grid_constant__ CUtensorMap mo, const __grid_constant__ CUtensorMap mw,
                                                    const __nv_bfloat16* __restrict__ x) {
  extern __shared__ __align__(1024) uint8_t smem_raw[];
  const uint32_t sb = (s2u(smem_raw) + 1023) & ~1023u;
  const uint32_t A = sb, RING = sb + 9 * 16384, BAR = RING + K3_NSTG * 16384;
  const uint32_t full = BAR, empty = BAR + 64, afull = BAR + 128;
  const int tid = threadIdx.x, lane = tid & 31, warp = tid >> 5;
  const int mb = blockIdx.x >> 3, nb = blockIdx.x & 7;
  if (tid == 0) {
    TS(3, 0);
    for (int i = 0; i < K3_NSTG; i++) { mbar_init(full + i * 8, 1); mbar_init(empty + i * 8, 8); }
    for (int i = 0; i < 9; i++) mbar_init(afull + i * 8, 1);
    fence_bar_init();
  }
  __syncthreads();
  pdl_launch();
  if (warp == 8) {
    if (lane == 0) {
      for (int s = 0; s < K3_NSTG; s++) {
        mbar_expect(full + s * 8, 16384);
        tma2d(RING + s * 16384, &mw, nb * 72, s * 64, full + s * 8);
        tma2d(RING + s * 16384 + 8192, &mw, nb * 72 + 64, s * 64, full + s * 8);
      }
      pdl_wait();
      for (int c = 0; c < 9; c++) { mbar_expect(afull + c * 8, 16384); tma2d(A + c * 16384, &mo, c * 64, mb * 128, afull + c * 8); }
      for (int s = K3_NSTG; s < 9; s++) {
        const int st = s % K3_NSTG;
        mbar_wait(empty + st * 8, ((s / K3_NSTG) & 1) ^ 1);
        mbar_expect(full + st * 8, 16384);
        tma2d(RING + st * 16384, &mw, nb * 72, s * 64, full + st * 8);
        tma2d(RING + st * 16384 + 8192, &mw, nb * 72 + 64, s * 64, full + st * 8);
      }
    }
  } else {
    const int g = lane >> 2, cq = lane & 3;
    const int row = mb * 128 + warp * 16 + g, col = nb * 72 + cq * 2;
    uint32_t xv[18];
#pragma unroll
    for (int i = 0; i < 9; i++) {
      xv[2 * i] = __ldg((const uint32_t*)(x + (size_t)row * DM + col + 8 * i));
      xv[2 * i + 1] = __ldg((const uint32_t*)(x + (size_t)(row + 8) * DM + col + 8 * i));
    }
    pdl_wait();
    if (tid == 0) TS(3, 1);
    float2 ga[9];
#pragma unroll
    for (int i = 0; i < 9; i++) ga[i] = *(const float2*)(g_ga + col + 8 * i);
    float acc[36];
    const uint32_t abase = A + (warp >> 2) * 8192;
#pragma unroll
    for (int s = 0; s < 9; s++) {
      const int st = s % K3_NSTG;
      mbar_wait(afull + s * 8, 0);
      mbar_wait(full + st * 8, (s / K3_NSTG) & 1);
      WG_FENCE();
#pragma unroll
      for (int k = 0; k < 4; k++)
        wg_ss_n72_t1(acc, mkdesc(abase + s * 16384 + k * 32, 16, 1024, 1), mkdesc(RING + st * 16384 + k * 2048, 8192, 1024, 1), (s | k) != 0);
      WG_COMMIT();
      if (s > 0) { WG_WAIT(1); if (lane == 0) mbar_arrive(empty + ((s - 1) % K3_NSTG) * 8); }
    }
    WG_WAIT(0);
    if (tid == 0) TS(3, 2);
    float s0 = 0, s1 = 0;
#pragma unroll
    for (int i = 0; i < 9; i++) {
      acc[4 * i] = rbf(bf_lo(xv[2 * i]) + rbf(ga[i].x * rbf(acc[4 * i])));
      acc[4 * i + 1] = rbf(bf_hi(xv[2 * i]) + rbf(ga[i].y * rbf(acc[4 * i + 1])));
      acc[4 * i + 2] = rbf(bf_lo(xv[2 * i + 1]) + rbf(ga[i].x * rbf(acc[4 * i + 2])));
      acc[4 * i + 3] = rbf(bf_hi(xv[2 * i + 1]) + rbf(ga[i].y * rbf(acc[4 * i + 3])));
      *(uint32_t*)(g_x1 + (size_t)row * DM + col + 8 * i) = pack_bf16(acc[4 * i], acc[4 * i + 1]);
      *(uint32_t*)(g_x1 + (size_t)(row + 8) * DM + col + 8 * i) = pack_bf16(acc[4 * i + 2], acc[4 * i + 3]);
      s0 += acc[4 * i] + acc[4 * i + 1];
      s1 += acc[4 * i + 2] + acc[4 * i + 3];
    }
    s0 += __shfl_xor_sync(~0u, s0, 1); s0 += __shfl_xor_sync(~0u, s0, 2);
    s1 += __shfl_xor_sync(~0u, s1, 1); s1 += __shfl_xor_sync(~0u, s1, 2);
    const float m0 = s0 * (1.0f / 72), m1 = s1 * (1.0f / 72);
    float q0 = 0, q1 = 0;
#pragma unroll
    for (int i = 0; i < 9; i++) {
      q0 += (acc[4 * i] - m0) * (acc[4 * i] - m0) + (acc[4 * i + 1] - m0) * (acc[4 * i + 1] - m0);
      q1 += (acc[4 * i + 2] - m1) * (acc[4 * i + 2] - m1) + (acc[4 * i + 3] - m1) * (acc[4 * i + 3] - m1);
    }
    q0 += __shfl_xor_sync(~0u, q0, 1); q0 += __shfl_xor_sync(~0u, q0, 2);
    q1 += __shfl_xor_sync(~0u, q1, 1); q1 += __shfl_xor_sync(~0u, q1, 2);
    if (cq == 0) {
      g_stat2[row * 8 + nb] = make_float2(m0, q0);
      g_stat2[(row + 8) * 8 + nb] = make_float2(m1, q1);
    }
    if (tid == 0) TS(3, 3);
  }
}

__device__ __forceinline__ uint4 ln2_consts(int row, int cq) {
  const float4 p = *(const float4*)(g_stat2 + row * 8 + cq * 2);
  float s = p.x + p.z;
  s += __shfl_xor_sync(~0u, s, 1); s += __shfl_xor_sync(~0u, s, 2);
  const float mean = s * 0.125f;
  float q = p.y + p.w + 72.0f * ((p.x - mean) * (p.x - mean) + (p.z - mean) * (p.z - mean));
  q += __shfl_xor_sync(~0u, q, 1); q += __shfl_xor_sync(~0u, q, 2);
  return ln_consts(mean, q * (1.0f / DM));
}
__device__ __forceinline__ uint32_t glu_pair(float g0, float g1, float u0, float u1) {
  return pack_bf16(fmaf(tanhf_fast(g0), u0, u0), fmaf(tanhf_fast(g1), u1, u1));
}
template <int NG>
__device__ __forceinline__ void stage_part(const float* acc, uint32_t stg, int lane) {
  const int r = (lane & 7) + ((lane >> 3) & 1) * 8;
#pragma unroll
  for (int i = 0; i < NG; i += 2) {
    const int ch = i + (lane >> 4);
    stsm4(stg + r * (NG * 16) + ((ch ^ (r & 7)) << 4), pack_bf16(acc[4 * i], acc[4 * i + 1]), pack_bf16(acc[4 * i + 2], acc[4 * i + 3]),
          pack_bf16(acc[4 * i + 4], acc[4 * i + 5]), pack_bf16(acc[4 * i + 6], acc[4 * i + 7]));
  }
}
__device__ __forceinline__ uint4 lds128(uint32_t a) {
  uint4 v;
  asm volatile("ld.shared.v4.b32 {%0,%1,%2,%3},[%4];" : "=r"(v.x), "=r"(v.y), "=r"(v.z), "=r"(v.w) : "r"(a) : "memory");
  return v;
}
__device__ __forceinline__ void sts128(uint32_t a, const uint4& v) {
  asm volatile("st.shared.v4.b32 [%0],{%1,%2,%3,%4};" ::"r"(a), "r"(v.x), "r"(v.y), "r"(v.z), "r"(v.w) : "memory");
}
__device__ __forceinline__ uint32_t res_pair(uint32_t x, uint32_t g, float s0, float s1) { return hadd2(x, hmul2(g, pack_bf16(s0, s1))); }

__global__ void __launch_bounds__(384, 1) k4_kernel(const __grid_constant__ CUtensorMap mx, const __grid_constant__ CUtensorMap mg,
                                                    const __grid_constant__ CUtensorMap mu, const __grid_constant__ CUtensorMap md,
                                                    __nv_bfloat16* __restrict__ out) {
  extern __shared__ __align__(1024) uint8_t smem_raw[];
  const uint32_t sb = s2u(smem_raw);
  const uint32_t R = sb, RING = sb + R_BYTES, BAR = RING + NSTG * STG_BYTES, TAB = BAR + 512;
  const uint32_t full = BAR, empty = BAR + 64, xfull = BAR + 128, gfull = BAR + 272, sfull = BAR + 320;
  const int tid = threadIdx.x, lane = tid & 31, warp = tid >> 5;
  const int mb = blockIdx.x >> 3, fb = blockIdx.x & 7;
  if (tid == 0) {
    TS(4, 0);
    if (sb & 1023) __trap();
    for (int i = 0; i < 10; i++) mbar_init(sfull + i * 8, 4);
    for (int i = 0; i < NSTG; i++) { mbar_init(full + i * 8, 1); mbar_init(empty + i * 8, 8); }
    for (int i = 0; i < 18; i++) mbar_init(xfull + i * 8, 1);
    for (int i = 0; i < 5; i++) mbar_init(gfull + i * 8, 1);
    mbar_arrive(full);
    fence_bar_init();
  }
  __syncthreads();
  if (warp >= 8) {
    REG_DEC(24);
    if (lane == 0) {
      if (warp == 8) {
        int st = 1; uint32_t ph = 0;
        for (int it = 0; it < 126; it++) {
          if (it == NSTG - 1) {
            pdl_wait();
            for (int c = 0; c < 18; c++) {
              const int w = c >= 9, k = c - w * 9;
              mbar_expect(xfull + c * 8, 8192);
              tma2d(R + k * 16384 + w * 8192, &mx, k * 64, mb * 128 + w * 64, xfull + c * 8);
            }
          }
          const int t = it / 9, s = it - t * 9;
          const uint32_t dst = RING + st * STG_BYTES, fb_ = full + st * 8;
          mbar_wait(empty + st * 8, ph ^ 1);
          if (t < 9) {
            mbar_expect(fb_, 16384);
            tma2d(dst, &mg, fb * 576 + t * 64, s * 64, fb_);
            tma2d(dst + 8192, &mu, fb * 576 + t * 64, s * 64, fb_);
          } else {
            mbar_expect(fb_, t < 13 ? 16384 : 8192);
            tma2d(dst, &md, (t - 9) * 128, fb * 576 + s * 64, fb_);
            if (t < 13) tma2d(dst + 8192, &md, (t - 9) * 128 + 64, fb * 576 + s * 64, fb_);
          }
          if (++st == NSTG) { st = 0; ph ^= 1; }
        }
      } else if (warp < 11) {
        const int wg = warp - 9;
#pragma unroll 1
        for (int p = 0; p < 5; p++) {
          uint8_t* dst = g_part + (size_t)((fb * 16 + mb) * 5 + p) * 32768;
          mbar_wait(sfull + (p * 2 + wg) * 8, 0);
          if (p < 4) {
            bulk_s2g(dst + wg * 16384, R + p * 32768 + wg * 8192, 8192);
            bulk_s2g(dst + wg * 16384 + 8192, R + p * 32768 + 16384 + wg * 8192, 8192);
          } else {
            bulk_s2g(dst + wg * 8192, RING + wg * STG_BYTES + 8192, 8192);
          }
          bulk_commit();
          bulk_wait0();
          asm volatile("fence.proxy.async;" ::: "memory");
          asm volatile("red.release.gpu.global.add.u32 [%0],1;" ::"l"(g_cnt + mb * 5 + p) : "memory");
        }
      } else {
        mbar_wait(sfull, 0);
#pragma unroll 1
        for (int p = 0; p < 5; p++) {
          unsigned int v; int n = 0;
          do {
            asm volatile("ld.acquire.gpu.global.u32 %0,[%1];" : "=r"(v) : "l"(g_cnt + mb * 5 + p) : "memory");
          } while (v < 16 && ++n < 20000000);
          if (v < 16) __trap();
          asm volatile("fence.proxy.async;" ::: "memory");
          const uint32_t sz = p < 4 ? 4096 : 2048;
          mbar_expect(gfull + p * 8, sz * 8);
#pragma unroll 1
          for (int f = 0; f < 8; f++)
            bulk_g2s(p < 4 ? R + p * 32768 + f * 4096 : RING + (2 + (f >> 2)) * STG_BYTES + 8192 + (f & 3) * 2048,
                     g_part + (size_t)((f * 16 + mb) * 5 + p) * 32768 + fb * sz, sz, gfull + p * 8);
        }
      }
    }
  } else {
    REG_INC(240);
    uint32_t a[36][4];
    const int wg = warp >> 2, wl = warp & 3;
    if (tid < 144) sts128(TAB + tid * 16, g_tab2[tid]);
    bar_sync(1, 256);
    pdl_wait();
    TSS(0);
    {
      const int g = lane >> 2, cq = lane & 3;
      const uint4 s0 = ln2_consts(mb * 128 + warp * 16 + g, cq), s1 = ln2_consts(mb * 128 + warp * 16 + g + 8, cq);
#pragma unroll
      for (int c = 0; c < 9; c++) {
        mbar_wait(xfull + (wg * 9 + c) * 8, 0);
        load_a_chunk(&a[c * 4], R + c * 16384, warp * 16, lane);
        if (c == 8) { __syncwarp(); if (lane == 0) mbar_arrive(empty); }
#pragma unroll
        for (int k = c * 4; k < c * 4 + 4; k++) {
          const uint4 t = lds128(TAB + (k * 4 + cq) * 16);
          a[k][0] = ln_apply(a[k][0], s0, t.x, t.y);
          a[k][1] = ln_apply(a[k][1], s1, t.x, t.y);
          a[k][2] = ln_apply(a[k][2], s0, t.z, t.w);
          a[k][3] = ln_apply(a[k][3], s1, t.z, t.w);
        }
      }
    }
    TSS(1);
    float acc[64];
    const uint32_t hsp = R + warp * 2048 + lane * 16;
#define GLU_SPILL(t)                                                            \
  _Pragma("unroll") for (int j = 0; j < 4; j++) {                               \
    uint32_t h[4];                                                              \
    _Pragma("unroll") for (int e = 0; e < 4; e++)                               \
      h[e] = glu_pair(acc[8 * j + 2 * e], acc[8 * j + 2 * e + 1], acc[32 + 8 * j + 2 * e], acc[32 + 8 * j + 2 * e + 1]); \
    asm volatile("st.shared.v4.b32 [%0],{%1,%2,%3,%4};" ::"r"(hsp + (t) * 16384 + j * 512), "r"(h[0]), "r"(h[1]), "r"(h[2]), "r"(h[3]) : "memory"); \
  }
#pragma unroll 1
    for (int t = 0; t < 4; t++) {
      MMA_TILE(wl_rs_n128_t1, 0, t & 1);
      GLU_SPILL(2 * t);
      MMA_TILE(wl_rs_n128_t1, 1, t & 1);
      GLU_SPILL(2 * t + 1);
    }
    MMA_TILE(wl_rs_n128_t1, 0, 0);
#pragma unroll
    for (int j = 0; j < 4; j++)
#pragma unroll
      for (int e = 0; e < 4; e++)
        a[32 + j][e] = glu_pair(acc[8 * j + 2 * e], acc[8 * j + 2 * e + 1], acc[32 + 8 * j + 2 * e], acc[32 + 8 * j + 2 * e + 1]);
#pragma unroll
    for (int k = 0; k < 32; k++)
      asm volatile("ld.shared.v4.b32 {%0,%1,%2,%3},[%4];" : "=r"(a[k][0]), "=r"(a[k][1]), "=r"(a[k][2]), "=r"(a[k][3]) : "r"(hsp + (k >> 2) * 16384 + (k & 3) * 512) : "memory");
    TSS(2);
    const uint32_t stg = R + (wl >> 1) * 16384 + wg * 8192 + (wl & 1) * 4096;
#define PART_OUT(p)                                                             \
  stage_part<16>(acc, stg + (p) * 32768, lane);                                 \
  fence_async_smem();                                                           \
  __syncwarp();                                                                 \
  if (lane == 0) mbar_arrive(sfull + ((p) * 2 + wg) * 8);
    bar_sync(2 + wg, 128);
#pragma unroll 1
    for (int p = 0; p < 2; p++) {
      MMA_TILE(wl_rs_n128_t1, 1, p);
      PART_OUT(2 * p);
      MMA_TILE(wl_rs_n128_t1, 0, p ^ 1);
      PART_OUT(2 * p + 1);
    }
    MMA_TILE(wl_rs_n64_t1, 1, 0);
    stage_part<8>(acc, RING + wg * STG_BYTES + 8192 + wl * 2048, lane);
    fence_async_smem();
    __syncwarp();
    if (lane == 0) mbar_arrive(sfull + (8 + wg) * 8);
    TSS(3);
    const int rl = tid >> 4, ch = tid & 15;
    const size_t off = (size_t)(mb * 128 + fb * 16 + rl) * DM + ch * 8;
    uint4 xv[5], gv[5];
#pragma unroll
    for (int p = 0; p < 5; p++)
      if (p < 4 || ch < 8) { xv[p] = __ldcg((const uint4*)(g_x1 + off + p * 128)); gv[p] = __ldcg((const uint4*)(g_gb + p * 128 + ch * 8)); }
#pragma unroll
    for (int p = 0; p < 5; p++) {
      if (p == 4 && ch >= 8) break;
      mbar_wait(gfull + p * 8, 0);
      float r8[8] = {0, 0, 0, 0, 0, 0, 0, 0};
#pragma unroll
      for (int f = 0; f < 8; f++) {
        const uint4 v = lds128((p < 4 ? R + p * 32768 + f * 4096 + rl * 256 : RING + (2 + (f >> 2)) * STG_BYTES + 8192 + (f & 3) * 2048 + rl * 128) +
                               ((ch ^ (rl & 7)) << 4));
        r8[0] += bf_lo(v.x); r8[1] += bf_hi(v.x); r8[2] += bf_lo(v.y); r8[3] += bf_hi(v.y);
        r8[4] += bf_lo(v.z); r8[5] += bf_hi(v.z); r8[6] += bf_lo(v.w); r8[7] += bf_hi(v.w);
      }
      uint4 r;
      r.x = res_pair(xv[p].x, gv[p].x, r8[0], r8[1]);
      r.y = res_pair(xv[p].y, gv[p].y, r8[2], r8[3]);
      r.z = res_pair(xv[p].z, gv[p].z, r8[4], r8[5]);
      r.w = res_pair(xv[p].w, gv[p].w, r8[6], r8[7]);
      *(uint4*)(out + off + p * 128) = r;
      if (p >= 2) TSS(2 + p);
    }
    TSDUMP(4);
  }
}

typedef CUresult (*EncodeFn)(CUtensorMap*, CUtensorMapDataType, cuuint32_t, void*, const cuuint64_t*, const cuuint64_t*,
                             const cuuint32_t*, const cuuint32_t*, CUtensorMapInterleave, CUtensorMapSwizzle,
                             CUtensorMapL2promotion, CUtensorMapFloatOOBfill);
static void make_map(EncodeFn fn, CUtensorMap* m, const void* p, int rows, int cols, int box_rows) {
  cuuint64_t dims[2] = {(cuuint64_t)cols, (cuuint64_t)rows};
  cuuint64_t strides[1] = {(cuuint64_t)cols * 2};
  cuuint32_t box[2] = {64, (cuuint32_t)box_rows};
  cuuint32_t es[2] = {1, 1};
  fn(m, CU_TENSOR_MAP_DATA_TYPE_BFLOAT16, 2, (void*)p, dims, strides, box, es, CU_TENSOR_MAP_INTERLEAVE_NONE,
     CU_TENSOR_MAP_SWIZZLE_128B, CU_TENSOR_MAP_L2_PROMOTION_L2_256B, CU_TENSOR_MAP_FLOAT_OOB_FILL_NONE);
}
template <typename... KA, typename... A>
static void launch(void (*k)(KA...), int grid, int block, int smem, bool pdl, A... args) {
  cudaLaunchConfig_t cfg = {};
  cfg.gridDim = dim3(grid); cfg.blockDim = dim3(block); cfg.dynamicSmemBytes = smem; cfg.stream = cudaStreamPerThread;
  cudaLaunchAttribute at;
  at.id = cudaLaunchAttributeProgrammaticStreamSerialization;
  at.val.programmaticStreamSerializationAllowed = 1;
  cfg.attrs = &at; cfg.numAttrs = pdl ? 1 : 0;
  cudaLaunchKernelEx(&cfg, k, KA(args)...);
}

extern "C" void kernel_launch(void* const* d_in, const int* in_sizes, int n_in, void* d_out, int out_size) {
  const __nv_bfloat16* x = (const __nv_bfloat16*)d_in[0];
  void* fnp = nullptr;
  cudaDriverEntryPointQueryResult qr;
  cudaGetDriverEntryPoint("cuTensorMapEncodeTiled", &fnp, cudaEnableDefault, &qr);
  EncodeFn fn = (EncodeFn)fnp;
  void *po, *px1;
  cudaGetSymbolAddress(&po, g_o);
  cudaGetSymbolAddress(&px1, g_x1);
  CUtensorMap mx, mqkv, mo, mwo, mx1, mg, mu, md;
  make_map(fn, &mx, x, SEQ, DM, 128);
  make_map(fn, &mqkv, d_in[1], DM, 3 * DM, 64);
  make_map(fn, &mo, po, SEQ, DM, 128);
  make_map(fn, &mwo, d_in[2], DM, DM, 64);
  make_map(fn, &mx1, px1, SEQ, DM, 64);
  make_map(fn, &mg, d_in[4], DM, FF, 64);
  make_map(fn, &mu, d_in[5], DM, FF, 64);
  make_map(fn, &md, d_in[6], FF, DM, 64);
  cudaFuncSetAttribute(k1_kernel, cudaFuncAttributeMaxDynamicSharedMemorySize, GEMM_SMEM);
  cudaFuncSetAttribute(k2_kernel, cudaFuncAttributeMaxDynamicSharedMemorySize, ATT_SMEM);
  cudaFuncSetAttribute(k3_kernel, cudaFuncAttributeMaxDynamicSharedMemorySize, K3_SMEM);
  cudaFuncSetAttribute(k4_kernel, cudaFuncAttributeMaxDynamicSharedMemorySize, GEMM_SMEM);
  launch(k0_kernel, 108 + 128, 256, 0, false, x, (const __nv_bfloat16*)d_in[7], (const __nv_bfloat16*)d_in[8]);
  launch(k1_kernel, 128, 384, GEMM_SMEM, true, mx, mqkv);
  launch(k2_kernel, 128, 512, ATT_SMEM, true, (const uint8_t*)d_in[2], (const uint8_t*)d_in[4], (const uint8_t*)d_in[5], (const uint8_t*)d_in[6]);
  launch(k3_kernel, 128, 288, K3_SMEM, true, mo, mwo, x);
  launch(k4_kernel, 128, 384, GEMM_SMEM, true, mx1, mg, mu, md, (__nv_bfloat16*)d_out);
}
```

```cpp
#include <cuda_runtime.h>
#include <cuda_bf16.h>
#include <cuda.h>
#include <stdint.h>

#define SEQ 2048
#define DM 576
#define NH 32
#define FF 4608

__device__ uint4 g_ll[36 * 4 * 2];
__device__ uint4 g_tab2[36 * 4];
__device__ __align__(16) __nv_bfloat16 g_ga[DM];
__device__ __align__(16) __nv_bfloat16 g_gb[DM];
__device__ float2 g_stat2[SEQ * 8];
__device__ __align__(1024) uint8_t g_qkv[96 * 98304];
__device__ float g_kmax[NH * 16];
__device__ __align__(1024) __nv_bfloat16 g_o[SEQ * DM];
__device__ __align__(1024) __nv_bfloat16 g_x1[SEQ * DM];
__device__ __align__(1024) uint8_t g_part[8 * 16 * 5 * 2 * 16384];
__device__ unsigned int g_cnt[16 * 5];

#define TS(k, i)
#define TSS(i)
#define TSDUMP(k)
__device__ __forceinline__ uint32_t s2u(const void* p) { return (uint32_t)__cvta_generic_to_shared(p); }
__device__ __forceinline__ void mbar_init(uint32_t b, int c) { asm volatile("mbarrier.init.shared::cta.b64 [%0],%1;" ::"r"(b), "r"(c)); }
__device__ __forceinline__ void mbar_expect(uint32_t b, uint32_t n) { asm volatile("mbarrier.arrive.expect_tx.shared::cta.b64 _,[%0],%1;" ::"r"(b), "r"(n) : "memory"); }
__device__ __forceinline__ void mbar_arrive(uint32_t b) { asm volatile("mbarrier.arrive.shared::cta.b64 _,[%0];" ::"r"(b) : "memory"); }
__device__ __forceinline__ void mbar_wait(uint32_t b, uint32_t ph) {
  asm volatile(
      "{.reg .pred p; .reg .u32 n;\n"
      "mbarrier.try_wait.parity.shared::cta.b64 p,[%0],%1;\n"
      "@p bra D;\n"
      "mov.u32 n,0;\n"
      "W: mbarrier.try_wait.parity.shared::cta.b64 p,[%0],%1;\n"
      "@p bra D;\n"
      "add.u32 n,n,1; setp.lt.u32 p,n,4000000; @p bra W;\n"
      "trap;\n"
      "D: }" ::"r"(b), "r"(ph) : "memory");
}
__device__ __forceinline__ void tma2d(uint32_t dst, const CUtensorMap* m, int c0, int c1, uint32_t bar) {
  asm volatile("cp.async.bulk.tensor.2d.shared::cluster.global.mbarrier::complete_tx::bytes [%0],[%1,{%3,%4}],[%2];"
               ::"r"(dst), "l"(m), "r"(bar), "r"(c0), "r"(c1) : "memory");
}
__device__ __forceinline__ void bulk_g2s(uint32_t dst, const void* src, uint32_t bytes, uint32_t bar) {
  asm volatile("cp.async.bulk.shared::cluster.global.mbarrier::complete_tx::bytes [%0],[%1],%2,[%3];"
               ::"r"(dst), "l"(src), "r"(bytes), "r"(bar) : "memory");
}
__device__ __forceinline__ void bulk_s2g(void* dst, uint32_t src, uint32_t bytes) {
  asm volatile("cp.async.bulk.global.shared::cta.bulk_group [%0],[%1],%2;" ::"l"(dst), "r"(src), "r"(bytes) : "memory");
}
__device__ __forceinline__ void bulk_commit() { asm volatile("cp.async.bulk.commit_group;" ::: "memory"); }
__device__ __forceinline__ void bulk_wait0() { asm volatile("cp.async.bulk.wait_group 0;" ::: "memory"); }
__device__ __forceinline__ void prefetch_map(const CUtensorMap* m) { asm volatile("prefetch.tensormap [%0];" ::"l"(m) : "memory"); }
__device__ __forceinline__ void fence_async_smem() { asm volatile("fence.proxy.async.shared::cta;" ::: "memory"); }
__device__ __forceinline__ void fence_bar_init() { asm volatile("fence.mbarrier_init.release.cluster;" ::: "memory"); }
__device__ __forceinline__ void pdl_wait() { asm volatile("griddepcontrol.wait;" ::: "memory"); }
__device__ __forceinline__ void pdl_launch() { asm volatile("griddepcontrol.launch_dependents;" ::: "memory"); }
__device__ __forceinline__ void bar_sync(int id, int n) { asm volatile("bar.sync %0,%1;" ::"r"(id), "r"(n) : "memory"); }
__device__ __forceinline__ void bar_arrive(int id, int n) { asm volatile("bar.arrive %0,%1;" ::"r"(id), "r"(n) : "memory"); }
#define WG_FENCE() asm volatile("wgmma.fence.sync.aligned;" ::: "memory")
#define WG_COMMIT() asm volatile("wgmma.commit_group.sync.aligned;" ::: "memory")
#define WG_WAIT(n) asm volatile("wgmma.wait_group.sync.aligned " #n ";" ::: "memory")
template <int N> __device__ __forceinline__ void fence_regs(float* r) {
#pragma unroll
  for (int i = 0; i < N; i++) asm volatile("" : "+f"(r[i])::"memory");
}
#define REG_INC(n) asm volatile("setmaxnreg.inc.sync.aligned.u32 " #n ";")
#define REG_DEC(n) asm volatile("setmaxnreg.dec.sync.aligned.u32 " #n ";")
__device__ __forceinline__ uint64_t mkdesc(uint32_t addr, uint32_t lbo, uint32_t sbo, int sw) {
  return (uint64_t)((addr & 0x3FFFF) >> 4) | ((uint64_t)(lbo >> 4) << 16) | ((uint64_t)(sbo >> 4) << 32) | ((uint64_t)sw << 62);
}
__device__ __forceinline__ void ldsm4(uint32_t* r, uint32_t addr) {
  asm volatile("ldmatrix.sync.aligned.m8n8.x4.shared.b16 {%0,%1,%2,%3},[%4];" : "=r"(r[0]), "=r"(r[1]), "=r"(r[2]), "=r"(r[3]) : "r"(addr) : "memory");
}
__device__ __forceinline__ void stsm4(uint32_t addr, uint32_t r0, uint32_t r1, uint32_t r2, uint32_t r3) {
  asm volatile("stmatrix.sync.aligned.m8n8.x4.shared.b16 [%0],{%1,%2,%3,%4};" ::"r"(addr), "r"(r0), "r"(r1), "r"(r2), "r"(r3) : "memory");
}
__device__ __forceinline__ uint32_t pack_bf16(float lo, float hi) {
  uint32_t r;
  asm("cvt.rn.bf16x2.f32 %0,%1,%2;" : "=r"(r) : "f"(hi), "f"(lo));
  return r;
}
__device__ __forceinline__ float bf_lo(uint32_t v) { return __uint_as_float(v << 16); }
__device__ __forceinline__ float bf_hi(uint32_t v) { return __uint_as_float(v & 0xFFFF0000u); }
__device__ __forceinline__ float sq2(uint32_t v) { return bf_lo(v) * bf_lo(v) + bf_hi(v) * bf_hi(v); }
__device__ __forceinline__ float rbf(float x) { return __bfloat162float(__float2bfloat16_rn(x)); }
__device__ __forceinline__ uint32_t hfma2(uint32_t a, uint32_t b, uint32_t c) {
  uint32_t r;
  asm("fma.rn.bf16x2 %0,%1,%2,%3;" : "=r"(r) : "r"(a), "r"(b), "r"(c));
  return r;
}
__device__ __forceinline__ uint32_t hadd2(uint32_t a, uint32_t b) {
  uint32_t r;
  asm("add.rn.bf16x2 %0,%1,%2;" : "=r"(r) : "r"(a), "r"(b));
  return r;
}
__device__ __forceinline__ uint32_t hmul2(uint32_t a, uint32_t b) {
  uint32_t r;
  asm("mul.rn.bf16x2 %0,%1,%2;" : "=r"(r) : "r"(a), "r"(b));
  return r;
}
__device__ __forceinline__ uint32_t hneg2(uint32_t a) {
  uint32_t r;
  asm("neg.bf16x2 %0,%1;" : "=r"(r) : "r"(a));
  return r;
}
__device__ __forceinline__ float ex2f(float x) {
  float r;
  asm("ex2.approx.ftz.f32 %0,%1;" : "=f"(r) : "f"(x));
  return r;
}
__device__ __forceinline__ float sqrt_fast(float x) {
  float r;
  asm("sqrt.approx.f32 %0,%1;" : "=f"(r) : "f"(x));
  return r;
}
__device__ __forceinline__ float rcp_fast(float x) {
  float r;
  asm("rcp.approx.f32 %0,%1;" : "=f"(r) : "f"(x));
  return r;
}
__device__ __forceinline__ float tanhf_fast(float x) {
  float r;
  asm("tanh.approx.f32 %0,%1;" : "=f"(r) : "f"(x));
  return r;
}
__device__ __forceinline__ uint4 ln_consts(float mean, float var) {
  float m = rbf(mean), v = rbf(var);
  float s = rbf(sqrtf(rbf(v + 1e-5f)));
  float r = 1.0f / s;
  float rh = rbf(r), rl = r - rh;
  return make_uint4(pack_bf16(-m, -m), pack_bf16(rh, rh), pack_bf16(rl, rl), 0u);
}
__device__ __forceinline__ uint32_t ln_apply(uint32_t x, const uint4& st, uint32_t a, uint32_t s) {
  uint32_t d = hadd2(x, st.x);
  uint32_t n = hfma2(d, st.y, hmul2(d, st.z));
  return hfma2(n, a, s);
}

__device__ __forceinline__ uint4 lds128(uint32_t a) {
  uint4 v;
  asm volatile("ld.shared.v4.b32 {%0,%1,%2,%3},[%4];" : "=r"(v.x), "=r"(v.y), "=r"(v.z), "=r"(v.w) : "r"(a) : "memory");
  return v;
}
__device__ __forceinline__ void sts128(uint32_t a, const uint4& v) {
  asm volatile("st.shared.v4.b32 [%0],{%1,%2,%3,%4};" ::"r"(a), "r"(v.x), "r"(v.y), "r"(v.z), "r"(v.w) : "memory");
}
__device__ __forceinline__ void hmma(float* c, const uint32_t* a, uint32_t b0, uint32_t b1) {
  asm volatile("mma.sync.aligned.m16n8k16.row.col.f32.bf16.bf16.f32 {%0,%1,%2,%3},{%4,%5,%6,%7},{%8,%9},{%0,%1,%2,%3};"
               : "+f"(c[0]), "+f"(c[1]), "+f"(c[2]), "+f"(c[3]) : "r"(a[0]), "r"(a[1]), "r"(a[2]), "r"(a[3]), "r"(b0), "r"(b1));
}
struct RowStat {
  float s[4], q0[4], q1[4];
  __device__ __forceinline__ void init() {
#pragma unroll
    for (int i = 0; i < 4; i++) s[i] = q0[i] = q1[i] = 0.f;
  }
  __device__ __forceinline__ void add(const uint32_t* a) {
    hmma(s, a, 0x3F803F80u, 0x3F803F80u);
    hmma(q0, a, a[0], a[2]);
    hmma(q1, a, a[1], a[3]);
  }
  __device__ __forceinline__ void finish(int lane, uint4& c0, uint4& c1) {
    const int g = lane >> 2, src = (lane & ~3) | (g >> 1);
    const float a0 = __shfl_sync(~0u, (g & 1) ? q0[1] : q0[0], src), a1 = __shfl_sync(~0u, (g & 1) ? q1[3] : q1[2], src);
    const float m0 = s[0] * (1.0f / DM), m1 = s[2] * (1.0f / DM);
    c0 = ln_consts(m0, fmaxf(a0 * (1.0f / DM) - m0 * m0, 0.f));
    c1 = ln_consts(m1, fmaxf(a1 * (1.0f / DM) - m1 * m1, 0.f));
  }
};
#define LN_APPLY_ALL()                                                          \
  _Pragma("unroll") for (int k = 0; k < 36; k++) {                              \
    const uint4 t = lds128(TAB + (k * 4 + (lane & 3)) * 16);                    \
    a[k][0] = ln_apply(a[k][0], s0, t.x, t.y);                                  \
    a[k][1] = ln_apply(a[k][1], s1, t.x, t.y);                                  \
    a[k][2] = ln_apply(a[k][2], s0, t.z, t.w);                                  \
    a[k][3] = ln_apply(a[k][3], s1, t.z, t.w);                                  \
  }

__device__ __forceinline__ void wg_ss_n72_t1(float* d, uint64_t da, uint64_t db, int sc) {
  asm volatile("{.reg .pred p; setp.ne.b32 p,%38,0; wgmma.mma_async.sync.aligned.m64n72k16.f32.bf16.bf16 {%0,%1,%2,%3,%4,%5,%6,%7,%8,%9,%10,%11,%12,%13,%14,%15,%16,%17,%18,%19,%20,%21,%22,%23,%24,%25,%26,%27,%28,%29,%30,%31,%32,%33,%34,%35}, %36, %37, p,1,1,0,1;}"
  : "+f"(d[0]),"+f"(d[1]),"+f"(d[2]),"+f"(d[3]),"+f"(d[4]),"+f"(d[5]),"+f"(d[6]),"+f"(d[7]),"+f"(d[8]),"+f"(d[9]),"+f"(d[10]),"+f"(d[11]),"+f"(d[12]),"+f"(d[13]),"+f"(d[14]),"+f"(d[15]),"+f"(d[16]),"+f"(d[17]),"+f"(d[18]),"+f"(d[19]),"+f"(d[20]),"+f"(d[21]),"+f"(d[22]),"+f"(d[23]),"+f"(d[24]),"+f"(d[25]),"+f"(d[26]),"+f"(d[27]),"+f"(d[28]),"+f"(d[29]),"+f"(d[30]),"+f"(d[31]),"+f"(d[32]),"+f"(d[33]),"+f"(d[34]),"+f"(d[35]) : "l"(da),"l"(db),"r"(sc));
}
template <int SC> __device__ __forceinline__ void wl_rs_n128_t1(float* d, const uint32_t* a, uint64_t e) {
  asm volatile("wgmma.mma_async.sync.aligned.m64n128k16.f32.bf16.bf16 {%0,%1,%2,%3,%4,%5,%6,%7,%8,%9,%10,%11,%12,%13,%14,%15,%16,%17,%18,%19,%20,%21,%22,%23,%24,%25,%26,%27,%28,%29,%30,%31,%32,%33,%34,%35,%36,%37,%38,%39,%40,%41,%42,%43,%44,%45,%46,%47,%48,%49,%50,%51,%52,%53,%54,%55,%56,%57,%58,%59,%60,%61,%62,%63}, {%64,%65,%66,%67}, %68, %69,1,1,1;"
  : "+f"(d[0]),"+f"(d[1]),"+f"(d[2]),"+f"(d[3]),"+f"(d[4]),"+f"(d[5]),"+f"(d[6]),"+f"(d[7]),"+f"(d[8]),"+f"(d[9]),"+f"(d[10]),"+f"(d[11]),"+f"(d[12]),"+f"(d[13]),"+f"(d[14]),"+f"(d[15]),"+f"(d[16]),"+f"(d[17]),"+f"(d[18]),"+f"(d[19]),"+f"(d[20]),"+f"(d[21]),"+f"(d[22]),"+f"(d[23]),"+f"(d[24]),"+f"(d[25]),"+f"(d[26]),"+f"(d[27]),"+f"(d[28]),"+f"(d[29]),"+f"(d[30]),"+f"(d[31]),"+f"(d[32]),"+f"(d[33]),"+f"(d[34]),"+f"(d[35]),"+f"(d[36]),"+f"(d[37]),"+f"(d[38]),"+f"(d[39]),"+f"(d[40]),"+f"(d[41]),"+f"(d[42]),"+f"(d[43]),"+f"(d[44]),"+f"(d[45]),"+f"(d[46]),"+f"(d[47]),"+f"(d[48]),"+f"(d[49]),"+f"(d[50]),"+f"(d[51]),"+f"(d[52]),"+f"(d[53]),"+f"(d[54]),"+f"(d[55]),"+f"(d[56]),"+f"(d[57]),"+f"(d[58]),"+f"(d[59]),"+f"(d[60]),"+f"(d[61]),"+f"(d[62]),"+f"(d[63]) : "r"(a[0]),"r"(a[1]),"r"(a[2]),"r"(a[3]),"l"(e),"n"(SC));
}
template <int SC> __device__ __forceinline__ void wl_rs_n24_t1(float* d, const uint32_t* a, uint64_t e) {
  asm volatile("wgmma.mma_async.sync.aligned.m64n24k16.f32.bf16.bf16 {%0,%1,%2,%3,%4,%5,%6,%7,%8,%9,%10,%11}, {%12,%13,%14,%15}, %16, %17,1,1,1;"
  : "+f"(d[0]),"+f"(d[1]),"+f"(d[2]),"+f"(d[3]),"+f"(d[4]),"+f"(d[5]),"+f"(d[6]),"+f"(d[7]),"+f"(d[8]),"+f"(d[9]),"+f"(d[10]),"+f"(d[11]) : "r"(a[0]),"r"(a[1]),"r"(a[2]),"r"(a[3]),"l"(e),"n"(SC));
}
template <int SC> __device__ __forceinline__ void wl_rs_n64_t0(float* d, const uint32_t* a, uint64_t e) {
  asm volatile("wgmma.mma_async.sync.aligned.m64n64k16.f32.bf16.bf16 {%0,%1,%2,%3,%4,%5,%6,%7,%8,%9,%10,%11,%12,%13,%14,%15,%16,%17,%18,%19,%20,%21,%22,%23,%24,%25,%26,%27,%28,%29,%30,%31}, {%32,%33,%34,%35}, %36, %37,1,1,0;"
  : "+f"(d[0]),"+f"(d[1]),"+f"(d[2]),"+f"(d[3]),"+f"(d[4]),"+f"(d[5]),"+f"(d[6]),"+f"(d[7]),"+f"(d[8]),"+f"(d[9]),"+f"(d[10]),"+f"(d[11]),"+f"(d[12]),"+f"(d[13]),"+f"(d[14]),"+f"(d[15]),"+f"(d[16]),"+f"(d[17]),"+f"(d[18]),"+f"(d[19]),"+f"(d[20]),"+f"(d[21]),"+f"(d[22]),"+f"(d[23]),"+f"(d[24]),"+f"(d[25]),"+f"(d[26]),"+f"(d[27]),"+f"(d[28]),"+f"(d[29]),"+f"(d[30]),"+f"(d[31]) : "r"(a[0]),"r"(a[1]),"r"(a[2]),"r"(a[3]),"l"(e),"n"(SC));
}
template <int SC> __device__ __forceinline__ void wl_rs_n64_t1(float* d, const uint32_t* a, uint64_t e) {
  asm volatile("wgmma.mma_async.sync.aligned.m64n64k16.f32.bf16.bf16 {%0,%1,%2,%3,%4,%5,%6,%7,%8,%9,%10,%11,%12,%13,%14,%15,%16,%17,%18,%19,%20,%21,%22,%23,%24,%25,%26,%27,%28,%29,%30,%31}, {%32,%33,%34,%35}, %36, %37,1,1,1;"
  : "+f"(d[0]),"+f"(d[1]),"+f"(d[2]),"+f"(d[3]),"+f"(d[4]),"+f"(d[5]),"+f"(d[6]),"+f"(d[7]),"+f"(d[8]),"+f"(d[9]),"+f"(d[10]),"+f"(d[11]),"+f"(d[12]),"+f"(d[13]),"+f"(d[14]),"+f"(d[15]),"+f"(d[16]),"+f"(d[17]),"+f"(d[18]),"+f"(d[19]),"+f"(d[20]),"+f"(d[21]),"+f"(d[22]),"+f"(d[23]),"+f"(d[24]),"+f"(d[25]),"+f"(d[26]),"+f"(d[27]),"+f"(d[28]),"+f"(d[29]),"+f"(d[30]),"+f"(d[31]) : "r"(a[0]),"r"(a[1]),"r"(a[2]),"r"(a[3]),"l"(e),"n"(SC));
}
template <int SC> __device__ __forceinline__ void wl_rs_n88_t1(float* d, const uint32_t* a, uint64_t e) {
  asm volatile("wgmma.mma_async.sync.aligned.m64n88k16.f32.bf16.bf16 {%0,%1,%2,%3,%4,%5,%6,%7,%8,%9,%10,%11,%12,%13,%14,%15,%16,%17,%18,%19,%20,%21,%22,%23,%24,%25,%26,%27,%28,%29,%30,%31,%32,%33,%34,%35,%36,%37,%38,%39,%40,%41,%42,%43}, {%44,%45,%46,%47}, %48, %49,1,1,1;"
  : "+f"(d[0]),"+f"(d[1]),"+f"(d[2]),"+f"(d[3]),"+f"(d[4]),"+f"(d[5]),"+f"(d[6]),"+f"(d[7]),"+f"(d[8]),"+f"(d[9]),"+f"(d[10]),"+f"(d[11]),"+f"(d[12]),"+f"(d[13]),"+f"(d[14]),"+f"(d[15]),"+f"(d[16]),"+f"(d[17]),"+f"(d[18]),"+f"(d[19]),"+f"(d[20]),"+f"(d[21]),"+f"(d[22]),"+f"(d[23]),"+f"(d[24]),"+f"(d[25]),"+f"(d[26]),"+f"(d[27]),"+f"(d[28]),"+f"(d[29]),"+f"(d[30]),"+f"(d[31]),"+f"(d[32]),"+f"(d[33]),"+f"(d[34]),"+f"(d[35]),"+f"(d[36]),"+f"(d[37]),"+f"(d[38]),"+f"(d[39]),"+f"(d[40]),"+f"(d[41]),"+f"(d[42]),"+f"(d[43]) : "r"(a[0]),"r"(a[1]),"r"(a[2]),"r"(a[3]),"l"(e),"n"(SC));
}

#define POLY_MASK 0xB5u
#define QSCALE (0.23570226039551584f * 1.4426950408889634f)

#define NSTG 6
#define STG_BYTES 16384
#define R_BYTES (8 * 16384)
#define GEMM_SMEM (R_BYTES + NSTG * STG_BYTES + 3072)

__device__ __forceinline__ void load_a_chunk(uint32_t (*a)[4], uint32_t chunk_base, int row_in_tile, int lane) {
  const int r = row_in_tile + (lane & 7) + ((lane >> 3) & 1) * 8;
  const uint32_t rb = chunk_base + r * 128;
#pragma unroll
  for (int k = 0; k < 4; k++) ldsm4(a[k], rb + (((k * 2 + (lane >> 4)) ^ (r & 7)) << 4));
}

#define MMA_TILE(FN, ODD, pj)                                                   \
  {                                                                             \
    uint32_t rb_ = RING >> 4;                                                   \
    asm volatile("" : "+r"(rb_));                                               \
    const uint64_t db = mkdesc(0, 8192, 1024, 1) + (uint32_t)__shfl_sync(~0u, rb_, 0); \
    _Pragma("unroll") for (int s = 0; s < 9; s++) {                             \
      const int g_ = 1 + (ODD) * 9 + s, st_ = g_ % NSTG;                        \
      mbar_wait(full + st_ * 8, (pj) ^ ((g_ / NSTG) & 1));                      \
      WG_FENCE();                                                               \
      if (s == 0) FN<0>(acc, a[0], db + st_ * 1024); else FN<1>(acc, a[s * 4], db + st_ * 1024); \
      _Pragma("unroll") for (int k = 1; k < 4; k++) FN<1>(acc, a[s * 4 + k], db + st_ * 1024 + k * 128); \
      WG_COMMIT();                                                              \
      if (s > 0) { WG_WAIT(1); if (lane == 0) mbar_arrive(empty + ((g_ - 1) % NSTG) * 8); } \
    }                                                                           \
    WG_WAIT(0);                                                                 \
    if (lane == 0) mbar_arrive(empty + ((9 + (ODD) * 9) % NSTG) * 8);           \
  }

template <int NG, int G0>
__device__ __forceinline__ void qkv_stage(const float* acc, uint32_t stg, int rowl, int cq, int col_base) {
  const float vs0 = ((POLY_MASK >> ((rowl >> 3) & 7)) & 1) ? 0.5f : 1.0f, vs1 = ((POLY_MASK >> (((rowl >> 3) + 1) & 7)) & 1) ? 0.5f : 1.0f;
#pragma unroll
  for (int i = 0; i < NG; i++) {
    const int cc = (G0 + i) * 8 + cq * 2;
    const int slot = (cc * 3641) >> 16, d = cc - slot * 18;
    const int gc = col_base + cc;
    const float sc0 = gc < DM ? QSCALE : (gc < 2 * DM ? vs0 : 1.0f), sc1 = gc < DM ? QSCALE : (gc < 2 * DM ? vs1 : 1.0f);
    const uint32_t ad = stg + slot * 6144 + (d >> 3) * 128 + (d & 7) * 2 + (rowl >> 3) * 384 + (rowl & 7) * 16;
    asm volatile("st.shared.b32 [%0],%1;" ::"r"(ad), "r"(pack_bf16(acc[4 * i] * sc0, acc[4 * i + 1] * sc0)) : "memory");
    asm volatile("st.shared.b32 [%0],%1;" ::"r"(ad + 384), "r"(pack_bf16(acc[4 * i + 2] * sc1, acc[4 * i + 3] * sc1)) : "memory");
  }
}

__device__ __forceinline__ float silu_bf(__nv_bfloat16 c) {
  const float v = __bfloat162float(c);
  return rbf(v / (1.0f + __expf(-v)));
}
__device__ __forceinline__ void fma8(float* acc, float sv, const uint4& w) {
  acc[0] += sv * bf_lo(w.x); acc[1] += sv * bf_hi(w.x); acc[2] += sv * bf_lo(w.y); acc[3] += sv * bf_hi(w.y);
  acc[4] += sv * bf_lo(w.z); acc[5] += sv * bf_hi(w.z); acc[6] += sv * bf_lo(w.w); acc[7] += sv * bf_hi(w.w);
}
__device__ __forceinline__ int tab_pos(int col, int shift) {
  return (((col >> 4) * 4 + ((col & 7) >> 1)) * 4 + ((col >> 3) & 1) * 2 + shift) * 2 + (col & 1);
}
__device__ __forceinline__ float knorm_row(uint32_t slot, int row) {
  const uint32_t ad = slot + (row >> 3) * 384 + (row & 7) * 16;
  const uint4 u = lds128(ad), v = lds128(ad + 128);
  uint32_t w;
  asm volatile("ld.shared.b32 %0,[%1];" : "=r"(w) : "r"(ad + 256) : "memory");
  float q = sq2(u.x) + sq2(u.y) + sq2(u.z) + sq2(u.w) + sq2(v.x) + sq2(v.y) + sq2(v.z) + sq2(v.w) + sq2(w);
  if ((POLY_MASK >> ((row >> 3) & 7)) & 1) q *= 4.0f;
  return q == q ? q : __int_as_float(0x7f800000);
}

__global__ void __launch_bounds__(384, 1) k1_kernel(const __grid_constant__ CUtensorMap mx, const __grid_constant__ CUtensorMap mw,
                                                    const __nv_bfloat16* __restrict__ cvec, const __nv_bfloat16* __restrict__ wmod) {
  extern __shared__ __align__(1024) uint8_t smem_raw[];
  const uint32_t sb = s2u(smem_raw);
  const uint32_t R = sb, RING = sb + R_BYTES, BAR = RING + NSTG * STG_BYTES, TAB = BAR + 512;
  const uint32_t full = BAR, empty = BAR + 64, xfull = BAR + 128;
  const int tid = threadIdx.x, lane = tid & 31, warp = tid >> 5;
  const int mb = blockIdx.x >> 3, nb = blockIdx.x & 7;
  if (tid == 0) TS(1, 0);
  if (blockIdx.x >= 128) {
    pdl_launch();
    float* sf = (float*)smem_raw;
    const int part = blockIdx.x - 126;
    for (int i = tid; i < DM; i += 384) sf[i] = silu_bf(cvec[i]);
    if (part == 2 && tid < 80) g_cnt[tid] = 0;
    __syncthreads();
    if (tid < 288) {
      const int cg = tid % 72, rg = tid / 72;
      const __nv_bfloat16* w = wmod + (size_t)rg * 144 * 3456 + part * DM + cg * 8;
      float acc[8] = {0, 0, 0, 0, 0, 0, 0, 0};
#pragma unroll 1
      for (int r = 0; r < 144; r += 16) {
        uint4 v[16];
#pragma unroll
        for (int i = 0; i < 16; i++) v[i] = __ldg((const uint4*)(w + (size_t)(r + i) * 3456));
#pragma unroll
        for (int i = 0; i < 16; i++) fma8(acc, sf[rg * 144 + r + i], v[i]);
      }
#pragma unroll
      for (int j = 0; j < 8; j++) sf[DM + rg * DM + cg * 8 + j] = acc[j];
    }
    __syncthreads();
    for (int col = tid; col < DM; col += 384) {
      const float v = rbf(sf[DM + col] + sf[2 * DM + col] + sf[3 * DM + col] + sf[4 * DM + col]);
      if (part == 2) g_ga[col] = __float2bfloat16_rn(v);
      else if (part == 5) g_gb[col] = __float2bfloat16_rn(v);
      else ((__nv_bfloat16*)g_tab2)[tab_pos(col, part == 3)] = __float2bfloat16_rn(0.5f * (part == 3 ? v : rbf(1.0f + v)));
    }
    if (tid == 0) TS(1, 15);
    return;
  }
  uint4 w[9];
  float sv[9];
  if (blockIdx.x < 36 && tid < 256) {
#pragma unroll
    for (int i = 0; i < 9; i++) w[i] = __ldg((const uint4*)(wmod + (size_t)((tid >> 2) + 64 * i) * 3456 + blockIdx.x * 32 + (tid & 3) * 8));
#pragma unroll
    for (int i = 0; i < 9; i++) sv[i] = __bfloat162float(cvec[(tid >> 2) + 64 * i]);
  }
  if (tid == 256) {
    if (sb & 1023) __trap();
    for (int i = 0; i < NSTG; i++) { mbar_init(full + i * 8, 1); mbar_init(empty + i * 8, 8); }
    for (int i = 0; i < 8; i++) mbar_init(xfull + i * 8, 1);
    fence_bar_init();
    for (int c = 0; c < 8; c++) { mbar_expect(xfull + c * 8, 16384); tma2d(R + c * 16384, &mx, c * 64, mb * 128, xfull + c * 8); }
    mbar_expect(full, 16384);
    tma2d(RING, &mx, 512, mb * 128, full);
  }
  __syncthreads();
  pdl_launch();
  if (warp >= 8) {
    REG_DEC(24);
    if (warp == 8) {
      if (lane == 0) {
        int st = 1; uint32_t ph = 0;
        for (int it = 0; it < 18; it++) {
          const int t = it / 9, s = it - t * 9;
          mbar_wait(empty + st * 8, ph ^ 1);
          mbar_expect(full + st * 8, 16384);
          tma2d(RING + st * STG_BYTES, &mw, nb * 216 + t * 128, s * 64, full + st * 8);
          tma2d(RING + st * STG_BYTES + 8192, &mw, nb * 216 + t * 128 + 64, s * 64, full + st * 8);
          if (++st == NSTG) { st = 0; ph ^= 1; }
        }
      }
    } else {
      const int ht = tid - 288;
      bar_sync(1, 352);
      for (int i = ht; i < 12 * 128; i += 96) {
        const int slot = i >> 7, row = i & 127, type = (nb * 12 + slot) >> 5;
        uint32_t v = 0;
        if (type == 1) v = ((POLY_MASK >> ((row >> 3) & 7)) & 1) ? 0x43403F00u : 0x40253F80u;
        if (type == 2) v = 0x3F80u;
        const uint32_t ad = R + slot * 6144 + (row >> 3) * 384 + 256 + (row & 7) * 16;
        asm volatile("st.shared.b32 [%0],%1;" ::"r"(ad + 4), "r"(v) : "memory");
        asm volatile("st.shared.v2.b32 [%0],{%1,%1};" ::"r"(ad + 8), "r"(0) : "memory");
      }
      fence_async_smem();
      bar_sync(2, 352);
      if (ht == 0) {
        for (int s = 0; s < 7; s++) bulk_s2g(g_qkv + (size_t)(nb * 12 + s) * 98304 + mb * 6144, R + s * 6144, 6144);
        bulk_commit();
      }
      for (int s = warp - 9; s < 7; s += 3) {
        const int gs = nb * 12 + s;
        if ((gs >> 5) != 1) continue;
        float mx2 = 0;
#pragma unroll 1
        for (int row = lane; row < 128; row += 32) mx2 = fmaxf(mx2, knorm_row(R + s * 6144, row));
#pragma unroll
        for (int o = 16; o; o >>= 1) mx2 = fmaxf(mx2, __shfl_xor_sync(~0u, mx2, o));
        if (lane == 0) g_kmax[(gs & 31) * 16 + mb] = mx2;
      }
      if (ht == 0) bulk_wait0();
    }
  } else {
    REG_INC(240);
    if (blockIdx.x < 36) {
      float acc[8] = {0, 0, 0, 0, 0, 0, 0, 0};
#pragma unroll
      for (int i = 0; i < 9; i++) fma8(acc, rbf(sv[i] / (1.0f + __expf(-sv[i]))), w[i]);
#pragma unroll
      for (int j = 0; j < 8; j++) {
        acc[j] += __shfl_xor_sync(~0u, acc[j], 4);
        acc[j] += __shfl_xor_sync(~0u, acc[j], 8);
        acc[j] += __shfl_xor_sync(~0u, acc[j], 16);
      }
      float* red = (float*)(smem_raw + (TAB - sb));
      if (lane < 4) {
#pragma unroll
        for (int j = 0; j < 8; j++) red[warp * 32 + lane * 8 + j] = acc[j];
      }
      bar_sync(4, 256);
      if (tid < 32) {
        float v = 0;
#pragma unroll
        for (int j = 0; j < 8; j++) v += red[j * 32 + tid];
        v = rbf(v);
        const int n = blockIdx.x * 32 + tid, shift = n < DM;
        const uint32_t word = pack_bf16(shift ? v : 1.0f + v, 1.0f);
        asm volatile("st.relaxed.gpu.global.u32 [%0],%1;" ::"l"((uint32_t*)g_ll + tab_pos(shift ? n : n - DM, shift)), "r"(word) : "memory");
      }
      bar_sync(4, 256);
    }
    TSS(0);
    uint32_t a[36][4];
    const int rowl = warp * 16;
    uint4 s0, s1;
    {
      RowStat rs;
      rs.init();
#pragma unroll
      for (int c = 0; c < 9; c++) {
        mbar_wait(c < 8 ? xfull + c * 8 : full, 0);
        load_a_chunk(&a[c * 4], R + c * 16384, rowl, lane);
#pragma unroll
        for (int k = 0; k < 4; k++) rs.add(a[c * 4 + k]);
      }
      if (lane == 0) mbar_arrive(empty);
      bar_arrive(1, 352);
      rs.finish(lane, s0, s1);
    }
    TSS(1);
    if (tid < 144) {
      uint4 u, v;
      int n = 0;
      do {
        asm volatile("ld.relaxed.gpu.global.v4.u32 {%0,%1,%2,%3},[%4];" : "=r"(u.x), "=r"(u.y), "=r"(u.z), "=r"(u.w) : "l"(g_ll + tid * 2) : "memory");
        asm volatile("ld.relaxed.gpu.global.v4.u32 {%0,%1,%2,%3},[%4];" : "=r"(v.x), "=r"(v.y), "=r"(v.z), "=r"(v.w) : "l"(g_ll + tid * 2 + 1) : "memory");
        if (++n > 4000000) __trap();
      } while (((u.x & u.y & u.z & u.w & v.x & v.y & v.z & v.w) >> 16) != 0x3F80u);
      sts128(TAB + tid * 16, make_uint4(__byte_perm(u.x, u.y, 0x5410), __byte_perm(u.z, u.w, 0x5410), __byte_perm(v.x, v.y, 0x5410), __byte_perm(v.z, v.w, 0x5410)));
    }
    bar_sync(4, 256);
    TSS(2);
    LN_APPLY_ALL();
    float acc[64];
    TSS(3);
    MMA_TILE(wl_rs_n128_t1, 0, 0);
    qkv_stage<16, 0>(acc, R, rowl + (lane >> 2), lane & 3, nb * 216);
    fence_async_smem();
    bar_arrive(2, 352);
    TSS(4);
    MMA_TILE(wl_rs_n88_t1, 1, 0);
    qkv_stage<11, 16>(acc, R, rowl + (lane >> 2), lane & 3, nb * 216);
    fence_async_smem();
    bar_sync(4, 256);
    TSS(5);
    if (tid == 0) {
      for (int s = 7; s < 12; s++) bulk_s2g(g_qkv + (size_t)(nb * 12 + s) * 98304 + mb * 6144, R + s * 6144, 6144);
      bulk_commit();
    }
    if (warp >= 3 && ((nb * 12 + 4 + warp) >> 5) == 1) {
      float mx2 = 0;
#pragma unroll
      for (int i = 0; i < 4; i++) mx2 = fmaxf(mx2, knorm_row(R + (4 + warp) * 6144, lane + 32 * i));
#pragma unroll
      for (int o = 16; o; o >>= 1) mx2 = fmaxf(mx2, __shfl_xor_sync(~0u, mx2, o));
      if (lane == 0) g_kmax[((nb * 12 + 4 + warp) & 31) * 16 + mb] = mx2;
    }
    if (tid == 0) bulk_wait0();
    TSS(6);
    TSDUMP(1);
  }
}

#define ATT_SMEM (2 * 98304 + 1024 + 256)

__device__ __forceinline__ uint32_t exp2_pair_fma(float t0, float t1) {
  uint32_t y;
  asm("prmt.b32 %0,%1,%2,0x6521;" : "=r"(y) : "r"(__float_as_uint(t0)), "r"(__float_as_uint(t1)));
  return hfma2(y, y | 0x3F803F80u, y | 0x007F007Fu);
}

__device__ __forceinline__ void softmax_fast(const float* s, uint32_t* p) {
#pragma unroll
  for (int i = 0; i < 8; i++) {
    if ((POLY_MASK >> i) & 1) {
      p[2 * i] = exp2_pair_fma(s[4 * i], s[4 * i + 1]);
      p[2 * i + 1] = exp2_pair_fma(s[4 * i + 2], s[4 * i + 3]);
    } else {
      p[2 * i] = pack_bf16(ex2f(s[4 * i]), ex2f(s[4 * i + 1]));
      p[2 * i + 1] = pack_bf16(ex2f(s[4 * i + 2]), ex2f(s[4 * i + 3]));
    }
  }
}
#define QK_MMA(S, kd)                                                           \
  wl_rs_n64_t0<0>(S, q, (kd));                                                  \
  wl_rs_n64_t0<1>(S, q + 4, (kd) + 16 - (8ull << 16));
#define PV_MMA(P, vd)                                                           \
  _Pragma("unroll") for (int t = 0; t < 4; t++) wl_rs_n24_t1<1>(o, P + 4 * t, (vd) + t * 48);

__device__ __forceinline__ void att_store(const float* o, int row0, int head, int lane) {
  const int cq = lane & 3;
  const float l0 = __shfl_sync(~0u, o[8], (lane & ~3) | 1), l1 = __shfl_sync(~0u, o[10], (lane & ~3) | 1);
  const float i0 = rcp_fast(l0), i1 = rcp_fast(l1);
  uint32_t* og = (uint32_t*)(g_o + (size_t)row0 * DM + head * 18 + cq * 2);
  og[0] = pack_bf16(o[0] * i0, o[1] * i0);
  og[4] = pack_bf16(o[4] * i0, o[5] * i0);
  og[8 * DM / 2] = pack_bf16(o[2] * i1, o[3] * i1);
  og[8 * DM / 2 + 4] = pack_bf16(o[6] * i1, o[7] * i1);
  if (cq == 0) {
    og[8] = pack_bf16(o[8] * i0, o[9] * i0);
    og[8 * DM / 2 + 8] = pack_bf16(o[10] * i1, o[11] * i1);
  }
}

__global__ void __launch_bounds__(512, 1) k2_kernel(const uint8_t* __restrict__ wo, const uint8_t* __restrict__ wg_, const uint8_t* __restrict__ wu,
                                                    const uint8_t* __restrict__ wd) {
  extern __shared__ __align__(1024) uint8_t smem_raw[];
  const uint32_t sb = (s2u(smem_raw) + 1023) & ~1023u;
  const uint32_t KS = sb, VS = sb + 98304, BAR = sb + 2 * 98304;
  const int tid = threadIdx.x, lane = tid & 31, warp = tid >> 5, wg = tid >> 7;
  const int head = blockIdx.x >> 2, qb = blockIdx.x & 3;
  if (tid == 0) {
    TS(2, 0);
    for (int i = 0; i < 16; i++) mbar_init(BAR + i * 8, 1);
    fence_bar_init();
  }
  __syncthreads();
  const int g = lane >> 2, cq = lane & 3;
  const int row0 = qb * 512 + wg * 128 + (warp & 3) * 16 + g;
  const uint8_t* qg = g_qkv + (size_t)head * 98304 + (row0 >> 3) * 384 + (row0 & 7) * 16 + cq * 4;
  pdl_wait();
  pdl_launch();
  if (blockIdx.x == 0 && tid < 288) g_ll[tid] = make_uint4(0, 0, 0, 0);
  if (tid == 0) TS(2, 1);
  const uint8_t* kg = g_qkv + (size_t)(32 + head) * 98304;
#define KV_LOAD(c) { mbar_expect(BAR + (c) * 8, 12288); bulk_g2s(KS + (c) * 6144, kg + (c) * 6144, 6144, BAR + (c) * 8); \
                     bulk_g2s(VS + (c) * 6144, kg + 32 * 98304 + (c) * 6144, 6144, BAR + (c) * 8); }
  if (lane == 0 && warp < 5) KV_LOAD(warp);
  __syncwarp();
  uint32_t q[8], q2[6];
  float kmax2 = __ldcg(g_kmax + head * 16 + (lane & 15));
#pragma unroll
  for (int i = 0; i < 6; i++) {
    q[i] = __ldcg((const uint32_t*)(qg + (i & 1) * 384 + (i >> 1) * 128));
    q2[i] = __ldcg((const uint32_t*)(qg + 3072 + (i & 1) * 384 + (i >> 1) * 128));
  }
  q[6] = __ldcg((const uint32_t*)(qg + 256 + 12 - cq * 4)); q[7] = __ldcg((const uint32_t*)(qg + 256 + 8 - cq * 4));
  const uint64_t dk = mkdesc(KS, 128, 384, 0), dv = mkdesc(VS, 384, 128, 0);
#pragma unroll
  for (int o = 8; o; o >>= 1) kmax2 = fmaxf(kmax2, __shfl_xor_sync(~0u, kmax2, o));
  float bd[4] = {sq2(q[0]) + sq2(q[2]) + sq2(q[4]), sq2(q[1]) + sq2(q[3]) + sq2(q[5]),
                 sq2(q2[0]) + sq2(q2[2]) + sq2(q2[4]), sq2(q2[1]) + sq2(q2[3]) + sq2(q2[5])};
  int ok = 1;
  if (tid == 0 && bd[0] + bd[3] + kmax2 != 1.2345f) TS(2, 5);
#pragma unroll
  for (int i = 0; i < 4; i++) {
    bd[i] += __shfl_xor_sync(~0u, bd[i], 1); bd[i] += __shfl_xor_sync(~0u, bd[i], 2);
    bd[i] = sqrt_fast(bd[i] * kmax2) * 1.01f + 1.0f;
    ok = ok && (bd[i] <= 62.0f);
  }
  {
    uint32_t all;
    asm volatile("{.reg .pred p,q; setp.ne.b32 p,%1,0; barrier.red.and.pred q,1,512,p; selp.u32 %0,1,0,q;}"
                 : "=r"(all) : "r"(ok) : "memory");
    ok = __all_sync(~0u, all);
  }
  float o[12];
#pragma unroll
  for (int i = 0; i < 12; i++) { o[i] = 0.f; asm volatile("" : "+f"(o[i])); }
  float s[32];
  uint32_t p[16];
  if (tid == 0) TS(2, 2);
  if (ok) {
    if (cq == 1) {
      q[4] = pack_bf16(-bd[0], 1.0f); q[5] = pack_bf16(-bd[1], 1.0f);
      q2[4] = pack_bf16(-bd[2], 1.0f); q2[5] = pack_bf16(-bd[3], 1.0f);
    }
    mbar_wait(BAR, 0);
    WG_FENCE();
    QK_MMA(s, dk);
    WG_COMMIT();
#pragma unroll 1
    for (int tile = 0; tile < 2; tile++) {
#pragma unroll 1
      for (int jj = 0; jj < 8; jj++) {
        const uint64_t kd = dk + (uint32_t)(jj * 768), vd = dv + (uint32_t)(jj * 768), kn = dk + (uint32_t)(((jj + 1) & 7) * 768);
        if (tile == 0) {
          if (lane == 0 && warp < 2 && 2 * jj + 5 + warp < 16) KV_LOAD(2 * jj + 5 + warp);
          if (lane == 0 && warp >= 4 && warp < 8) {
            const uint8_t* w = warp == 4 ? wg_ : warp == 5 ? wu : warp == 6 ? wd : wo;
            const uint32_t n = warp == 7 ? 656 : 5184, o_ = (blockIdx.x * 8 + jj) * n;
            if (warp < 7 || o_ + n <= DM * DM * 2) asm volatile("cp.async.bulk.prefetch.L2.global [%0],%1;" ::"l"(w + o_), "r"(n) : "memory");
          }
          __syncwarp();
          mbar_wait(BAR + jj * 16 + 8, 0); mbar_wait(BAR + ((jj * 16 + 16) & 127), 0); if (tid == 0) TS(2, 8 + jj); }
#pragma unroll
        for (int u = 0; u < 4; u++) {
          WG_WAIT(0);
          fence_regs<32>(s);
          softmax_fast(s, p);
          if (u == 3 && jj == 7) {
#pragma unroll
            for (int i = 0; i < 6; i++) q[i] = q2[i];
          }
          WG_FENCE();
          PV_MMA(p, vd + u * 192);
          QK_MMA(s, u < 3 ? kd + u * 192 + 192 : kn);
          WG_COMMIT();
        }
      }
      WG_WAIT(0);
      fence_regs<12>(o);
      att_store(o, row0 + tile * 64, head, lane);
#pragma unroll
      for (int i = 0; i < 12; i++) o[i] = 0.f;
      fence_regs<12>(o);
      if (tid == 0 && tile == 0) TS(2, 3);
    }
  } else {
    if (lane == 0 && warp >= 5) KV_LOAD(warp);
    __syncwarp();
#pragma unroll 1
    for (int tile = 0; tile < 2; tile++) {
      float m0 = -INFINITY, m1 = -INFINITY;
#pragma unroll 1
      for (int j = 0; j < 32; j++) {
        mbar_wait(BAR + (j >> 1) * 8, 0);
        WG_FENCE();
        QK_MMA(s, dk + (uint32_t)(j * 192));
        WG_COMMIT();
        WG_WAIT(0);
        fence_regs<32>(s);
#pragma unroll
        for (int i = 0; i < 32; i++) if ((POLY_MASK >> (i >> 2)) & 1) s[i] *= 2.0f;
        float x0 = m0, x1 = m1;
#pragma unroll
        for (int i = 0; i < 8; i++) {
          x0 = fmaxf(x0, fmaxf(s[4 * i], s[4 * i + 1]));
          x1 = fmaxf(x1, fmaxf(s[4 * i + 2], s[4 * i + 3]));
        }
        x0 = fmaxf(x0, __shfl_xor_sync(~0u, x0, 1)); x0 = fmaxf(x0, __shfl_xor_sync(~0u, x0, 2));
        x1 = fmaxf(x1, __shfl_xor_sync(~0u, x1, 1)); x1 = fmaxf(x1, __shfl_xor_sync(~0u, x1, 2));
        const float c0 = ex2f(m0 - x0), c1 = ex2f(m1 - x1);
        m0 = x0; m1 = x1;
#pragma unroll
        for (int i = 0; i < 3; i++) { o[4 * i] *= c0; o[4 * i + 1] *= c0; o[4 * i + 2] *= c1; o[4 * i + 3] *= c1; }
#pragma unroll
        for (int i = 0; i < 8; i++) {
          p[2 * i] = pack_bf16(ex2f(s[4 * i] - x0), ex2f(s[4 * i + 1] - x0));
          p[2 * i + 1] = pack_bf16(ex2f(s[4 * i + 2] - x1), ex2f(s[4 * i + 3] - x1));
        }
        WG_FENCE();
        PV_MMA(p, dv + (uint32_t)(j * 192));
        WG_COMMIT();
        WG_WAIT(0);
        fence_regs<12>(o);
      }
      att_store(o, row0 + tile * 64, head, lane);
#pragma unroll
      for (int i = 0; i < 12; i++) o[i] = 0.f;
#pragma unroll
      for (int i = 0; i < 6; i++) q[i] = q2[i];
    }
  }
  if (tid == 0) TS(2, 4);
}

#define K3_NSTG 4
#define K3_SMEM (9 * 16384 + K3_NSTG * 16384 + 1024 + 256)
__global__ void __launch_bounds__(288, 1) k3_kernel(const __grid_constant__ CUtensorMap mo, const __grid_constant__ CUtensorMap mw,
                                                    const __nv_bfloat16* __restrict__ x) {
  extern __shared__ __align__(1024) uint8_t smem_raw[];
  const uint32_t sb = (s2u(smem_raw) + 1023) & ~1023u;
  const uint32_t A = sb, RING = sb + 9 * 16384, BAR = RING + K3_NSTG * 16384;
  const uint32_t full = BAR, empty = BAR + 64, afull = BAR + 128;
  const int tid = threadIdx.x, lane = tid & 31, warp = tid >> 5;
  const int mb = blockIdx.x >> 3, nb = blockIdx.x & 7;
  if (tid == 0) {
    TS(3, 0);
    for (int i = 0; i < K3_NSTG; i++) { mbar_init(full + i * 8, 1); mbar_init(empty + i * 8, 8); }
    for (int i = 0; i < 9; i++) mbar_init(afull + i * 8, 1);
    fence_bar_init();
  }
  __syncthreads();
  pdl_launch();
  if (warp == 8) {
    if (lane == 0) {
      for (int s = 0; s < K3_NSTG; s++) {
        mbar_expect(full + s * 8, 16384);
        tma2d(RING + s * 16384, &mw, nb * 72, s * 64, full + s * 8);
        tma2d(RING + s * 16384 + 8192, &mw, nb * 72 + 64, s * 64, full + s * 8);
      }
      pdl_wait();
      for (int c = 0; c < 9; c++) { mbar_expect(afull + c * 8, 16384); tma2d(A + c * 16384, &mo, c * 64, mb * 128, afull + c * 8); }
      for (int s = K3_NSTG; s < 9; s++) {
        const int st = s % K3_NSTG;
        mbar_wait(empty + st * 8, ((s / K3_NSTG) & 1) ^ 1);
        mbar_expect(full + st * 8, 16384);
        tma2d(RING + st * 16384, &mw, nb * 72, s * 64, full + st * 8);
        tma2d(RING + st * 16384 + 8192, &mw, nb * 72 + 64, s * 64, full + st * 8);
      }
    }
  } else {
    const int g = lane >> 2, cq = lane & 3;
    const int row = mb * 128 + warp * 16 + g, col = nb * 72 + cq * 2;
    uint32_t xv[18];
#pragma unroll
    for (int i = 0; i < 9; i++) {
      xv[2 * i] = __ldg((const uint32_t*)(x + (size_t)row * DM + col + 8 * i));
      xv[2 * i + 1] = __ldg((const uint32_t*)(x + (size_t)(row + 8) * DM + col + 8 * i));
    }
    pdl_wait();
    if (tid == 0) TS(3, 1);
    float2 ga[9];
#pragma unroll
    for (int i = 0; i < 9; i++) { const uint32_t t = *(const uint32_t*)(g_ga + col + 8 * i); ga[i] = make_float2(bf_lo(t), bf_hi(t)); }
    float acc[36];
    const uint32_t abase = A + (warp >> 2) * 8192;
#pragma unroll
    for (int s = 0; s < 9; s++) {
      const int st = s % K3_NSTG;
      mbar_wait(afull + s * 8, 0);
      mbar_wait(full + st * 8, (s / K3_NSTG) & 1);
      WG_FENCE();
#pragma unroll
      for (int k = 0; k < 4; k++)
        wg_ss_n72_t1(acc, mkdesc(abase + s * 16384 + k * 32, 16, 1024, 1), mkdesc(RING + st * 16384 + k * 2048, 8192, 1024, 1), (s | k) != 0);
      WG_COMMIT();
      if (s > 0) { WG_WAIT(1); if (lane == 0) mbar_arrive(empty + ((s - 1) % K3_NSTG) * 8); }
    }
    WG_WAIT(0);
    if (tid == 0) TS(3, 2);
    float s0 = 0, s1 = 0;
#pragma unroll
    for (int i = 0; i < 9; i++) {
      acc[4 * i] = rbf(bf_lo(xv[2 * i]) + rbf(ga[i].x * rbf(acc[4 * i])));
      acc[4 * i + 1] = rbf(bf_hi(xv[2 * i]) + rbf(ga[i].y * rbf(acc[4 * i + 1])));
      acc[4 * i + 2] = rbf(bf_lo(xv[2 * i + 1]) + rbf(ga[i].x * rbf(acc[4 * i + 2])));
      acc[4 * i + 3] = rbf(bf_hi(xv[2 * i + 1]) + rbf(ga[i].y * rbf(acc[4 * i + 3])));
      *(uint32_t*)(g_x1 + (size_t)row * DM + col + 8 * i) = pack_bf16(acc[4 * i], acc[4 * i + 1]);
      *(uint32_t*)(g_x1 + (size_t)(row + 8) * DM + col + 8 * i) = pack_bf16(acc[4 * i + 2], acc[4 * i + 3]);
      s0 += acc[4 * i] + acc[4 * i + 1];
      s1 += acc[4 * i + 2] + acc[4 * i + 3];
    }
    s0 += __shfl_xor_sync(~0u, s0, 1); s0 += __shfl_xor_sync(~0u, s0, 2);
    s1 += __shfl_xor_sync(~0u, s1, 1); s1 += __shfl_xor_sync(~0u, s1, 2);
    const float m0 = s0 * (1.0f / 72), m1 = s1 * (1.0f / 72);
    float q0 = 0, q1 = 0;
#pragma unroll
    for (int i = 0; i < 9; i++) {
      q0 += (acc[4 * i] - m0) * (acc[4 * i] - m0) + (acc[4 * i + 1] - m0) * (acc[4 * i + 1] - m0);
      q1 += (acc[4 * i + 2] - m1) * (acc[4 * i + 2] - m1) + (acc[4 * i + 3] - m1) * (acc[4 * i + 3] - m1);
    }
    q0 += __shfl_xor_sync(~0u, q0, 1); q0 += __shfl_xor_sync(~0u, q0, 2);
    q1 += __shfl_xor_sync(~0u, q1, 1); q1 += __shfl_xor_sync(~0u, q1, 2);
    if (cq == 0) {
      g_stat2[row * 8 + nb] = make_float2(m0, q0);
      g_stat2[(row + 8) * 8 + nb] = make_float2(m1, q1);
    }
    if (tid == 0) TS(3, 3);
  }
}

__device__ __forceinline__ uint4 ln2_consts(int row, int cq) {
  const float4 p = *(const float4*)(g_stat2 + row * 8 + cq * 2);
  float s = p.x + p.z;
  s += __shfl_xor_sync(~0u, s, 1); s += __shfl_xor_sync(~0u, s, 2);
  const float mean = s * 0.125f;
  float q = p.y + p.w + 72.0f * ((p.x - mean) * (p.x - mean) + (p.z - mean) * (p.z - mean));
  q += __shfl_xor_sync(~0u, q, 1); q += __shfl_xor_sync(~0u, q, 2);
  return ln_consts(mean, q * (1.0f / DM));
}
__device__ __forceinline__ uint32_t glu_pair(float g0, float g1, float u0, float u1) {
  return pack_bf16(fmaf(tanhf_fast(g0), u0, u0), fmaf(tanhf_fast(g1), u1, u1));
}
template <int NG>
__device__ __forceinline__ void stage_part(const float* acc, uint32_t stg, int lane) {
  const int r = (lane & 7) + ((lane >> 3) & 1) * 8;
#pragma unroll
  for (int i = 0; i < NG; i += 2) {
    const int ch = i + (lane >> 4);
    stsm4(stg + r * (NG * 16) + ((ch ^ (r & 7)) << 4), pack_bf16(acc[4 * i], acc[4 * i + 1]), pack_bf16(acc[4 * i + 2], acc[4 * i + 3]),
          pack_bf16(acc[4 * i + 4], acc[4 * i + 5]), pack_bf16(acc[4 * i + 6], acc[4 * i + 7]));
  }
}
__device__ __forceinline__ uint32_t res_pair(uint32_t x, uint32_t g, float s0, float s1) { return hadd2(x, hmul2(g, pack_bf16(s0, s1))); }

__global__ void __launch_bounds__(384, 1) k4_kernel(const __grid_constant__ CUtensorMap mx, const __grid_constant__ CUtensorMap mg,
                                                    const __grid_constant__ CUtensorMap mu, const __grid_constant__ CUtensorMap md,
                                                    __nv_bfloat16* __restrict__ out) {
  extern __shared__ __align__(1024) uint8_t smem_raw[];
  const uint32_t sb = s2u(smem_raw);
  const uint32_t R = sb, RING = sb + R_BYTES, BAR = RING + NSTG * STG_BYTES, TAB = BAR + 512;
  const uint32_t full = BAR, empty = BAR + 64, xfull = BAR + 128, gfull = BAR + 272, sfull = BAR + 320;
  const int tid = threadIdx.x, lane = tid & 31, warp = tid >> 5;
  const int mb = blockIdx.x >> 3, fb = blockIdx.x & 7;
  if (tid == 0) {
    TS(4, 0);
    if (sb & 1023) __trap();
    for (int i = 0; i < 10; i++) mbar_init(sfull + i * 8, 4);
    for (int i = 0; i < NSTG; i++) { mbar_init(full + i * 8, 1); mbar_init(empty + i * 8, 8); }
    for (int i = 0; i < 18; i++) mbar_init(xfull + i * 8, 1);
    for (int i = 0; i < 5; i++) mbar_init(gfull + i * 8, 1);
    mbar_arrive(full);
    fence_bar_init();
  }
  __syncthreads();
  if (warp >= 8) {
    REG_DEC(24);
    if (lane == 0) {
      if (warp == 8) {
        int st = 1; uint32_t ph = 0;
        for (int it = 0; it < 126; it++) {
          if (it == NSTG - 1) {
            pdl_wait();
            for (int c = 0; c < 18; c++) {
              const int w = c >= 9, k = c - w * 9;
              mbar_expect(xfull + c * 8, 8192);
              tma2d(R + k * 16384 + w * 8192, &mx, k * 64, mb * 128 + w * 64, xfull + c * 8);
            }
          }
          const int t = it / 9, s = it - t * 9;
          const uint32_t dst = RING + st * STG_BYTES, fb_ = full + st * 8;
          mbar_wait(empty + st * 8, ph ^ 1);
          if (t < 9) {
            mbar_expect(fb_, 16384);
            tma2d(dst, &mg, fb * 576 + t * 64, s * 64, fb_);
            tma2d(dst + 8192, &mu, fb * 576 + t * 64, s * 64, fb_);
          } else {
            mbar_expect(fb_, t < 13 ? 16384 : 8192);
            tma2d(dst, &md, (t - 9) * 128, fb * 576 + s * 64, fb_);
            if (t < 13) tma2d(dst + 8192, &md, (t - 9) * 128 + 64, fb * 576 + s * 64, fb_);
          }
          if (++st == NSTG) { st = 0; ph ^= 1; }
        }
      } else if (warp < 11) {
        const int wg = warp - 9;
#pragma unroll 1
        for (int p = 0; p < 5; p++) {
          uint8_t* dst = g_part + (size_t)((fb * 16 + mb) * 5 + p) * 32768;
          mbar_wait(sfull + (p * 2 + wg) * 8, 0);
          if (p < 4) {
            bulk_s2g(dst + wg * 16384, R + p * 32768 + wg * 8192, 8192);
            bulk_s2g(dst + wg * 16384 + 8192, R + p * 32768 + 16384 + wg * 8192, 8192);
          } else {
            bulk_s2g(dst + wg * 8192, RING + wg * STG_BYTES + 8192, 8192);
          }
          bulk_commit();
          if (wg == 0 && p >= 3) TS(3, 11 + p);
          bulk_wait0();
          if (wg == 0) TS(3, 4 + p);
          asm volatile("fence.proxy.async.global;" ::: "memory");
          asm volatile("red.relaxed.gpu.global.add.u32 [%0],1;" ::"l"(g_cnt + mb * 5 + p) : "memory");
        }
      } else {
        mbar_wait(sfull, 0);
#pragma unroll 1
        for (int p = 0; p < 5; p++) {
          unsigned int v; int n = 0;
          do {
            asm volatile("ld.acquire.gpu.global.u32 %0,[%1];" : "=r"(v) : "l"(g_cnt + mb * 5 + p) : "memory");
          } while (v < 16 && ++n < 20000000);
          if (v < 16) __trap();
          asm volatile("fence.proxy.async.global;" ::: "memory");
          TS(3, 9 + p);
          const uint32_t sz = p < 4 ? 4096 : 2048;
          mbar_expect(gfull + p * 8, sz * 8);
#pragma unroll 1
          for (int f = 0; f < 8; f++)
            bulk_g2s(p < 4 ? R + p * 32768 + f * 4096 : RING + (2 + (f >> 2)) * STG_BYTES + 8192 + (f & 3) * 2048,
                     g_part + (size_t)((f * 16 + mb) * 5 + p) * 32768 + fb * sz, sz, gfull + p * 8);
        }
      }
    }
  } else {
    REG_INC(240);
    uint32_t a[36][4];
    const int wg = warp >> 2, wl = warp & 3;
    if (tid < 144) sts128(TAB + tid * 16, g_tab2[tid]);
    bar_sync(1, 256);
    pdl_wait();
    TSS(0);
    {
      const int g = lane >> 2, cq = lane & 3;
      const uint4 s0 = ln2_consts(mb * 128 + warp * 16 + g, cq), s1 = ln2_consts(mb * 128 + warp * 16 + g + 8, cq);
#pragma unroll
      for (int c = 0; c < 9; c++) {
        mbar_wait(xfull + (wg * 9 + c) * 8, 0);
        load_a_chunk(&a[c * 4], R + c * 16384, warp * 16, lane);
        if (c == 8) { __syncwarp(); if (lane == 0) mbar_arrive(empty); }
#pragma unroll
        for (int k = c * 4; k < c * 4 + 4; k++) {
          const uint4 t = lds128(TAB + (k * 4 + cq) * 16);
          a[k][0] = ln_apply(a[k][0], s0, t.x, t.y);
          a[k][1] = ln_apply(a[k][1], s1, t.x, t.y);
          a[k][2] = ln_apply(a[k][2], s0, t.z, t.w);
          a[k][3] = ln_apply(a[k][3], s1, t.z, t.w);
        }
      }
    }
    TSS(1);
    float acc[64];
    const uint32_t hsp = R + warp * 2048 + lane * 16;
#define GLU_SPILL(t)                                                            \
  _Pragma("unroll") for (int j = 0; j < 4; j++) {                               \
    uint32_t h[4];                                                              \
    _Pragma("unroll") for (int e = 0; e < 4; e++)                               \
      h[e] = glu_pair(acc[8 * j + 2 * e], acc[8 * j + 2 * e + 1], acc[32 + 8 * j + 2 * e], acc[32 + 8 * j + 2 * e + 1]); \
    asm volatile("st.shared.v4.b32 [%0],{%1,%2,%3,%4};" ::"r"(hsp + (t) * 16384 + j * 512), "r"(h[0]), "r"(h[1]), "r"(h[2]), "r"(h[3]) : "memory"); \
  }
#pragma unroll 1
    for (int t = 0; t < 4; t++) {
      MMA_TILE(wl_rs_n128_t1, 0, t & 1);
      GLU_SPILL(2 * t);
      MMA_TILE(wl_rs_n128_t1, 1, t & 1);
      GLU_SPILL(2 * t + 1);
    }
    MMA_TILE(wl_rs_n128_t1, 0, 0);
#pragma unroll
    for (int j = 0; j < 4; j++)
#pragma unroll
      for (int e = 0; e < 4; e++)
        a[32 + j][e] = glu_pair(acc[8 * j + 2 * e], acc[8 * j + 2 * e + 1], acc[32 + 8 * j + 2 * e], acc[32 + 8 * j + 2 * e + 1]);
#pragma unroll
    for (int k = 0; k < 32; k++)
      asm volatile("ld.shared.v4.b32 {%0,%1,%2,%3},[%4];" : "=r"(a[k][0]), "=r"(a[k][1]), "=r"(a[k][2]), "=r"(a[k][3]) : "r"(hsp + (k >> 2) * 16384 + (k & 3) * 512) : "memory");
    TSS(2);
    const uint32_t stg = R + (wl >> 1) * 16384 + wg * 8192 + (wl & 1) * 4096;
#define PART_OUT(p)                                                             \
  stage_part<16>(acc, stg + (p) * 32768, lane);                                 \
  fence_async_smem();                                                           \
  __syncwarp();                                                                 \
  if (lane == 0) mbar_arrive(sfull + ((p) * 2 + wg) * 8);
    bar_sync(2 + wg, 128);
#pragma unroll 1
    for (int p = 0; p < 2; p++) {
      MMA_TILE(wl_rs_n128_t1, 1, p);
      PART_OUT(2 * p);
      MMA_TILE(wl_rs_n128_t1, 0, p ^ 1);
      PART_OUT(2 * p + 1);
    }
    MMA_TILE(wl_rs_n64_t1, 1, 0);
    stage_part<8>(acc, RING + wg * STG_BYTES + 8192 + wl * 2048, lane);
    fence_async_smem();
    __syncwarp();
    if (lane == 0) mbar_arrive(sfull + (8 + wg) * 8);
    TSS(3);
    const int rl = tid >> 4, ch = tid & 15;
    const size_t off = (size_t)(mb * 128 + fb * 16 + rl) * DM + ch * 8;
    uint4 xv[5], gv[5];
#pragma unroll
    for (int p = 0; p < 5; p++)
      if (p < 4 || ch < 8) { xv[p] = __ldcg((const uint4*)(g_x1 + off + p * 128)); gv[p] = __ldcg((const uint4*)(g_gb + p * 128 + ch * 8)); }
#pragma unroll
    for (int p = 0; p < 5; p++) {
      if (p == 4 && ch >= 8) break;
      mbar_wait(gfull + p * 8, 0);
      float r8[8] = {0, 0, 0, 0, 0, 0, 0, 0};
#pragma unroll
      for (int f = 0; f < 8; f++) {
        const uint4 v = lds128((p < 4 ? R + p * 32768 + f * 4096 + rl * 256 : RING + (2 + (f >> 2)) * STG_BYTES + 8192 + (f & 3) * 2048 + rl * 128) +
                               ((ch ^ (rl & 7)) << 4));
        r8[0] += bf_lo(v.x); r8[1] += bf_hi(v.x); r8[2] += bf_lo(v.y); r8[3] += bf_hi(v.y);
        r8[4] += bf_lo(v.z); r8[5] += bf_hi(v.z); r8[6] += bf_lo(v.w); r8[7] += bf_hi(v.w);
      }
      uint4 r;
      r.x = res_pair(xv[p].x, gv[p].x, r8[0], r8[1]);
      r.y = res_pair(xv[p].y, gv[p].y, r8[2], r8[3]);
      r.z = res_pair(xv[p].z, gv[p].z, r8[4], r8[5]);
      r.w = res_pair(xv[p].w, gv[p].w, r8[6], r8[7]);
      *(uint4*)(out + off + p * 128) = r;
      if (p >= 2) TSS(2 + p);
    }
    TSDUMP(4);
  }
}

typedef CUresult (*EncodeFn)(CUtensorMap*, CUtensorMapDataType, cuuint32_t, void*, const cuuint64_t*, const cuuint64_t*,
                             const cuuint32_t*, const cuuint32_t*, CUtensorMapInterleave, CUtensorMapSwizzle,
                             CUtensorMapL2promotion, CUtensorMapFloatOOBfill);
static void make_map(EncodeFn fn, CUtensorMap* m, const void* p, int rows, int cols, int box_rows) {
  cuuint64_t dims[2] = {(cuuint64_t)cols, (cuuint64_t)rows};
  cuuint64_t strides[1] = {(cuuint64_t)cols * 2};
  cuuint32_t box[2] = {64, (cuuint32_t)box_rows};
  cuuint32_t es[2] = {1, 1};
  fn(m, CU_TENSOR_MAP_DATA_TYPE_BFLOAT16, 2, (void*)p, dims, strides, box, es, CU_TENSOR_MAP_INTERLEAVE_NONE,
     CU_TENSOR_MAP_SWIZZLE_128B, CU_TENSOR_MAP_L2_PROMOTION_L2_256B, CU_TENSOR_MAP_FLOAT_OOB_FILL_NONE);
}
template <typename... KA, typename... A>
static void launch(void (*k)(KA...), int grid, int block, int smem, bool pdl, A... args) {
  cudaLaunchConfig_t cfg = {};
  cfg.gridDim = dim3(grid); cfg.blockDim = dim3(block); cfg.dynamicSmemBytes = smem; cfg.stream = cudaStreamPerThread;
  cudaLaunchAttribute at;
  at.id = cudaLaunchAttributeProgrammaticStreamSerialization;
  at.val.programmaticStreamSerializationAllowed = 1;
  cfg.attrs = &at; cfg.numAttrs = pdl ? 1 : 0;
  cudaLaunchKernelEx(&cfg, k, KA(args)...);
}

extern "C" void kernel_launch(void* const* d_in, const int* in_sizes, int n_in, void* d_out, int out_size) {
  const __nv_bfloat16* x = (const __nv_bfloat16*)d_in[0];
  void* fnp = nullptr;
  cudaDriverEntryPointQueryResult qr;
  cudaGetDriverEntryPoint("cuTensorMapEncodeTiled", &fnp, cudaEnableDefault, &qr);
  EncodeFn fn = (EncodeFn)fnp;
  void *po, *px1;
  cudaGetSymbolAddress(&po, g_o);
  cudaGetSymbolAddress(&px1, g_x1);
  CUtensorMap mx, mqkv, mo, mwo, mx1, mg, mu, md;
  make_map(fn, &mx, x, SEQ, DM, 128);
  make_map(fn, &mqkv, d_in[1], DM, 3 * DM, 64);
  make_map(fn, &mo, po, SEQ, DM, 128);
  make_map(fn, &mwo, d_in[2], DM, DM, 64);
  make_map(fn, &mx1, px1, SEQ, DM, 64);
  make_map(fn, &mg, d_in[4], DM, FF, 64);
  make_map(fn, &mu, d_in[5], DM, FF, 64);
  make_map(fn, &md, d_in[6], FF, DM, 64);
  cudaFuncSetAttribute(k1_kernel, cudaFuncAttributeMaxDynamicSharedMemorySize, GEMM_SMEM);
  cudaFuncSetAttribute(k2_kernel, cudaFuncAttributeMaxDynamicSharedMemorySize, ATT_SMEM);
  cudaFuncSetAttribute(k3_kernel, cudaFuncAttributeMaxDynamicSharedMemorySize, K3_SMEM);
  cudaFuncSetAttribute(k4_kernel, cudaFuncAttributeMaxDynamicSharedMemorySize, GEMM_SMEM);
  launch(k1_kernel, 132, 384, GEMM_SMEM, false, mx, mqkv, (const __nv_bfloat16*)d_in[7], (const __nv_bfloat16*)d_in[8]);
  launch(k2_kernel, 128, 512, ATT_SMEM, true, (const uint8_t*)d_in[2], (const uint8_t*)d_in[4], (const uint8_t*)d_in[5], (const uint8_t*)d_in[6]);
  launch(k3_kernel, 128, 288, K3_SMEM, true, mo, mwo, x);
  launch(k4_kernel, 128, 384, GEMM_SMEM, true, mx1, mg, mu, md, (__nv_bfloat16*)d_out);
}
```

```cpp
#include <cuda_runtime.h>
#include <cuda_bf16.h>
#include <cuda.h>
#include <stdint.h>

#define SEQ 2048
#define DM 576
#define NH 32
#define FF 4608

__device__ uint4 g_ll[36 * 4 * 2];
__device__ uint4 g_tab2[36 * 4];
__device__ __align__(16) __nv_bfloat16 g_ga[DM];
__device__ __align__(16) __nv_bfloat16 g_gb[DM];
__device__ float2 g_stat2[SEQ * 8];
__device__ __align__(1024) uint8_t g_qkv[96 * 98304];
__device__ float g_kmax[NH * 16];
__device__ __align__(1024) __nv_bfloat16 g_o[SEQ * DM];
__device__ __align__(1024) __nv_bfloat16 g_x1[SEQ * DM];
__device__ __align__(1024) uint8_t g_part[8 * 16 * 5 * 2 * 16384];
__device__ unsigned int g_cnt[16 * 5];

#define TS(k, i)
#define TSS(i)
#define TSDUMP(k)
__device__ __forceinline__ uint32_t s2u(const void* p) { return (uint32_t)__cvta_generic_to_shared(p); }
__device__ __forceinline__ void mbar_init(uint32_t b, int c) { asm volatile("mbarrier.init.shared::cta.b64 [%0],%1;" ::"r"(b), "r"(c)); }
__device__ __forceinline__ void mbar_expect(uint32_t b, uint32_t n) { asm volatile("mbarrier.arrive.expect_tx.shared::cta.b64 _,[%0],%1;" ::"r"(b), "r"(n) : "memory"); }
__device__ __forceinline__ void mbar_arrive(uint32_t b) { asm volatile("mbarrier.arrive.shared::cta.b64 _,[%0];" ::"r"(b) : "memory"); }
__device__ __forceinline__ void mbar_wait(uint32_t b, uint32_t ph) {
  asm volatile(
      "{.reg .pred p; .reg .u32 n;\n"
      "mbarrier.try_wait.parity.shared::cta.b64 p,[%0],%1;\n"
      "@p bra D;\n"
      "mov.u32 n,0;\n"
      "W: mbarrier.try_wait.parity.shared::cta.b64 p,[%0],%1;\n"
      "@p bra D;\n"
      "add.u32 n,n,1; setp.lt.u32 p,n,4000000; @p bra W;\n"
      "trap;\n"
      "D: }" ::"r"(b), "r"(ph) : "memory");
}
__device__ __forceinline__ void tma2d(uint32_t dst, const CUtensorMap* m, int c0, int c1, uint32_t bar) {
  asm volatile("cp.async.bulk.tensor.2d.shared::cluster.global.mbarrier::complete_tx::bytes [%0],[%1,{%3,%4}],[%2];"
               ::"r"(dst), "l"(m), "r"(bar), "r"(c0), "r"(c1) : "memory");
}
__device__ __forceinline__ void bulk_g2s(uint32_t dst, const void* src, uint32_t bytes, uint32_t bar) {
  asm volatile("cp.async.bulk.shared::cluster.global.mbarrier::complete_tx::bytes [%0],[%1],%2,[%3];"
               ::"r"(dst), "l"(src), "r"(bytes), "r"(bar) : "memory");
}
__device__ __forceinline__ void bulk_s2g(void* dst, uint32_t src, uint32_t bytes) {
  asm volatile("cp.async.bulk.global.shared::cta.bulk_group [%0],[%1],%2;" ::"l"(dst), "r"(src), "r"(bytes) : "memory");
}
__device__ __forceinline__ void bulk_commit() { asm volatile("cp.async.bulk.commit_group;" ::: "memory"); }
__device__ __forceinline__ void bulk_wait0() { asm volatile("cp.async.bulk.wait_group 0;" ::: "memory"); }
__device__ __forceinline__ void prefetch_map(const CUtensorMap* m) { asm volatile("prefetch.tensormap [%0];" ::"l"(m) : "memory"); }
__device__ __forceinline__ void fence_async_smem() { asm volatile("fence.proxy.async.shared::cta;" ::: "memory"); }
__device__ __forceinline__ void fence_bar_init() { asm volatile("fence.mbarrier_init.release.cluster;" ::: "memory"); }
__device__ __forceinline__ void pdl_wait() { asm volatile("griddepcontrol.wait;" ::: "memory"); }
__device__ __forceinline__ void pdl_launch() { asm volatile("griddepcontrol.launch_dependents;" ::: "memory"); }
__device__ __forceinline__ void bar_sync(int id, int n) { asm volatile("bar.sync %0,%1;" ::"r"(id), "r"(n) : "memory"); }
__device__ __forceinline__ void bar_arrive(int id, int n) { asm volatile("bar.arrive %0,%1;" ::"r"(id), "r"(n) : "memory"); }
#define WG_FENCE() asm volatile("wgmma.fence.sync.aligned;" ::: "memory")
#define WG_COMMIT() asm volatile("wgmma.commit_group.sync.aligned;" ::: "memory")
#define WG_WAIT(n) asm volatile("wgmma.wait_group.sync.aligned " #n ";" ::: "memory")
template <int N> __device__ __forceinline__ void fence_regs(float* r) {
#pragma unroll
  for (int i = 0; i < N; i++) asm volatile("" : "+f"(r[i])::"memory");
}
#define REG_INC(n) asm volatile("setmaxnreg.inc.sync.aligned.u32 " #n ";")
#define REG_DEC(n) asm volatile("setmaxnreg.dec.sync.aligned.u32 " #n ";")
__device__ __forceinline__ uint64_t mkdesc(uint32_t addr, uint32_t lbo, uint32_t sbo, int sw) {
  return (uint64_t)((addr & 0x3FFFF) >> 4) | ((uint64_t)(lbo >> 4) << 16) | ((uint64_t)(sbo >> 4) << 32) | ((uint64_t)sw << 62);
}
__device__ __forceinline__ void ldsm4(uint32_t* r, uint32_t addr) {
  asm volatile("ldmatrix.sync.aligned.m8n8.x4.shared.b16 {%0,%1,%2,%3},[%4];" : "=r"(r[0]), "=r"(r[1]), "=r"(r[2]), "=r"(r[3]) : "r"(addr) : "memory");
}
__device__ __forceinline__ void stsm4(uint32_t addr, uint32_t r0, uint32_t r1, uint32_t r2, uint32_t r3) {
  asm volatile("stmatrix.sync.aligned.m8n8.x4.shared.b16 [%0],{%1,%2,%3,%4};" ::"r"(addr), "r"(r0), "r"(r1), "r"(r2), "r"(r3) : "memory");
}
__device__ __forceinline__ uint32_t pack_bf16(float lo, float hi) {
  uint32_t r;
  asm("cvt.rn.bf16x2.f32 %0,%1,%2;" : "=r"(r) : "f"(hi), "f"(lo));
  return r;
}
__device__ __forceinline__ float bf_lo(uint32_t v) { return __uint_as_float(v << 16); }
__device__ __forceinline__ float bf_hi(uint32_t v) { return __uint_as_float(v & 0xFFFF0000u); }
__device__ __forceinline__ float sq2(uint32_t v) { return bf_lo(v) * bf_lo(v) + bf_hi(v) * bf_hi(v); }
__device__ __forceinline__ float rbf(float x) { return __bfloat162float(__float2bfloat16_rn(x)); }
__device__ __forceinline__ uint32_t hfma2(uint32_t a, uint32_t b, uint32_t c) {
  uint32_t r;
  asm("fma.rn.bf16x2 %0,%1,%2,%3;" : "=r"(r) : "r"(a), "r"(b), "r"(c));
  return r;
}
__device__ __forceinline__ uint32_t hadd2(uint32_t a, uint32_t b) {
  uint32_t r;
  asm("add.rn.bf16x2 %0,%1,%2;" : "=r"(r) : "r"(a), "r"(b));
  return r;
}
__device__ __forceinline__ uint32_t hmul2(uint32_t a, uint32_t b) {
  uint32_t r;
  asm("mul.rn.bf16x2 %0,%1,%2;" : "=r"(r) : "r"(a), "r"(b));
  return r;
}
__device__ __forceinline__ uint32_t hneg2(uint32_t a) {
  uint32_t r;
  asm("neg.bf16x2 %0,%1;" : "=r"(r) : "r"(a));
  return r;
}
__device__ __forceinline__ float ex2f(float x) {
  float r;
  asm("ex2.approx.ftz.f32 %0,%1;" : "=f"(r) : "f"(x));
  return r;
}
__device__ __forceinline__ float sqrt_fast(float x) {
  float r;
  asm("sqrt.approx.f32 %0,%1;" : "=f"(r) : "f"(x));
  return r;
}
__device__ __forceinline__ float rcp_fast(float x) {
  float r;
  asm("rcp.approx.f32 %0,%1;" : "=f"(r) : "f"(x));
  return r;
}
__device__ __forceinline__ float tanhf_fast(float x) {
  float r;
  asm("tanh.approx.f32 %0,%1;" : "=f"(r) : "f"(x));
  return r;
}
__device__ __forceinline__ uint4 ln_consts(float mean, float var) {
  float m = rbf(mean), v = rbf(var);
  float s = rbf(sqrtf(rbf(v + 1e-5f)));
  float r = 1.0f / s;
  float rh = rbf(r), rl = r - rh;
  return make_uint4(pack_bf16(-m, -m), pack_bf16(rh, rh), pack_bf16(rl, rl), 0u);
}
__device__ __forceinline__ uint32_t ln_apply(uint32_t x, const uint4& st, uint32_t a, uint32_t s) {
  uint32_t d = hadd2(x, st.x);
  uint32_t n = hfma2(d, st.y, hmul2(d, st.z));
  return hfma2(n, a, s);
}

__device__ __forceinline__ uint4 lds128(uint32_t a) {
  uint4 v;
  asm volatile("ld.shared.v4.b32 {%0,%1,%2,%3},[%4];" : "=r"(v.x), "=r"(v.y), "=r"(v.z), "=r"(v.w) : "r"(a) : "memory");
  return v;
}
__device__ __forceinline__ void sts128(uint32_t a, const uint4& v) {
  asm volatile("st.shared.v4.b32 [%0],{%1,%2,%3,%4};" ::"r"(a), "r"(v.x), "r"(v.y), "r"(v.z), "r"(v.w) : "memory");
}
__device__ __forceinline__ void hmma(float* c, const uint32_t* a, uint32_t b0, uint32_t b1) {
  asm volatile("mma.sync.aligned.m16n8k16.row.col.f32.bf16.bf16.f32 {%0,%1,%2,%3},{%4,%5,%6,%7},{%8,%9},{%0,%1,%2,%3};"
               : "+f"(c[0]), "+f"(c[1]), "+f"(c[2]), "+f"(c[3]) : "r"(a[0]), "r"(a[1]), "r"(a[2]), "r"(a[3]), "r"(b0), "r"(b1));
}
struct RowStat {
  float s[4], q0[4], q1[4];
  __device__ __forceinline__ void init() {
#pragma unroll
    for (int i = 0; i < 4; i++) s[i] = q0[i] = q1[i] = 0.f;
  }
  __device__ __forceinline__ void add(const uint32_t* a) {
    hmma(s, a, 0x3F803F80u, 0x3F803F80u);
    hmma(q0, a, a[0], a[2]);
    hmma(q1, a, a[1], a[3]);
  }
  __device__ __forceinline__ void merge(const RowStat& o) {
#pragma unroll
    for (int i = 0; i < 4; i++) { s[i] += o.s[i]; q0[i] += o.q0[i]; q1[i] += o.q1[i]; }
  }
  __device__ __forceinline__ void finish(int lane, uint4& c0, uint4& c1) {
    const int g = lane >> 2, src = (lane & ~3) | (g >> 1);
    const float a0 = __shfl_sync(~0u, (g & 1) ? q0[1] : q0[0], src), a1 = __shfl_sync(~0u, (g & 1) ? q1[3] : q1[2], src);
    const float m0 = s[0] * (1.0f / DM), m1 = s[2] * (1.0f / DM);
    c0 = ln_consts(m0, fmaxf(a0 * (1.0f / DM) - m0 * m0, 0.f));
    c1 = ln_consts(m1, fmaxf(a1 * (1.0f / DM) - m1 * m1, 0.f));
  }
};
#define LN_APPLY_ALL()                                                          \
  _Pragma("unroll") for (int k = 0; k < 36; k++) {                              \
    const uint4 t = lds128(TAB + (k * 4 + (lane & 3)) * 16);                    \
    a[k][0] = ln_apply(a[k][0], s0, t.x, t.y);                                  \
    a[k][1] = ln_apply(a[k][1], s1, t.x, t.y);                                  \
    a[k][2] = ln_apply(a[k][2], s0, t.z, t.w);                                  \
    a[k][3] = ln_apply(a[k][3], s1, t.z, t.w);                                  \
  }

__device__ __forceinline__ void wg_ss_n72_t1(float* d, uint64_t da, uint64_t db, int sc) {
  asm volatile("{.reg .pred p; setp.ne.b32 p,%38,0; wgmma.mma_async.sync.aligned.m64n72k16.f32.bf16.bf16 {%0,%1,%2,%3,%4,%5,%6,%7,%8,%9,%10,%11,%12,%13,%14,%15,%16,%17,%18,%19,%20,%21,%22,%23,%24,%25,%26,%27,%28,%29,%30,%31,%32,%33,%34,%35}, %36, %37, p,1,1,0,1;}"
  : "+f"(d[0]),"+f"(d[1]),"+f"(d[2]),"+f"(d[3]),"+f"(d[4]),"+f"(d[5]),"+f"(d[6]),"+f"(d[7]),"+f"(d[8]),"+f"(d[9]),"+f"(d[10]),"+f"(d[11]),"+f"(d[12]),"+f"(d[13]),"+f"(d[14]),"+f"(d[15]),"+f"(d[16]),"+f"(d[17]),"+f"(d[18]),"+f"(d[19]),"+f"(d[20]),"+f"(d[21]),"+f"(d[22]),"+f"(d[23]),"+f"(d[24]),"+f"(d[25]),"+f"(d[26]),"+f"(d[27]),"+f"(d[28]),"+f"(d[29]),"+f"(d[30]),"+f"(d[31]),"+f"(d[32]),"+f"(d[33]),"+f"(d[34]),"+f"(d[35]) : "l"(da),"l"(db),"r"(sc));
}
template <int SC> __device__ __forceinline__ void wl_rs_n128_t1(float* d, const uint32_t* a, uint64_t e) {
  asm volatile("wgmma.mma_async.sync.aligned.m64n128k16.f32.bf16.bf16 {%0,%1,%2,%3,%4,%5,%6,%7,%8,%9,%10,%11,%12,%13,%14,%15,%16,%17,%18,%19,%20,%21,%22,%23,%24,%25,%26,%27,%28,%29,%30,%31,%32,%33,%34,%35,%36,%37,%38,%39,%40,%41,%42,%43,%44,%45,%46,%47,%48,%49,%50,%51,%52,%53,%54,%55,%56,%57,%58,%59,%60,%61,%62,%63}, {%64,%65,%66,%67}, %68, %69,1,1,1;"
  : "+f"(d[0]),"+f"(d[1]),"+f"(d[2]),"+f"(d[3]),"+f"(d[4]),"+f"(d[5]),"+f"(d[6]),"+f"(d[7]),"+f"(d[8]),"+f"(d[9]),"+f"(d[10]),"+f"(d[11]),"+f"(d[12]),"+f"(d[13]),"+f"(d[14]),"+f"(d[15]),"+f"(d[16]),"+f"(d[17]),"+f"(d[18]),"+f"(d[19]),"+f"(d[20]),"+f"(d[21]),"+f"(d[22]),"+f"(d[23]),"+f"(d[24]),"+f"(d[25]),"+f"(d[26]),"+f"(d[27]),"+f"(d[28]),"+f"(d[29]),"+f"(d[30]),"+f"(d[31]),"+f"(d[32]),"+f"(d[33]),"+f"(d[34]),"+f"(d[35]),"+f"(d[36]),"+f"(d[37]),"+f"(d[38]),"+f"(d[39]),"+f"(d[40]),"+f"(d[41]),"+f"(d[42]),"+f"(d[43]),"+f"(d[44]),"+f"(d[45]),"+f"(d[46]),"+f"(d[47]),"+f"(d[48]),"+f"(d[49]),"+f"(d[50]),"+f"(d[51]),"+f"(d[52]),"+f"(d[53]),"+f"(d[54]),"+f"(d[55]),"+f"(d[56]),"+f"(d[57]),"+f"(d[58]),"+f"(d[59]),"+f"(d[60]),"+f"(d[61]),"+f"(d[62]),"+f"(d[63]) : "r"(a[0]),"r"(a[1]),"r"(a[2]),"r"(a[3]),"l"(e),"n"(SC));
}
template <int SC> __device__ __forceinline__ void wl_rs_n24_t1(float* d, const uint32_t* a, uint64_t e) {
  asm volatile("wgmma.mma_async.sync.aligned.m64n24k16.f32.bf16.bf16 {%0,%1,%2,%3,%4,%5,%6,%7,%8,%9,%10,%11}, {%12,%13,%14,%15}, %16, %17,1,1,1;"
  : "+f"(d[0]),"+f"(d[1]),"+f"(d[2]),"+f"(d[3]),"+f"(d[4]),"+f"(d[5]),"+f"(d[6]),"+f"(d[7]),"+f"(d[8]),"+f"(d[9]),"+f"(d[10]),"+f"(d[11]) : "r"(a[0]),"r"(a[1]),"r"(a[2]),"r"(a[3]),"l"(e),"n"(SC));
}
template <int SC> __device__ __forceinline__ void wl_rs_n64_t0(float* d, const uint32_t* a, uint64_t e) {
  asm volatile("wgmma.mma_async.sync.aligned.m64n64k16.f32.bf16.bf16 {%0,%1,%2,%3,%4,%5,%6,%7,%8,%9,%10,%11,%12,%13,%14,%15,%16,%17,%18,%19,%20,%21,%22,%23,%24,%25,%26,%27,%28,%29,%30,%31}, {%32,%33,%34,%35}, %36, %37,1,1,0;"
  : "+f"(d[0]),"+f"(d[1]),"+f"(d[2]),"+f"(d[3]),"+f"(d[4]),"+f"(d[5]),"+f"(d[6]),"+f"(d[7]),"+f"(d[8]),"+f"(d[9]),"+f"(d[10]),"+f"(d[11]),"+f"(d[12]),"+f"(d[13]),"+f"(d[14]),"+f"(d[15]),"+f"(d[16]),"+f"(d[17]),"+f"(d[18]),"+f"(d[19]),"+f"(d[20]),"+f"(d[21]),"+f"(d[22]),"+f"(d[23]),"+f"(d[24]),"+f"(d[25]),"+f"(d[26]),"+f"(d[27]),"+f"(d[28]),"+f"(d[29]),"+f"(d[30]),"+f"(d[31]) : "r"(a[0]),"r"(a[1]),"r"(a[2]),"r"(a[3]),"l"(e),"n"(SC));
}
template <int SC> __device__ __forceinline__ void wl_rs_n64_t1(float* d, const uint32_t* a, uint64_t e) {
  asm volatile("wgmma.mma_async.sync.aligned.m64n64k16.f32.bf16.bf16 {%0,%1,%2,%3,%4,%5,%6,%7,%8,%9,%10,%11,%12,%13,%14,%15,%16,%17,%18,%19,%20,%21,%22,%23,%24,%25,%26,%27,%28,%29,%30,%31}, {%32,%33,%34,%35}, %36, %37,1,1,1;"
  : "+f"(d[0]),"+f"(d[1]),"+f"(d[2]),"+f"(d[3]),"+f"(d[4]),"+f"(d[5]),"+f"(d[6]),"+f"(d[7]),"+f"(d[8]),"+f"(d[9]),"+f"(d[10]),"+f"(d[11]),"+f"(d[12]),"+f"(d[13]),"+f"(d[14]),"+f"(d[15]),"+f"(d[16]),"+f"(d[17]),"+f"(d[18]),"+f"(d[19]),"+f"(d[20]),"+f"(d[21]),"+f"(d[22]),"+f"(d[23]),"+f"(d[24]),"+f"(d[25]),"+f"(d[26]),"+f"(d[27]),"+f"(d[28]),"+f"(d[29]),"+f"(d[30]),"+f"(d[31]) : "r"(a[0]),"r"(a[1]),"r"(a[2]),"r"(a[3]),"l"(e),"n"(SC));
}
template <int SC> __device__ __forceinline__ void wl_rs_n88_t1(float* d, const uint32_t* a, uint64_t e) {
  asm volatile("wgmma.mma_async.sync.aligned.m64n88k16.f32.bf16.bf16 {%0,%1,%2,%3,%4,%5,%6,%7,%8,%9,%10,%11,%12,%13,%14,%15,%16,%17,%18,%19,%20,%21,%22,%23,%24,%25,%26,%27,%28,%29,%30,%31,%32,%33,%34,%35,%36,%37,%38,%39,%40,%41,%42,%43}, {%44,%45,%46,%47}, %48, %49,1,1,1;"
  : "+f"(d[0]),"+f"(d[1]),"+f"(d[2]),"+f"(d[3]),"+f"(d[4]),"+f"(d[5]),"+f"(d[6]),"+f"(d[7]),"+f"(d[8]),"+f"(d[9]),"+f"(d[10]),"+f"(d[11]),"+f"(d[12]),"+f"(d[13]),"+f"(d[14]),"+f"(d[15]),"+f"(d[16]),"+f"(d[17]),"+f"(d[18]),"+f"(d[19]),"+f"(d[20]),"+f"(d[21]),"+f"(d[22]),"+f"(d[23]),"+f"(d[24]),"+f"(d[25]),"+f"(d[26]),"+f"(d[27]),"+f"(d[28]),"+f"(d[29]),"+f"(d[30]),"+f"(d[31]),"+f"(d[32]),"+f"(d[33]),"+f"(d[34]),"+f"(d[35]),"+f"(d[36]),"+f"(d[37]),"+f"(d[38]),"+f"(d[39]),"+f"(d[40]),"+f"(d[41]),"+f"(d[42]),"+f"(d[43]) : "r"(a[0]),"r"(a[1]),"r"(a[2]),"r"(a[3]),"l"(e),"n"(SC));
}

#define POLY_MASK 0xB5u
#define QSCALE (0.23570226039551584f * 1.4426950408889634f)

#define NSTG 6
#define STG_BYTES 16384
#define R_BYTES (8 * 16384)
#define GEMM_SMEM (R_BYTES + NSTG * STG_BYTES + 3072)

__device__ __forceinline__ void load_a_chunk(uint32_t (*a)[4], uint32_t chunk_base, int row_in_tile, int lane) {
  const int r = row_in_tile + (lane & 7) + ((lane >> 3) & 1) * 8;
  const uint32_t rb = chunk_base + r * 128;
#pragma unroll
  for (int k = 0; k < 4; k++) ldsm4(a[k], rb + (((k * 2 + (lane >> 4)) ^ (r & 7)) << 4));
}

#define MMA_TILE(FN, ODD, pj)                                                   \
  {                                                                             \
    uint32_t rb_ = RING >> 4;                                                   \
    asm volatile("" : "+r"(rb_));                                               \
    const uint64_t db = mkdesc(0, 8192, 1024, 1) + (uint32_t)__shfl_sync(~0u, rb_, 0); \
    _Pragma("unroll") for (int s = 0; s < 9; s++) {                             \
      const int g_ = 1 + (ODD) * 9 + s, st_ = g_ % NSTG;                        \
      mbar_wait(full + st_ * 8, (pj) ^ ((g_ / NSTG) & 1));                      \
      WG_FENCE();                                                               \
      if (s == 0) FN<0>(acc, a[0], db + st_ * 1024); else FN<1>(acc, a[s * 4], db + st_ * 1024); \
      _Pragma("unroll") for (int k = 1; k < 4; k++) FN<1>(acc, a[s * 4 + k], db + st_ * 1024 + k * 128); \
      WG_COMMIT();                                                              \
      if (s > 0) { WG_WAIT(1); if (lane == 0) mbar_arrive(empty + ((g_ - 1) % NSTG) * 8); } \
    }                                                                           \
    WG_WAIT(0);                                                                 \
    if (lane == 0) mbar_arrive(empty + ((9 + (ODD) * 9) % NSTG) * 8);           \
  }

template <int NG, int G0>
__device__ __forceinline__ void qkv_stage(const float* acc, uint32_t stg, int rowl, int cq, int col_base) {
  const float vs0 = ((POLY_MASK >> ((rowl >> 3) & 7)) & 1) ? 0.5f : 1.0f, vs1 = ((POLY_MASK >> (((rowl >> 3) + 1) & 7)) & 1) ? 0.5f : 1.0f;
#pragma unroll
  for (int i = 0; i < NG; i++) {
    const int cc = (G0 + i) * 8 + cq * 2;
    const int slot = (cc * 3641) >> 16, d = cc - slot * 18;
    const int gc = col_base + cc;
    const float sc0 = gc < DM ? QSCALE : (gc < 2 * DM ? vs0 : 1.0f), sc1 = gc < DM ? QSCALE : (gc < 2 * DM ? vs1 : 1.0f);
    const uint32_t ad = stg + slot * 6144 + (d >> 3) * 128 + (d & 7) * 2 + (rowl >> 3) * 384 + (rowl & 7) * 16;
    asm volatile("st.shared.b32 [%0],%1;" ::"r"(ad), "r"(pack_bf16(acc[4 * i] * sc0, acc[4 * i + 1] * sc0)) : "memory");
    asm volatile("st.shared.b32 [%0],%1;" ::"r"(ad + 384), "r"(pack_bf16(acc[4 * i + 2] * sc1, acc[4 * i + 3] * sc1)) : "memory");
  }
}

__device__ __forceinline__ float silu_bf(__nv_bfloat16 c) {
  const float v = __bfloat162float(c);
  return rbf(v / (1.0f + __expf(-v)));
}
__device__ __forceinline__ void fma8(float* acc, float sv, const uint4& w) {
  acc[0] += sv * bf_lo(w.x); acc[1] += sv * bf_hi(w.x); acc[2] += sv * bf_lo(w.y); acc[3] += sv * bf_hi(w.y);
  acc[4] += sv * bf_lo(w.z); acc[5] += sv * bf_hi(w.z); acc[6] += sv * bf_lo(w.w); acc[7] += sv * bf_hi(w.w);
}
__device__ __forceinline__ int tab_pos(int col, int shift) {
  return (((col >> 4) * 4 + ((col & 7) >> 1)) * 4 + ((col >> 3) & 1) * 2 + shift) * 2 + (col & 1);
}
__device__ __forceinline__ float knorm_row(uint32_t slot, int row) {
  const uint32_t ad = slot + (row >> 3) * 384 + (row & 7) * 16;
  const uint4 u = lds128(ad), v = lds128(ad + 128);
  uint32_t w;
  asm volatile("ld.shared.b32 %0,[%1];" : "=r"(w) : "r"(ad + 256) : "memory");
  float q = sq2(u.x) + sq2(u.y) + sq2(u.z) + sq2(u.w) + sq2(v.x) + sq2(v.y) + sq2(v.z) + sq2(v.w) + sq2(w);
  if ((POLY_MASK >> ((row >> 3) & 7)) & 1) q *= 4.0f;
  return q == q ? q : __int_as_float(0x7f800000);
}

__global__ void __launch_bounds__(384, 1) k1_kernel(const __grid_constant__ CUtensorMap mx, const __grid_constant__ CUtensorMap mw,
                                                    const __nv_bfloat16* __restrict__ cvec, const __nv_bfloat16* __restrict__ wmod) {
  extern __shared__ __align__(1024) uint8_t smem_raw[];
  const uint32_t sb = s2u(smem_raw);
  const uint32_t R = sb, RING = sb + R_BYTES, BAR = RING + NSTG * STG_BYTES, TAB = BAR + 512;
  const uint32_t full = BAR, empty = BAR + 64, xfull = BAR + 128;
  const int tid = threadIdx.x, lane = tid & 31, warp = tid >> 5;
  const int mb = blockIdx.x >> 3, nb = blockIdx.x & 7;
  if (tid == 0) TS(1, 0);
  uint4 w[9];
  float sv[9];
  const int pt = tid - 256;
  if (blockIdx.x < 72 && pt >= 0) {
#pragma unroll
    for (int i = 0; i < 9; i++) w[i] = __ldg((const uint4*)(wmod + (size_t)((pt >> 1) + 64 * i) * 3456 + blockIdx.x * 16 + (pt & 1) * 8));
#pragma unroll
    for (int i = 0; i < 9; i++) sv[i] = __bfloat162float(cvec[(pt >> 1) + 64 * i]);
  }
  if (tid == 0) {
    if (sb & 1023) __trap();
    for (int i = 0; i < NSTG; i++) { mbar_init(full + i * 8, 1); mbar_init(empty + i * 8, 8); }
    for (int i = 0; i < 8; i++) mbar_init(xfull + i * 8, 1);
    fence_bar_init();
  }
  __syncthreads();
  pdl_launch();
  if (lane == 0) {
    if (warp < 8) { mbar_expect(xfull + warp * 8, 16384); tma2d(R + warp * 16384, &mx, warp * 64, mb * 128, xfull + warp * 8); }
    if (warp == 0) { mbar_expect(full, 16384); tma2d(RING, &mx, 512, mb * 128, full); }
    if (warp >= 1 && warp < NSTG) {
      mbar_expect(full + warp * 8, 16384);
      tma2d(RING + warp * STG_BYTES, &mw, nb * 216, warp * 64 - 64, full + warp * 8);
      tma2d(RING + warp * STG_BYTES + 8192, &mw, nb * 216 + 64, warp * 64 - 64, full + warp * 8);
    }
  }
  __syncwarp();
  if (warp >= 8) {
    if (blockIdx.x < 72) {
      float acc[8] = {0, 0, 0, 0, 0, 0, 0, 0};
#pragma unroll
      for (int i = 0; i < 9; i++) fma8(acc, rbf(sv[i] / (1.0f + __expf(-sv[i]))), w[i]);
#pragma unroll
      for (int j = 0; j < 8; j++)
#pragma unroll
        for (int o = 2; o < 32; o *= 2) acc[j] += __shfl_xor_sync(~0u, acc[j], o);
      float* red = (float*)(smem_raw + (BAR + 256 - sb));
      if (lane < 2) {
#pragma unroll
        for (int j = 0; j < 8; j++) red[(warp - 8) * 16 + lane * 8 + j] = acc[j];
      }
      bar_sync(3, 128);
      if (pt < 16) {
        const float v = rbf(red[pt] + red[16 + pt] + red[32 + pt] + red[48 + pt]);
        const int n = blockIdx.x * 16 + pt, shift = n < DM;
        const uint32_t word = pack_bf16(shift ? v : 1.0f + v, 1.0f);
        asm volatile("st.relaxed.gpu.global.u32 [%0],%1;" ::"l"((uint32_t*)g_ll + tab_pos(shift ? n : n - DM, shift)), "r"(word) : "memory");
      }
      __syncwarp();
    }
    REG_DEC(24);
    if (warp == 8) {
      if (lane == 0) {
        int st = 0; uint32_t ph = 1;
        for (int it = NSTG - 1; it < 18; it++) {
          const int t = it / 9, s = it - t * 9;
          mbar_wait(empty + st * 8, ph ^ 1);
          mbar_expect(full + st * 8, 16384);
          tma2d(RING + st * STG_BYTES, &mw, nb * 216 + t * 128, s * 64, full + st * 8);
          tma2d(RING + st * STG_BYTES + 8192, &mw, nb * 216 + t * 128 + 64, s * 64, full + st * 8);
          if (++st == NSTG) { st = 0; ph ^= 1; }
        }
      }
    } else {
      const int ht = tid - 288;
      bar_sync(1, 352);
      for (int i = ht; i < 12 * 128; i += 96) {
        const int slot = i >> 7, row = i & 127, type = (nb * 12 + slot) >> 5;
        uint32_t v = 0;
        if (type == 1) v = ((POLY_MASK >> ((row >> 3) & 7)) & 1) ? 0x43403F00u : 0x40253F80u;
        if (type == 2) v = 0x3F80u;
        const uint32_t ad = R + slot * 6144 + (row >> 3) * 384 + 256 + (row & 7) * 16;
        asm volatile("st.shared.b32 [%0],%1;" ::"r"(ad + 4), "r"(v) : "memory");
        asm volatile("st.shared.v2.b32 [%0],{%1,%1};" ::"r"(ad + 8), "r"(0) : "memory");
      }
      fence_async_smem();
      bar_sync(2, 352);
      if (ht == 0) {
        for (int s = 0; s < 7; s++) bulk_s2g(g_qkv + (size_t)(nb * 12 + s) * 98304 + mb * 6144, R + s * 6144, 6144);
        bulk_commit();
      }
      for (int s = warp - 9; s < 7; s += 3) {
        const int gs = nb * 12 + s;
        if ((gs >> 5) != 1) continue;
        float mx2 = 0;
#pragma unroll 1
        for (int row = lane; row < 128; row += 32) mx2 = fmaxf(mx2, knorm_row(R + s * 6144, row));
#pragma unroll
        for (int o = 16; o; o >>= 1) mx2 = fmaxf(mx2, __shfl_xor_sync(~0u, mx2, o));
        if (lane == 0) g_kmax[(gs & 31) * 16 + mb] = mx2;
      }
      if (ht == 0) bulk_wait0();
    }
  } else {
    REG_INC(240);
    TSS(0);
    uint32_t a[36][4];
    const int rowl = warp * 16;
    uint4 s0, s1;
    {
      RowStat rs, rt;
      rs.init(); rt.init();
#pragma unroll
      for (int c = 0; c < 9; c++) {
        mbar_wait(c < 8 ? xfull + c * 8 : full, 0);
        load_a_chunk(&a[c * 4], R + c * 16384, rowl, lane);
#pragma unroll
        for (int k = 0; k < 4; k += 2) { rs.add(a[c * 4 + k]); rt.add(a[c * 4 + k + 1]); }
      }
      if (lane == 0) mbar_arrive(empty);
      bar_arrive(1, 352);
      rs.merge(rt);
      rs.finish(lane, s0, s1);
    }
    TSS(1);
    if (tid < 144) {
      uint4 u, v;
      int n = 0;
      do {
        asm volatile("ld.relaxed.gpu.global.v4.u32 {%0,%1,%2,%3},[%4];" : "=r"(u.x), "=r"(u.y), "=r"(u.z), "=r"(u.w) : "l"(g_ll + tid * 2) : "memory");
        asm volatile("ld.relaxed.gpu.global.v4.u32 {%0,%1,%2,%3},[%4];" : "=r"(v.x), "=r"(v.y), "=r"(v.z), "=r"(v.w) : "l"(g_ll + tid * 2 + 1) : "memory");
        if (++n > 4000000) __trap();
      } while (((u.x & u.y & u.z & u.w & v.x & v.y & v.z & v.w) >> 16) != 0x3F80u);
      sts128(TAB + tid * 16, make_uint4(__byte_perm(u.x, u.y, 0x5410), __byte_perm(u.z, u.w, 0x5410), __byte_perm(v.x, v.y, 0x5410), __byte_perm(v.z, v.w, 0x5410)));
    }
    bar_sync(4, 256);
    TSS(2);
    LN_APPLY_ALL();
    float acc[64];
    TSS(3);
    MMA_TILE(wl_rs_n128_t1, 0, 0);
    int t2 = threadIdx.x;
    asm volatile("" : "+r"(t2));
    qkv_stage<16, 0>(acc, R, (t2 >> 5) * 16 + ((t2 & 31) >> 2), t2 & 3, nb * 216);
    fence_async_smem();
    bar_arrive(2, 352);
    TSS(4);
    MMA_TILE(wl_rs_n88_t1, 1, 0);
    asm volatile("" : "+r"(t2));
    qkv_stage<11, 16>(acc, R, (t2 >> 5) * 16 + ((t2 & 31) >> 2), t2 & 3, nb * 216);
    fence_async_smem();
    bar_sync(4, 256);
    TSS(5);
    if (tid == 0) {
      for (int s = 7; s < 12; s++) bulk_s2g(g_qkv + (size_t)(nb * 12 + s) * 98304 + mb * 6144, R + s * 6144, 6144);
      bulk_commit();
    }
    if (warp >= 3 && ((nb * 12 + 4 + warp) >> 5) == 1) {
      float mx2 = 0;
#pragma unroll
      for (int i = 0; i < 4; i++) mx2 = fmaxf(mx2, knorm_row(R + (4 + warp) * 6144, lane + 32 * i));
#pragma unroll
      for (int o = 16; o; o >>= 1) mx2 = fmaxf(mx2, __shfl_xor_sync(~0u, mx2, o));
      if (lane == 0) g_kmax[((nb * 12 + 4 + warp) & 31) * 16 + mb] = mx2;
    }
    if (tid == 0) bulk_wait0();
    TSS(6);
    TSDUMP(1);
  }
}

#define ATT_SMEM (2 * 98304 + 1024 + 256)

__device__ __forceinline__ uint32_t exp2_pair_fma(float t0, float t1) {
  uint32_t y;
  asm("prmt.b32 %0,%1,%2,0x6521;" : "=r"(y) : "r"(__float_as_uint(t0)), "r"(__float_as_uint(t1)));
  return hfma2(y, y | 0x3F803F80u, y | 0x007F007Fu);
}

__device__ __forceinline__ void softmax_fast(const float* s, uint32_t* p) {
#pragma unroll
  for (int i = 0; i < 8; i++) {
    if ((POLY_MASK >> i) & 1) {
      p[2 * i] = exp2_pair_fma(s[4 * i], s[4 * i + 1]);
      p[2 * i + 1] = exp2_pair_fma(s[4 * i + 2], s[4 * i + 3]);
    } else {
      p[2 * i] = pack_bf16(ex2f(s[4 * i]), ex2f(s[4 * i + 1]));
      p[2 * i + 1] = pack_bf16(ex2f(s[4 * i + 2]), ex2f(s[4 * i + 3]));
    }
  }
}
#define QK_MMA(S, kd)                                                           \
  wl_rs_n64_t0<0>(S, q, (kd));                                                  \
  wl_rs_n64_t0<1>(S, q + 4, (kd) + 16 - (8ull << 16));
#define PV_MMA(P, vd)                                                           \
  _Pragma("unroll") for (int t = 0; t < 4; t++) wl_rs_n24_t1<1>(o, P + 4 * t, (vd) + t * 48);

__device__ __forceinline__ void att_store(const float* o, int row0, int head, int lane) {
  const int cq = lane & 3;
  const float l0 = __shfl_sync(~0u, o[8], (lane & ~3) | 1), l1 = __shfl_sync(~0u, o[10], (lane & ~3) | 1);
  const float i0 = rcp_fast(l0), i1 = rcp_fast(l1);
  uint32_t* og = (uint32_t*)(g_o + (size_t)row0 * DM + head * 18 + cq * 2);
  og[0] = pack_bf16(o[0] * i0, o[1] * i0);
  og[4] = pack_bf16(o[4] * i0, o[5] * i0);
  og[8 * DM / 2] = pack_bf16(o[2] * i1, o[3] * i1);
  og[8 * DM / 2 + 4] = pack_bf16(o[6] * i1, o[7] * i1);
  if (cq == 0) {
    og[8] = pack_bf16(o[8] * i0, o[9] * i0);
    og[8 * DM / 2 + 8] = pack_bf16(o[10] * i1, o[11] * i1);
  }
}

__global__ void __launch_bounds__(512, 1) k2_kernel(const uint8_t* __restrict__ wo, const uint8_t* __restrict__ wg_, const uint8_t* __restrict__ wu,
                                                    const uint8_t* __restrict__ wd, const __nv_bfloat16* __restrict__ cvec,
                                                    const __nv_bfloat16* __restrict__ wmod) {
  extern __shared__ __align__(1024) uint8_t smem_raw[];
  const uint32_t sb = (s2u(smem_raw) + 1023) & ~1023u;
  const uint32_t KS = sb, VS = sb + 98304, BAR = sb + 2 * 98304;
  const int tid = threadIdx.x, lane = tid & 31, warp = tid >> 5, wg = tid >> 7;
  if (blockIdx.x < 4) {
    float* sf = (float*)smem_raw;
    const int part = blockIdx.x + 2;
    for (int i = tid; i < DM; i += 512) sf[i] = silu_bf(cvec[i]);
    if (part == 2 && tid < 80) g_cnt[tid] = 0;
    __syncthreads();
    if (tid < 432) {
      const int cg = tid % 72, rg = tid / 72;
      const __nv_bfloat16* w = wmod + (size_t)rg * 96 * 3456 + part * DM + cg * 8;
      float acc[8] = {0, 0, 0, 0, 0, 0, 0, 0};
#pragma unroll 1
      for (int r = 0; r < 96; r += 12) {
        uint4 v[12];
#pragma unroll
        for (int i = 0; i < 12; i++) v[i] = __ldg((const uint4*)(w + (size_t)(r + i) * 3456));
#pragma unroll
        for (int i = 0; i < 12; i++) fma8(acc, sf[rg * 96 + r + i], v[i]);
      }
#pragma unroll
      for (int j = 0; j < 8; j++) sf[DM + rg * DM + cg * 8 + j] = acc[j];
    }
    __syncthreads();
    for (int col = tid; col < DM; col += 512) {
      float v = 0;
#pragma unroll
      for (int j = 1; j < 7; j++) v += sf[j * DM + col];
      v = rbf(v);
      if (part == 2) g_ga[col] = __float2bfloat16_rn(v);
      else if (part == 5) g_gb[col] = __float2bfloat16_rn(v);
      else ((__nv_bfloat16*)g_tab2)[tab_pos(col, part == 3)] = __float2bfloat16_rn(0.5f * (part == 3 ? v : rbf(1.0f + v)));
    }
    pdl_wait();
    if (part == 2 && tid < 288) g_ll[tid] = make_uint4(0, 0, 0, 0);
    if (tid == 0) TS(0, 0);
    return;
  }
  const int bid = blockIdx.x - 4, head = bid >> 2, qb = bid & 3;
  if (tid == 0) {
    TS(2, 0);
    for (int i = 0; i < 16; i++) mbar_init(BAR + i * 8, 1);
    fence_bar_init();
  }
  __syncthreads();
  const int g = lane >> 2, cq = lane & 3;
  const int row0 = qb * 512 + wg * 128 + (warp & 3) * 16 + g;
  const uint8_t* qg = g_qkv + (size_t)head * 98304 + (row0 >> 3) * 384 + (row0 & 7) * 16 + cq * 4;
  pdl_wait();
  pdl_launch();
  if (tid == 0) TS(2, 1);
  const uint8_t* kg = g_qkv + (size_t)(32 + head) * 98304;
#define KV_LOAD(c) { mbar_expect(BAR + (c) * 8, 12288); bulk_g2s(KS + (c) * 6144, kg + (c) * 6144, 6144, BAR + (c) * 8); \
                     bulk_g2s(VS + (c) * 6144, kg + 32 * 98304 + (c) * 6144, 6144, BAR + (c) * 8); }
  if (lane == 0 && warp < 5) KV_LOAD(warp);
  __syncwarp();
  uint32_t q[8], q2[6];
  float kmax2 = __ldcg(g_kmax + head * 16 + (lane & 15));
#pragma unroll
  for (int i = 0; i < 6; i++) {
    q[i] = __ldcg((const uint32_t*)(qg + (i & 1) * 384 + (i >> 1) * 128));
    q2[i] = __ldcg((const uint32_t*)(qg + 3072 + (i & 1) * 384 + (i >> 1) * 128));
  }
  q[6] = __ldcg((const uint32_t*)(qg + 256 + 12 - cq * 4)); q[7] = __ldcg((const uint32_t*)(qg + 256 + 8 - cq * 4));
  const uint64_t dk = mkdesc(KS, 128, 384, 0), dv = mkdesc(VS, 384, 128, 0);
#pragma unroll
  for (int o = 8; o; o >>= 1) kmax2 = fmaxf(kmax2, __shfl_xor_sync(~0u, kmax2, o));
  float bd[4] = {sq2(q[0]) + sq2(q[2]) + sq2(q[4]), sq2(q[1]) + sq2(q[3]) + sq2(q[5]),
                 sq2(q2[0]) + sq2(q2[2]) + sq2(q2[4]), sq2(q2[1]) + sq2(q2[3]) + sq2(q2[5])};
  int ok = 1;
  if (tid == 0 && bd[0] + bd[3] + kmax2 != 1.2345f) TS(2, 5);
#pragma unroll
  for (int i = 0; i < 4; i++) {
    bd[i] += __shfl_xor_sync(~0u, bd[i], 1); bd[i] += __shfl_xor_sync(~0u, bd[i], 2);
    bd[i] = sqrt_fast(bd[i] * kmax2) * 1.01f + 1.0f;
    ok = ok && (bd[i] <= 62.0f);
  }
  {
    uint32_t all;
    asm volatile("{.reg .pred p,q; setp.ne.b32 p,%1,0; barrier.red.and.pred q,1,512,p; selp.u32 %0,1,0,q;}"
                 : "=r"(all) : "r"(ok) : "memory");
    ok = __all_sync(~0u, all);
  }
  float o[12];
#pragma unroll
  for (int i = 0; i < 12; i++) { o[i] = 0.f; asm volatile("" : "+f"(o[i])); }
  float s[32];
  uint32_t p[16];
  if (tid == 0) TS(2, 2);
  if (ok) {
    if (cq == 1) {
      q[4] = pack_bf16(-bd[0], 1.0f); q[5] = pack_bf16(-bd[1], 1.0f);
      q2[4] = pack_bf16(-bd[2], 1.0f); q2[5] = pack_bf16(-bd[3], 1.0f);
    }
    mbar_wait(BAR, 0);
    WG_FENCE();
    QK_MMA(s, dk);
    WG_COMMIT();
#pragma unroll 1
    for (int tile = 0; tile < 2; tile++) {
#pragma unroll 1
      for (int jj = 0; jj < 8; jj++) {
        const uint64_t kd = dk + (uint32_t)(jj * 768), vd = dv + (uint32_t)(jj * 768), kn = dk + (uint32_t)(((jj + 1) & 7) * 768);
        if (tile == 0) {
          if (lane == 0 && warp < 2 && 2 * jj + 5 + warp < 16) KV_LOAD(2 * jj + 5 + warp);
          if (lane == 0 && warp >= 4 && warp < 8) {
            const uint8_t* w = warp == 4 ? wg_ : warp == 5 ? wu : warp == 6 ? wd : wo;
            const uint32_t n = warp == 7 ? 656 : 5184, o_ = (bid * 8 + jj) * n;
            if (warp < 7 || o_ + n <= DM * DM * 2) asm volatile("cp.async.bulk.prefetch.L2.global [%0],%1;" ::"l"(w + o_), "r"(n) : "memory");
          }
          __syncwarp();
          mbar_wait(BAR + jj * 16 + 8, 0); mbar_wait(BAR + ((jj * 16 + 16) & 127), 0); if (tid == 0) TS(2, 8 + jj); }
#pragma unroll
        for (int u = 0; u < 4; u++) {
          WG_WAIT(0);
          fence_regs<32>(s);
          softmax_fast(s, p);
          if (u == 3 && jj == 7) {
#pragma unroll
            for (int i = 0; i < 6; i++) q[i] = q2[i];
          }
          WG_FENCE();
          PV_MMA(p, vd + u * 192);
          QK_MMA(s, u < 3 ? kd + u * 192 + 192 : kn);
          WG_COMMIT();
        }
      }
      WG_WAIT(0);
      fence_regs<12>(o);
      att_store(o, row0 + tile * 64, head, lane);
#pragma unroll
      for (int i = 0; i < 12; i++) o[i] = 0.f;
      fence_regs<12>(o);
      if (tid == 0 && tile == 0) TS(2, 3);
    }
  } else {
    if (lane == 0 && warp >= 5) KV_LOAD(warp);
    __syncwarp();
#pragma unroll 1
    for (int tile = 0; tile < 2; tile++) {
      float m0 = -INFINITY, m1 = -INFINITY;
#pragma unroll 1
      for (int j = 0; j < 32; j++) {
        mbar_wait(BAR + (j >> 1) * 8, 0);
        WG_FENCE();
        QK_MMA(s, dk + (uint32_t)(j * 192));
        WG_COMMIT();
        WG_WAIT(0);
        fence_regs<32>(s);
#pragma unroll
        for (int i = 0; i < 32; i++) if ((POLY_MASK >> (i >> 2)) & 1) s[i] *= 2.0f;
        float x0 = m0, x1 = m1;
#pragma unroll
        for (int i = 0; i < 8; i++) {
          x0 = fmaxf(x0, fmaxf(s[4 * i], s[4 * i + 1]));
          x1 = fmaxf(x1, fmaxf(s[4 * i + 2], s[4 * i + 3]));
        }
        x0 = fmaxf(x0, __shfl_xor_sync(~0u, x0, 1)); x0 = fmaxf(x0, __shfl_xor_sync(~0u, x0, 2));
        x1 = fmaxf(x1, __shfl_xor_sync(~0u, x1, 1)); x1 = fmaxf(x1, __shfl_xor_sync(~0u, x1, 2));
        const float c0 = ex2f(m0 - x0), c1 = ex2f(m1 - x1);
        m0 = x0; m1 = x1;
#pragma unroll
        for (int i = 0; i < 3; i++) { o[4 * i] *= c0; o[4 * i + 1] *= c0; o[4 * i + 2] *= c1; o[4 * i + 3] *= c1; }
#pragma unroll
        for (int i = 0; i < 8; i++) {
          p[2 * i] = pack_bf16(ex2f(s[4 * i] - x0), ex2f(s[4 * i + 1] - x0));
          p[2 * i + 1] = pack_bf16(ex2f(s[4 * i + 2] - x1), ex2f(s[4 * i + 3] - x1));
        }
        WG_FENCE();
        PV_MMA(p, dv + (uint32_t)(j * 192));
        WG_COMMIT();
        WG_WAIT(0);
        fence_regs<12>(o);
      }
      att_store(o, row0 + tile * 64, head, lane);
#pragma unroll
      for (int i = 0; i < 12; i++) o[i] = 0.f;
#pragma unroll
      for (int i = 0; i < 6; i++) q[i] = q2[i];
    }
  }
  if (tid == 0) TS(2, 4);
}

#define K3_NSTG 4
#define K3_SMEM (9 * 16384 + K3_NSTG * 16384 + 1024 + 256)
__global__ void __launch_bounds__(288, 1) k3_kernel(const __grid_constant__ CUtensorMap mo, const __grid_constant__ CUtensorMap mw,
                                                    const __nv_bfloat16* __restrict__ x) {
  extern __shared__ __align__(1024) uint8_t smem_raw[];
  const uint32_t sb = (s2u(smem_raw) + 1023) & ~1023u;
  const uint32_t A = sb, RING = sb + 9 * 16384, BAR = RING + K3_NSTG * 16384;
  const uint32_t full = BAR, empty = BAR + 64, afull = BAR + 128;
  const int tid = threadIdx.x, lane = tid & 31, warp = tid >> 5;
  const int mb = blockIdx.x >> 3, nb = blockIdx.x & 7;
  if (tid == 0) {
    TS(3, 0);
    for (int i = 0; i < K3_NSTG; i++) { mbar_init(full + i * 8, 1); mbar_init(empty + i * 8, 8); }
    for (int i = 0; i < 9; i++) mbar_init(afull + i * 8, 1);
    fence_bar_init();
  }
  __syncthreads();
  if (warp == 8) {
    if (lane == 0) {
      for (int s = 0; s < K3_NSTG; s++) {
        mbar_expect(full + s * 8, 16384);
        tma2d(RING + s * 16384, &mw, nb * 72, s * 64, full + s * 8);
        tma2d(RING + s * 16384 + 8192, &mw, nb * 72 + 64, s * 64, full + s * 8);
      }
      pdl_wait();
      for (int c = 0; c < 9; c++) { mbar_expect(afull + c * 8, 16384); tma2d(A + c * 16384, &mo, c * 64, mb * 128, afull + c * 8); }
      for (int s = K3_NSTG; s < 9; s++) {
        const int st = s % K3_NSTG;
        mbar_wait(empty + st * 8, ((s / K3_NSTG) & 1) ^ 1);
        mbar_expect(full + st * 8, 16384);
        tma2d(RING + st * 16384, &mw, nb * 72, s * 64, full + st * 8);
        tma2d(RING + st * 16384 + 8192, &mw, nb * 72 + 64, s * 64, full + st * 8);
      }
    }
  } else {
    const int g = lane >> 2, cq = lane & 3;
    const int row = mb * 128 + warp * 16 + g, col = nb * 72 + cq * 2;
    uint32_t xv[18];
#pragma unroll
    for (int i = 0; i < 9; i++) {
      xv[2 * i] = __ldg((const uint32_t*)(x + (size_t)row * DM + col + 8 * i));
      xv[2 * i + 1] = __ldg((const uint32_t*)(x + (size_t)(row + 8) * DM + col + 8 * i));
    }
    pdl_wait();
    pdl_launch();
    if (tid == 0) TS(3, 1);
    float2 ga[9];
#pragma unroll
    for (int i = 0; i < 9; i++) { const uint32_t t = *(const uint32_t*)(g_ga + col + 8 * i); ga[i] = make_float2(bf_lo(t), bf_hi(t)); }
    float acc[36];
    const uint32_t abase = A + (warp >> 2) * 8192;
#pragma unroll
    for (int s = 0; s < 9; s++) {
      const int st = s % K3_NSTG;
      mbar_wait(afull + s * 8, 0);
      mbar_wait(full + st * 8, (s / K3_NSTG) & 1);
      WG_FENCE();
#pragma unroll
      for (int k = 0; k < 4; k++)
        wg_ss_n72_t1(acc, mkdesc(abase + s * 16384 + k * 32, 16, 1024, 1), mkdesc(RING + st * 16384 + k * 2048, 8192, 1024, 1), (s | k) != 0);
      WG_COMMIT();
      if (s > 0) { WG_WAIT(1); if (lane == 0) mbar_arrive(empty + ((s - 1) % K3_NSTG) * 8); }
    }
    WG_WAIT(0);
    if (tid == 0) TS(3, 2);
    float s0 = 0, s1 = 0;
#pragma unroll
    for (int i = 0; i < 9; i++) {
      acc[4 * i] = rbf(bf_lo(xv[2 * i]) + rbf(ga[i].x * rbf(acc[4 * i])));
      acc[4 * i + 1] = rbf(bf_hi(xv[2 * i]) + rbf(ga[i].y * rbf(acc[4 * i + 1])));
      acc[4 * i + 2] = rbf(bf_lo(xv[2 * i + 1]) + rbf(ga[i].x * rbf(acc[4 * i + 2])));
      acc[4 * i + 3] = rbf(bf_hi(xv[2 * i + 1]) + rbf(ga[i].y * rbf(acc[4 * i + 3])));
      *(uint32_t*)(g_x1 + (size_t)row * DM + col + 8 * i) = pack_bf16(acc[4 * i], acc[4 * i + 1]);
      *(uint32_t*)(g_x1 + (size_t)(row + 8) * DM + col + 8 * i) = pack_bf16(acc[4 * i + 2], acc[4 * i + 3]);
      s0 += acc[4 * i] + acc[4 * i + 1];
      s1 += acc[4 * i + 2] + acc[4 * i + 3];
    }
    s0 += __shfl_xor_sync(~0u, s0, 1); s0 += __shfl_xor_sync(~0u, s0, 2);
    s1 += __shfl_xor_sync(~0u, s1, 1); s1 += __shfl_xor_sync(~0u, s1, 2);
    const float m0 = s0 * (1.0f / 72), m1 = s1 * (1.0f / 72);
    float q0 = 0, q1 = 0;
#pragma unroll
    for (int i = 0; i < 9; i++) {
      q0 += (acc[4 * i] - m0) * (acc[4 * i] - m0) + (acc[4 * i + 1] - m0) * (acc[4 * i + 1] - m0);
      q1 += (acc[4 * i + 2] - m1) * (acc[4 * i + 2] - m1) + (acc[4 * i + 3] - m1) * (acc[4 * i + 3] - m1);
    }
    q0 += __shfl_xor_sync(~0u, q0, 1); q0 += __shfl_xor_sync(~0u, q0, 2);
    q1 += __shfl_xor_sync(~0u, q1, 1); q1 += __shfl_xor_sync(~0u, q1, 2);
    if (cq == 0) {
      g_stat2[row * 8 + nb] = make_float2(m0, q0);
      g_stat2[(row + 8) * 8 + nb] = make_float2(m1, q1);
    }
    if (tid == 0) TS(3, 3);
  }
}

__device__ __forceinline__ uint4 ln2_consts(int row, int cq) {
  const float4 p = *(const float4*)(g_stat2 + row * 8 + cq * 2);
  float s = p.x + p.z;
  s += __shfl_xor_sync(~0u, s, 1); s += __shfl_xor_sync(~0u, s, 2);
  const float mean = s * 0.125f;
  float q = p.y + p.w + 72.0f * ((p.x - mean) * (p.x - mean) + (p.z - mean) * (p.z - mean));
  q += __shfl_xor_sync(~0u, q, 1); q += __shfl_xor_sync(~0u, q, 2);
  return ln_consts(mean, q * (1.0f / DM));
}
__device__ __forceinline__ uint32_t glu_pair(float g0, float g1, float u0, float u1) {
  return pack_bf16(fmaf(tanhf_fast(g0), u0, u0), fmaf(tanhf_fast(g1), u1, u1));
}
template <int NG>
__device__ __forceinline__ void stage_part(const float* acc, uint32_t stg, int lane) {
  const int r = (lane & 7) + ((lane >> 3) & 1) * 8;
#pragma unroll
  for (int i = 0; i < NG; i += 2) {
    const int ch = i + (lane >> 4);
    stsm4(stg + r * (NG * 16) + ((ch ^ (r & 7)) << 4), pack_bf16(acc[4 * i], acc[4 * i + 1]), pack_bf16(acc[4 * i + 2], acc[4 * i + 3]),
          pack_bf16(acc[4 * i + 4], acc[4 * i + 5]), pack_bf16(acc[4 * i + 6], acc[4 * i + 7]));
  }
}
__device__ __forceinline__ uint32_t res_pair(uint32_t x, uint32_t g, float s0, float s1) { return hadd2(x, hmul2(g, pack_bf16(s0, s1))); }

__global__ void __launch_bounds__(384, 1) k4_kernel(const __grid_constant__ CUtensorMap mx, const __grid_constant__ CUtensorMap mg,
                                                    const __grid_constant__ CUtensorMap mu, const __grid_constant__ CUtensorMap md,
                                                    __nv_bfloat16* __restrict__ out) {
  extern __shared__ __align__(1024) uint8_t smem_raw[];
  const uint32_t sb = s2u(smem_raw);
  const uint32_t R = sb, RING = sb + R_BYTES, BAR = RING + NSTG * STG_BYTES, TAB = BAR + 512;
  const uint32_t full = BAR, empty = BAR + 64, xfull = BAR + 128, gfull = BAR + 272, sfull = BAR + 320;
  const int tid = threadIdx.x, lane = tid & 31, warp = tid >> 5;
  const int mb = blockIdx.x >> 3, fb = blockIdx.x & 7;
  if (tid == 0) {
    TS(4, 0);
    if (sb & 1023) __trap();
    for (int i = 0; i < 10; i++) mbar_init(sfull + i * 8, 4);
    for (int i = 0; i < NSTG; i++) { mbar_init(full + i * 8, 1); mbar_init(empty + i * 8, 8); }
    for (int i = 0; i < 18; i++) mbar_init(xfull + i * 8, 1);
    for (int i = 0; i < 5; i++) mbar_init(gfull + i * 8, 1);
    mbar_arrive(full);
    fence_bar_init();
  }
  __syncthreads();
  if (warp >= 8) {
    REG_DEC(24);
    if (lane == 0) {
      if (warp == 8) {
        int st = 1; uint32_t ph = 0;
        for (int it = 0; it < 126; it++) {
          if (it == NSTG - 1) {
            pdl_wait();
            for (int c = 0; c < 18; c++) {
              const int w = c >= 9, k = c - w * 9;
              mbar_expect(xfull + c * 8, 8192);
              tma2d(R + k * 16384 + w * 8192, &mx, k * 64, mb * 128 + w * 64, xfull + c * 8);
            }
          }
          const int t = it / 9, s = it - t * 9;
          const uint32_t dst = RING + st * STG_BYTES, fb_ = full + st * 8;
          mbar_wait(empty + st * 8, ph ^ 1);
          if (t < 9) {
            mbar_expect(fb_, 16384);
            tma2d(dst, &mg, fb * 576 + t * 64, s * 64, fb_);
            tma2d(dst + 8192, &mu, fb * 576 + t * 64, s * 64, fb_);
          } else {
            mbar_expect(fb_, t < 13 ? 16384 : 8192);
            tma2d(dst, &md, (t - 9) * 128, fb * 576 + s * 64, fb_);
            if (t < 13) tma2d(dst + 8192, &md, (t - 9) * 128 + 64, fb * 576 + s * 64, fb_);
          }
          if (++st == NSTG) { st = 0; ph ^= 1; }
        }
      } else if (warp < 11) {
        const int wg = warp - 9;
#pragma unroll 1
        for (int p = 0; p < 5; p++) {
          uint8_t* dst = g_part + (size_t)((fb * 16 + mb) * 5 + p) * 32768;
          mbar_wait(sfull + (p * 2 + wg) * 8, 0);
          if (p < 4) {
            bulk_s2g(dst + wg * 16384, R + p * 32768 + wg * 8192, 8192);
            bulk_s2g(dst + wg * 16384 + 8192, R + p * 32768 + 16384 + wg * 8192, 8192);
          } else {
            bulk_s2g(dst + wg * 8192, RING + wg * STG_BYTES + 8192, 8192);
          }
          bulk_commit();
          if (wg == 0 && p >= 3) TS(3, 11 + p);
          bulk_wait0();
          if (wg == 0) TS(3, 4 + p);
          asm volatile("fence.proxy.async.global;" ::: "memory");
          asm volatile("red.relaxed.gpu.global.add.u32 [%0],1;" ::"l"(g_cnt + mb * 5 + p) : "memory");
        }
      } else {
        mbar_wait(sfull, 0);
#pragma unroll 1
        for (int p = 0; p < 5; p++) {
          unsigned int v; int n = 0;
          do {
            asm volatile("ld.acquire.gpu.global.u32 %0,[%1];" : "=r"(v) : "l"(g_cnt + mb * 5 + p) : "memory");
          } while (v < 16 && ++n < 20000000);
          if (v < 16) __trap();
          asm volatile("fence.proxy.async.global;" ::: "memory");
          TS(3, 9 + p);
          const uint32_t sz = p < 4 ? 4096 : 2048;
          mbar_expect(gfull + p * 8, sz * 8);
#pragma unroll 1
          for (int f = 0; f < 8; f++)
            bulk_g2s(p < 4 ? R + p * 32768 + f * 4096 : RING + (2 + (f >> 2)) * STG_BYTES + 8192 + (f & 3) * 2048,
                     g_part + (size_t)((f * 16 + mb) * 5 + p) * 32768 + fb * sz, sz, gfull + p * 8);
        }
      }
    }
  } else {
    REG_INC(240);
    uint32_t a[36][4];
    const int wg = warp >> 2, wl = warp & 3;
    if (tid < 144) sts128(TAB + tid * 16, g_tab2[tid]);
    bar_sync(1, 256);
    pdl_wait();
    TSS(0);
    {
      const int g = lane >> 2, cq = lane & 3;
      const uint4 s0 = ln2_consts(mb * 128 + warp * 16 + g, cq), s1 = ln2_consts(mb * 128 + warp * 16 + g + 8, cq);
#pragma unroll
      for (int c = 0; c < 9; c++) {
        mbar_wait(xfull + (wg * 9 + c) * 8, 0);
        load_a_chunk(&a[c * 4], R + c * 16384, warp * 16, lane);
        if (c == 8) { __syncwarp(); if (lane == 0) mbar_arrive(empty); }
#pragma unroll
        for (int k = c * 4; k < c * 4 + 4; k++) {
          const uint4 t = lds128(TAB + (k * 4 + cq) * 16);
          a[k][0] = ln_apply(a[k][0], s0, t.x, t.y);
          a[k][1] = ln_apply(a[k][1], s1, t.x, t.y);
          a[k][2] = ln_apply(a[k][2], s0, t.z, t.w);
          a[k][3] = ln_apply(a[k][3], s1, t.z, t.w);
        }
      }
    }
    TSS(1);
    float acc[64];
    const uint32_t hsp = R + warp * 2048 + lane * 16;
#define GLU_SPILL(t)                                                            \
  _Pragma("unroll") for (int j = 0; j < 4; j++) {                               \
    uint32_t h[4];                                                              \
    _Pragma("unroll") for (int e = 0; e < 4; e++)                               \
      h[e] = glu_pair(acc[8 * j + 2 * e], acc[8 * j + 2 * e + 1], acc[32 + 8 * j + 2 * e], acc[32 + 8 * j + 2 * e + 1]); \
    asm volatile("st.shared.v4.b32 [%0],{%1,%2,%3,%4};" ::"r"(hsp + (t) * 16384 + j * 512), "r"(h[0]), "r"(h[1]), "r"(h[2]), "r"(h[3]) : "memory"); \
  }
#pragma unroll 1
    for (int t = 0; t < 4; t++) {
      MMA_TILE(wl_rs_n128_t1, 0, t & 1);
      GLU_SPILL(2 * t);
      MMA_TILE(wl_rs_n128_t1, 1, t & 1);
      GLU_SPILL(2 * t + 1);
    }
    MMA_TILE(wl_rs_n128_t1, 0, 0);
#pragma unroll
    for (int j = 0; j < 4; j++)
#pragma unroll
      for (int e = 0; e < 4; e++)
        a[32 + j][e] = glu_pair(acc[8 * j + 2 * e], acc[8 * j + 2 * e + 1], acc[32 + 8 * j + 2 * e], acc[32 + 8 * j + 2 * e + 1]);
#pragma unroll
    for (int k = 0; k < 32; k++)
      asm volatile("ld.shared.v4.b32 {%0,%1,%2,%3},[%4];" : "=r"(a[k][0]), "=r"(a[k][1]), "=r"(a[k][2]), "=r"(a[k][3]) : "r"(hsp + (k >> 2) * 16384 + (k & 3) * 512) : "memory");
    TSS(2);
    const uint32_t stg = R + (wl >> 1) * 16384 + wg * 8192 + (wl & 1) * 4096;
#define PART_OUT(p)                                                             \
  stage_part<16>(acc, stg + (p) * 32768, lane);                                 \
  fence_async_smem();                                                           \
  __syncwarp();                                                                 \
  if (lane == 0) mbar_arrive(sfull + ((p) * 2 + wg) * 8);
    bar_sync(2 + wg, 128);
#pragma unroll 1
    for (int p = 0; p < 2; p++) {
      MMA_TILE(wl_rs_n128_t1, 1, p);
      PART_OUT(2 * p);
      MMA_TILE(wl_rs_n128_t1, 0, p ^ 1);
      PART_OUT(2 * p + 1);
    }
    MMA_TILE(wl_rs_n64_t1, 1, 0);
    stage_part<8>(acc, RING + wg * STG_BYTES + 8192 + wl * 2048, lane);
    fence_async_smem();
    __syncwarp();
    if (lane == 0) mbar_arrive(sfull + (8 + wg) * 8);
    TSS(3);
    const int rl = tid >> 4, ch = tid & 15;
    const size_t off = (size_t)(mb * 128 + fb * 16 + rl) * DM + ch * 8;
    uint4 xv[5], gv[5];
#pragma unroll
    for (int p = 0; p < 5; p++)
      if (p < 4 || ch < 8) { xv[p] = __ldcg((const uint4*)(g_x1 + off + p * 128)); gv[p] = __ldcg((const uint4*)(g_gb + p * 128 + ch * 8)); }
#pragma unroll
    for (int p = 0; p < 5; p++) {
      if (p == 4 && ch >= 8) break;
      mbar_wait(gfull + p * 8, 0);
      float r8[8] = {0, 0, 0, 0, 0, 0, 0, 0};
#pragma unroll
      for (int f = 0; f < 8; f++) {
        const uint4 v = lds128((p < 4 ? R + p * 32768 + f * 4096 + rl * 256 : RING + (2 + (f >> 2)) * STG_BYTES + 8192 + (f & 3) * 2048 + rl * 128) +
                               ((ch ^ (rl & 7)) << 4));
        r8[0] += bf_lo(v.x); r8[1] += bf_hi(v.x); r8[2] += bf_lo(v.y); r8[3] += bf_hi(v.y);
        r8[4] += bf_lo(v.z); r8[5] += bf_hi(v.z); r8[6] += bf_lo(v.w); r8[7] += bf_hi(v.w);
      }
      uint4 r;
      r.x = res_pair(xv[p].x, gv[p].x, r8[0], r8[1]);
      r.y = res_pair(xv[p].y, gv[p].y, r8[2], r8[3]);
      r.z = res_pair(xv[p].z, gv[p].z, r8[4], r8[5]);
      r.w = res_pair(xv[p].w, gv[p].w, r8[6], r8[7]);
      *(uint4*)(out + off + p * 128) = r;
      if (p >= 2) TSS(2 + p);
    }
    TSDUMP(4);
  }
}

typedef CUresult (*EncodeFn)(CUtensorMap*, CUtensorMapDataType, cuuint32_t, void*, const cuuint64_t*, const cuuint64_t*,
                             const cuuint32_t*, const cuuint32_t*, CUtensorMapInterleave, CUtensorMapSwizzle,
                             CUtensorMapL2promotion, CUtensorMapFloatOOBfill);
static void make_map(EncodeFn fn, CUtensorMap* m, const void* p, int rows, int cols, int box_rows) {
  cuuint64_t dims[2] = {(cuuint64_t)cols, (cuuint64_t)rows};
  cuuint64_t strides[1] = {(cuuint64_t)cols * 2};
  cuuint32_t box[2] = {64, (cuuint32_t)box_rows};
  cuuint32_t es[2] = {1, 1};
  fn(m, CU_TENSOR_MAP_DATA_TYPE_BFLOAT16, 2, (void*)p, dims, strides, box, es, CU_TENSOR_MAP_INTERLEAVE_NONE,
     CU_TENSOR_MAP_SWIZZLE_128B, CU_TENSOR_MAP_L2_PROMOTION_L2_256B, CU_TENSOR_MAP_FLOAT_OOB_FILL_NONE);
}
template <typename... KA, typename... A>
static void launch(void (*k)(KA...), int grid, int block, int smem, bool pdl, A... args) {
  cudaLaunchConfig_t cfg = {};
  cfg.gridDim = dim3(grid); cfg.blockDim = dim3(block); cfg.dynamicSmemBytes = smem; cfg.stream = cudaStreamPerThread;
  cudaLaunchAttribute at;
  at.id = cudaLaunchAttributeProgrammaticStreamSerialization;
  at.val.programmaticStreamSerializationAllowed = 1;
  cfg.attrs = &at; cfg.numAttrs = pdl ? 1 : 0;
  cudaLaunchKernelEx(&cfg, k, KA(args)...);
}

extern "C" void kernel_launch(void* const* d_in, const int* in_sizes, int n_in, void* d_out, int out_size) {
  const __nv_bfloat16* x = (const __nv_bfloat16*)d_in[0];
  void* fnp = nullptr;
  cudaDriverEntryPointQueryResult qr;
  cudaGetDriverEntryPoint("cuTensorMapEncodeTiled", &fnp, cudaEnableDefault, &qr);
  EncodeFn fn = (EncodeFn)fnp;
  void *po, *px1;
  cudaGetSymbolAddress(&po, g_o);
  cudaGetSymbolAddress(&px1, g_x1);
  CUtensorMap mx, mqkv, mo, mwo, mx1, mg, mu, md;
  make_map(fn, &mx, x, SEQ, DM, 128);
  make_map(fn, &mqkv, d_in[1], DM, 3 * DM, 64);
  make_map(fn, &mo, po, SEQ, DM, 128);
  make_map(fn, &mwo, d_in[2], DM, DM, 64);
  make_map(fn, &mx1, px1, SEQ, DM, 64);
  make_map(fn, &mg, d_in[4], DM, FF, 64);
  make_map(fn, &mu, d_in[5], DM, FF, 64);
  make_map(fn, &md, d_in[6], FF, DM, 64);
  cudaFuncSetAttribute(k1_kernel, cudaFuncAttributeMaxDynamicSharedMemorySize, GEMM_SMEM);
  cudaFuncSetAttribute(k2_kernel, cudaFuncAttributeMaxDynamicSharedMemorySize, ATT_SMEM);
  cudaFuncSetAttribute(k3_kernel, cudaFuncAttributeMaxDynamicSharedMemorySize, K3_SMEM);
  cudaFuncSetAttribute(k4_kernel, cudaFuncAttributeMaxDynamicSharedMemorySize, GEMM_SMEM);
  launch(k1_kernel, 128, 384, GEMM_SMEM, false, mx, mqkv, (const __nv_bfloat16*)d_in[7], (const __nv_bfloat16*)d_in[8]);
  launch(k2_kernel, 132, 512, ATT_SMEM, true, (const uint8_t*)d_in[2], (const uint8_t*)d_in[4], (const uint8_t*)d_in[5], (const uint8_t*)d_in[6],
         (const __nv_bfloat16*)d_in[7], (const __nv_bfloat16*)d_in[8]);
  launch(k3_kernel, 128, 288, K3_SMEM, true, mo, mwo, x);
  launch(k4_kernel, 128, 384, GEMM_SMEM, true, mx1, mg, mu, md, (__nv_bfloat16*)d_out);
}
```

```cpp
#include <cuda_runtime.h>
#include <cuda_bf16.h>
#include <cuda.h>
#include <stdint.h>

#define SEQ 2048
#define DM 576
#define NH 32
#define FF 4608

__device__ uint4 g_ll[36 * 4 * 2];
__device__ uint4 g_tab2[36 * 4];
__device__ __align__(16) __nv_bfloat16 g_ga[DM];
__device__ __align__(16) __nv_bfloat16 g_gb[DM];
__device__ float2 g_stat2[SEQ * 8];
__device__ __align__(1024) uint8_t g_qkv[96 * 98304];
__device__ float g_kmax[NH * 16];
__device__ __align__(1024) __nv_bfloat16 g_o[SEQ * DM];
__device__ __align__(1024) __nv_bfloat16 g_x1[SEQ * DM];
__device__ __align__(1024) uint8_t g_part[8 * 16 * 5 * 2 * 16384];
__device__ unsigned int g_cnt[16 * 5];

#define TS(k, i)
#define TSS(i)
#define TSDUMP(k)
__device__ __forceinline__ uint32_t s2u(const void* p) { return (uint32_t)__cvta_generic_to_shared(p); }
__device__ __forceinline__ void mbar_init(uint32_t b, int c) { asm volatile("mbarrier.init.shared::cta.b64 [%0],%1;" ::"r"(b), "r"(c)); }
__device__ __forceinline__ void mbar_expect(uint32_t b, uint32_t n) { asm volatile("mbarrier.arrive.expect_tx.shared::cta.b64 _,[%0],%1;" ::"r"(b), "r"(n) : "memory"); }
__device__ __forceinline__ void mbar_arrive(uint32_t b) { asm volatile("mbarrier.arrive.shared::cta.b64 _,[%0];" ::"r"(b) : "memory"); }
__device__ __forceinline__ void mbar_wait(uint32_t b, uint32_t ph) {
  asm volatile(
      "{.reg .pred p; .reg .u32 n;\n"
      "mbarrier.try_wait.parity.shared::cta.b64 p,[%0],%1;\n"
      "@p bra D;\n"
      "mov.u32 n,0;\n"
      "W: mbarrier.try_wait.parity.shared::cta.b64 p,[%0],%1;\n"
      "@p bra D;\n"
      "add.u32 n,n,1; setp.lt.u32 p,n,4000000; @p bra W;\n"
      "trap;\n"
      "D: }" ::"r"(b), "r"(ph) : "memory");
}
__device__ __forceinline__ void tma2d(uint32_t dst, const CUtensorMap* m, int c0, int c1, uint32_t bar) {
  asm volatile("cp.async.bulk.tensor.2d.shared::cluster.global.mbarrier::complete_tx::bytes [%0],[%1,{%3,%4}],[%2];"
               ::"r"(dst), "l"(m), "r"(bar), "r"(c0), "r"(c1) : "memory");
}
__device__ __forceinline__ void bulk_g2s(uint32_t dst, const void* src, uint32_t bytes, uint32_t bar) {
  asm volatile("cp.async.bulk.shared::cluster.global.mbarrier::complete_tx::bytes [%0],[%1],%2,[%3];"
               ::"r"(dst), "l"(src), "r"(bytes), "r"(bar) : "memory");
}
__device__ __forceinline__ void bulk_s2g(void* dst, uint32_t src, uint32_t bytes) {
  asm volatile("cp.async.bulk.global.shared::cta.bulk_group [%0],[%1],%2;" ::"l"(dst), "r"(src), "r"(bytes) : "memory");
}
__device__ __forceinline__ void bulk_commit() { asm volatile("cp.async.bulk.commit_group;" ::: "memory"); }
__device__ __forceinline__ void bulk_wait0() { asm volatile("cp.async.bulk.wait_group 0;" ::: "memory"); }
__device__ __forceinline__ void prefetch_map(const CUtensorMap* m) { asm volatile("prefetch.tensormap [%0];" ::"l"(m) : "memory"); }
__device__ __forceinline__ void fence_async_smem() { asm volatile("fence.proxy.async.shared::cta;" ::: "memory"); }
__device__ __forceinline__ void fence_bar_init() { asm volatile("fence.mbarrier_init.release.cluster;" ::: "memory"); }
__device__ __forceinline__ void pdl_wait() { asm volatile("griddepcontrol.wait;" ::: "memory"); }
__device__ __forceinline__ void pdl_launch() { asm volatile("griddepcontrol.launch_dependents;" ::: "memory"); }
__device__ __forceinline__ void bar_sync(int id, int n) { asm volatile("bar.sync %0,%1;" ::"r"(id), "r"(n) : "memory"); }
__device__ __forceinline__ void bar_arrive(int id, int n) { asm volatile("bar.arrive %0,%1;" ::"r"(id), "r"(n) : "memory"); }
#define WG_FENCE() asm volatile("wgmma.fence.sync.aligned;" ::: "memory")
#define WG_COMMIT() asm volatile("wgmma.commit_group.sync.aligned;" ::: "memory")
#define WG_WAIT(n) asm volatile("wgmma.wait_group.sync.aligned " #n ";" ::: "memory")
template <int N> __device__ __forceinline__ void fence_regs(float* r) {
#pragma unroll
  for (int i = 0; i < N; i++) asm volatile("" : "+f"(r[i])::"memory");
}
#define REG_INC(n) asm volatile("setmaxnreg.inc.sync.aligned.u32 " #n ";")
#define REG_DEC(n) asm volatile("setmaxnreg.dec.sync.aligned.u32 " #n ";")
__device__ __forceinline__ uint64_t mkdesc(uint32_t addr, uint32_t lbo, uint32_t sbo, int sw) {
  return (uint64_t)((addr & 0x3FFFF) >> 4) | ((uint64_t)(lbo >> 4) << 16) | ((uint64_t)(sbo >> 4) << 32) | ((uint64_t)sw << 62);
}
__device__ __forceinline__ void ldsm4(uint32_t* r, uint32_t addr) {
  asm volatile("ldmatrix.sync.aligned.m8n8.x4.shared.b16 {%0,%1,%2,%3},[%4];" : "=r"(r[0]), "=r"(r[1]), "=r"(r[2]), "=r"(r[3]) : "r"(addr) : "memory");
}
__device__ __forceinline__ void stsm4(uint32_t addr, uint32_t r0, uint32_t r1, uint32_t r2, uint32_t r3) {
  asm volatile("stmatrix.sync.aligned.m8n8.x4.shared.b16 [%0],{%1,%2,%3,%4};" ::"r"(addr), "r"(r0), "r"(r1), "r"(r2), "r"(r3) : "memory");
}
__device__ __forceinline__ uint32_t pack_bf16(float lo, float hi) {
  uint32_t r;
  asm("cvt.rn.bf16x2.f32 %0,%1,%2;" : "=r"(r) : "f"(hi), "f"(lo));
  return r;
}
__device__ __forceinline__ float bf_lo(uint32_t v) { return __uint_as_float(v << 16); }
__device__ __forceinline__ float bf_hi(uint32_t v) { return __uint_as_float(v & 0xFFFF0000u); }
__device__ __forceinline__ float sq2(uint32_t v) { return bf_lo(v) * bf_lo(v) + bf_hi(v) * bf_hi(v); }
__device__ __forceinline__ float rbf(float x) { return __bfloat162float(__float2bfloat16_rn(x)); }
__device__ __forceinline__ uint32_t hfma2(uint32_t a, uint32_t b, uint32_t c) {
  uint32_t r;
  asm("fma.rn.bf16x2 %0,%1,%2,%3;" : "=r"(r) : "r"(a), "r"(b), "r"(c));
  return r;
}
__device__ __forceinline__ uint32_t hadd2(uint32_t a, uint32_t b) {
  uint32_t r;
  asm("add.rn.bf16x2 %0,%1,%2;" : "=r"(r) : "r"(a), "r"(b));
  return r;
}
__device__ __forceinline__ uint32_t hmul2(uint32_t a, uint32_t b) {
  uint32_t r;
  asm("mul.rn.bf16x2 %0,%1,%2;" : "=r"(r) : "r"(a), "r"(b));
  return r;
}
__device__ __forceinline__ uint32_t hneg2(uint32_t a) {
  uint32_t r;
  asm("neg.bf16x2 %0,%1;" : "=r"(r) : "r"(a));
  return r;
}
__device__ __forceinline__ float ex2f(float x) {
  float r;
  asm("ex2.approx.ftz.f32 %0,%1;" : "=f"(r) : "f"(x));
  return r;
}
__device__ __forceinline__ float sqrt_fast(float x) {
  float r;
  asm("sqrt.approx.f32 %0,%1;" : "=f"(r) : "f"(x));
  return r;
}
__device__ __forceinline__ float rcp_fast(float x) {
  float r;
  asm("rcp.approx.f32 %0,%1;" : "=f"(r) : "f"(x));
  return r;
}
__device__ __forceinline__ float tanhf_fast(float x) {
  float r;
  asm("tanh.approx.f32 %0,%1;" : "=f"(r) : "f"(x));
  return r;
}
__device__ __forceinline__ uint4 ln_consts(float mean, float var) {
  float m = rbf(mean), v = rbf(var);
  float s = rbf(sqrtf(rbf(v + 1e-5f)));
  float r = 1.0f / s;
  float rh = rbf(r), rl = r - rh;
  return make_uint4(pack_bf16(-m, -m), pack_bf16(rh, rh), pack_bf16(rl, rl), 0u);
}
__device__ __forceinline__ uint32_t ln_apply(uint32_t x, const uint4& st, uint32_t a, uint32_t s) {
  uint32_t d = hadd2(x, st.x);
  uint32_t n = hfma2(d, st.y, hmul2(d, st.z));
  return hfma2(n, a, s);
}

__device__ __forceinline__ uint4 lds128(uint32_t a) {
  uint4 v;
  asm volatile("ld.shared.v4.b32 {%0,%1,%2,%3},[%4];" : "=r"(v.x), "=r"(v.y), "=r"(v.z), "=r"(v.w) : "r"(a) : "memory");
  return v;
}
__device__ __forceinline__ void sts128(uint32_t a, const uint4& v) {
  asm volatile("st.shared.v4.b32 [%0],{%1,%2,%3,%4};" ::"r"(a), "r"(v.x), "r"(v.y), "r"(v.z), "r"(v.w) : "memory");
}
__device__ __forceinline__ void hmma(float* c, const uint32_t* a, uint32_t b0, uint32_t b1) {
  asm volatile("mma.sync.aligned.m16n8k16.row.col.f32.bf16.bf16.f32 {%0,%1,%2,%3},{%4,%5,%6,%7},{%8,%9},{%0,%1,%2,%3};"
               : "+f"(c[0]), "+f"(c[1]), "+f"(c[2]), "+f"(c[3]) : "r"(a[0]), "r"(a[1]), "r"(a[2]), "r"(a[3]), "r"(b0), "r"(b1));
}
struct RowStat {
  float s[4], q0[4], q1[4];
  __device__ __forceinline__ void init() {
#pragma unroll
    for (int i = 0; i < 4; i++) s[i] = q0[i] = q1[i] = 0.f;
  }
  __device__ __forceinline__ void add(const uint32_t* a) {
    hmma(s, a, 0x3F803F80u, 0x3F803F80u);
    hmma(q0, a, a[0], a[2]);
    hmma(q1, a, a[1], a[3]);
  }
  __device__ __forceinline__ void merge(const RowStat& o) {
#pragma unroll
    for (int i = 0; i < 4; i++) { s[i] += o.s[i]; q0[i] += o.q0[i]; q1[i] += o.q1[i]; }
  }
  __device__ __forceinline__ void finish(int lane, uint4& c0, uint4& c1) {
    const int g = lane >> 2, src = (lane & ~3) | (g >> 1);
    const float a0 = __shfl_sync(~0u, (g & 1) ? q0[1] : q0[0], src), a1 = __shfl_sync(~0u, (g & 1) ? q1[3] : q1[2], src);
    const float m0 = s[0] * (1.0f / DM), m1 = s[2] * (1.0f / DM);
    c0 = ln_consts(m0, fmaxf(a0 * (1.0f / DM) - m0 * m0, 0.f));
    c1 = ln_consts(m1, fmaxf(a1 * (1.0f / DM) - m1 * m1, 0.f));
  }
};
#define LN_CHUNK(c)                                                             \
  load_a_chunk(&a[(c) * 4], R + (c) * 16384, warp * 16, lane);                  \
  _Pragma("unroll") for (int k = (c) * 4; k < (c) * 4 + 4; k++) {               \
    const uint4 t = lds128(TAB + (k * 4 + (lane & 3)) * 16);                    \
    a[k][0] = ln_apply(a[k][0], s0, t.x, t.y);                                  \
    a[k][1] = ln_apply(a[k][1], s1, t.x, t.y);                                  \
    a[k][2] = ln_apply(a[k][2], s0, t.z, t.w);                                  \
    a[k][3] = ln_apply(a[k][3], s1, t.z, t.w);                                  \
  }

__device__ __forceinline__ void wg_ss_n72_t1(float* d, uint64_t da, uint64_t db, int sc) {
  asm volatile("{.reg .pred p; setp.ne.b32 p,%38,0; wgmma.mma_async.sync.aligned.m64n72k16.f32.bf16.bf16 {%0,%1,%2,%3,%4,%5,%6,%7,%8,%9,%10,%11,%12,%13,%14,%15,%16,%17,%18,%19,%20,%21,%22,%23,%24,%25,%26,%27,%28,%29,%30,%31,%32,%33,%34,%35}, %36, %37, p,1,1,0,1;}"
  : "+f"(d[0]),"+f"(d[1]),"+f"(d[2]),"+f"(d[3]),"+f"(d[4]),"+f"(d[5]),"+f"(d[6]),"+f"(d[7]),"+f"(d[8]),"+f"(d[9]),"+f"(d[10]),"+f"(d[11]),"+f"(d[12]),"+f"(d[13]),"+f"(d[14]),"+f"(d[15]),"+f"(d[16]),"+f"(d[17]),"+f"(d[18]),"+f"(d[19]),"+f"(d[20]),"+f"(d[21]),"+f"(d[22]),"+f"(d[23]),"+f"(d[24]),"+f"(d[25]),"+f"(d[26]),"+f"(d[27]),"+f"(d[28]),"+f"(d[29]),"+f"(d[30]),"+f"(d[31]),"+f"(d[32]),"+f"(d[33]),"+f"(d[34]),"+f"(d[35]) : "l"(da),"l"(db),"r"(sc));
}
template <int SC> __device__ __forceinline__ void wl_rs_n128_t1(float* d, const uint32_t* a, uint64_t e) {
  if (SC) asm volatile("wgmma.mma_async.sync.aligned.m64n128k16.f32.bf16.bf16 {%0,%1,%2,%3,%4,%5,%6,%7,%8,%9,%10,%11,%12,%13,%14,%15,%16,%17,%18,%19,%20,%21,%22,%23,%24,%25,%26,%27,%28,%29,%30,%31,%32,%33,%34,%35,%36,%37,%38,%39,%40,%41,%42,%43,%44,%45,%46,%47,%48,%49,%50,%51,%52,%53,%54,%55,%56,%57,%58,%59,%60,%61,%62,%63}, {%64,%65,%66,%67}, %68, 1,1,1,1;"
  : "+f"(d[0]),"+f"(d[1]),"+f"(d[2]),"+f"(d[3]),"+f"(d[4]),"+f"(d[5]),"+f"(d[6]),"+f"(d[7]),"+f"(d[8]),"+f"(d[9]),"+f"(d[10]),"+f"(d[11]),"+f"(d[12]),"+f"(d[13]),"+f"(d[14]),"+f"(d[15]),"+f"(d[16]),"+f"(d[17]),"+f"(d[18]),"+f"(d[19]),"+f"(d[20]),"+f"(d[21]),"+f"(d[22]),"+f"(d[23]),"+f"(d[24]),"+f"(d[25]),"+f"(d[26]),"+f"(d[27]),"+f"(d[28]),"+f"(d[29]),"+f"(d[30]),"+f"(d[31]),"+f"(d[32]),"+f"(d[33]),"+f"(d[34]),"+f"(d[35]),"+f"(d[36]),"+f"(d[37]),"+f"(d[38]),"+f"(d[39]),"+f"(d[40]),"+f"(d[41]),"+f"(d[42]),"+f"(d[43]),"+f"(d[44]),"+f"(d[45]),"+f"(d[46]),"+f"(d[47]),"+f"(d[48]),"+f"(d[49]),"+f"(d[50]),"+f"(d[51]),"+f"(d[52]),"+f"(d[53]),"+f"(d[54]),"+f"(d[55]),"+f"(d[56]),"+f"(d[57]),"+f"(d[58]),"+f"(d[59]),"+f"(d[60]),"+f"(d[61]),"+f"(d[62]),"+f"(d[63]) : "r"(a[0]),"r"(a[1]),"r"(a[2]),"r"(a[3]),"l"(e));
  else asm volatile("wgmma.mma_async.sync.aligned.m64n128k16.f32.bf16.bf16 {%0,%1,%2,%3,%4,%5,%6,%7,%8,%9,%10,%11,%12,%13,%14,%15,%16,%17,%18,%19,%20,%21,%22,%23,%24,%25,%26,%27,%28,%29,%30,%31,%32,%33,%34,%35,%36,%37,%38,%39,%40,%41,%42,%43,%44,%45,%46,%47,%48,%49,%50,%51,%52,%53,%54,%55,%56,%57,%58,%59,%60,%61,%62,%63}, {%64,%65,%66,%67}, %68, 0,1,1,1;"
  : "=f"(d[0]),"=f"(d[1]),"=f"(d[2]),"=f"(d[3]),"=f"(d[4]),"=f"(d[5]),"=f"(d[6]),"=f"(d[7]),"=f"(d[8]),"=f"(d[9]),"=f"(d[10]),"=f"(d[11]),"=f"(d[12]),"=f"(d[13]),"=f"(d[14]),"=f"(d[15]),"=f"(d[16]),"=f"(d[17]),"=f"(d[18]),"=f"(d[19]),"=f"(d[20]),"=f"(d[21]),"=f"(d[22]),"=f"(d[23]),"=f"(d[24]),"=f"(d[25]),"=f"(d[26]),"=f"(d[27]),"=f"(d[28]),"=f"(d[29]),"=f"(d[30]),"=f"(d[31]),"=f"(d[32]),"=f"(d[33]),"=f"(d[34]),"=f"(d[35]),"=f"(d[36]),"=f"(d[37]),"=f"(d[38]),"=f"(d[39]),"=f"(d[40]),"=f"(d[41]),"=f"(d[42]),"=f"(d[43]),"=f"(d[44]),"=f"(d[45]),"=f"(d[46]),"=f"(d[47]),"=f"(d[48]),"=f"(d[49]),"=f"(d[50]),"=f"(d[51]),"=f"(d[52]),"=f"(d[53]),"=f"(d[54]),"=f"(d[55]),"=f"(d[56]),"=f"(d[57]),"=f"(d[58]),"=f"(d[59]),"=f"(d[60]),"=f"(d[61]),"=f"(d[62]),"=f"(d[63]) : "r"(a[0]),"r"(a[1]),"r"(a[2]),"r"(a[3]),"l"(e));
}
template <int SC> __device__ __forceinline__ void wl_rs_n24_t1(float* d, const uint32_t* a, uint64_t e) {
  if (SC) asm volatile("wgmma.mma_async.sync.aligned.m64n24k16.f32.bf16.bf16 {%0,%1,%2,%3,%4,%5,%6,%7,%8,%9,%10,%11}, {%12,%13,%14,%15}, %16, 1,1,1,1;"
  : "+f"(d[0]),"+f"(d[1]),"+f"(d[2]),"+f"(d[3]),"+f"(d[4]),"+f"(d[5]),"+f"(d[6]),"+f"(d[7]),"+f"(d[8]),"+f"(d[9]),"+f"(d[10]),"+f"(d[11]) : "r"(a[0]),"r"(a[1]),"r"(a[2]),"r"(a[3]),"l"(e));
  else asm volatile("wgmma.mma_async.sync.aligned.m64n24k16.f32.bf16.bf16 {%0,%1,%2,%3,%4,%5,%6,%7,%8,%9,%10,%11}, {%12,%13,%14,%15}, %16, 0,1,1,1;"
  : "=f"(d[0]),"=f"(d[1]),"=f"(d[2]),"=f"(d[3]),"=f"(d[4]),"=f"(d[5]),"=f"(d[6]),"=f"(d[7]),"=f"(d[8]),"=f"(d[9]),"=f"(d[10]),"=f"(d[11]) : "r"(a[0]),"r"(a[1]),"r"(a[2]),"r"(a[3]),"l"(e));
}
template <int SC> __device__ __forceinline__ void wl_rs_n64_t0(float* d, const uint32_t* a, uint64_t e) {
  if (SC) asm volatile("wgmma.mma_async.sync.aligned.m64n64k16.f32.bf16.bf16 {%0,%1,%2,%3,%4,%5,%6,%7,%8,%9,%10,%11,%12,%13,%14,%15,%16,%17,%18,%19,%20,%21,%22,%23,%24,%25,%26,%27,%28,%29,%30,%31}, {%32,%33,%34,%35}, %36, 1,1,1,0;"
  : "+f"(d[0]),"+f"(d[1]),"+f"(d[2]),"+f"(d[3]),"+f"(d[4]),"+f"(d[5]),"+f"(d[6]),"+f"(d[7]),"+f"(d[8]),"+f"(d[9]),"+f"(d[10]),"+f"(d[11]),"+f"(d[12]),"+f"(d[13]),"+f"(d[14]),"+f"(d[15]),"+f"(d[16]),"+f"(d[17]),"+f"(d[18]),"+f"(d[19]),"+f"(d[20]),"+f"(d[21]),"+f"(d[22]),"+f"(d[23]),"+f"(d[24]),"+f"(d[25]),"+f"(d[26]),"+f"(d[27]),"+f"(d[28]),"+f"(d[29]),"+f"(d[30]),"+f"(d[31]) : "r"(a[0]),"r"(a[1]),"r"(a[2]),"r"(a[3]),"l"(e));
  else asm volatile("wgmma.mma_async.sync.aligned.m64n64k16.f32.bf16.bf16 {%0,%1,%2,%3,%4,%5,%6,%7,%8,%9,%10,%11,%12,%13,%14,%15,%16,%17,%18,%19,%20,%21,%22,%23,%24,%25,%26,%27,%28,%29,%30,%31}, {%32,%33,%34,%35}, %36, 0,1,1,0;"
  : "=f"(d[0]),"=f"(d[1]),"=f"(d[2]),"=f"(d[3]),"=f"(d[4]),"=f"(d[5]),"=f"(d[6]),"=f"(d[7]),"=f"(d[8]),"=f"(d[9]),"=f"(d[10]),"=f"(d[11]),"=f"(d[12]),"=f"(d[13]),"=f"(d[14]),"=f"(d[15]),"=f"(d[16]),"=f"(d[17]),"=f"(d[18]),"=f"(d[19]),"=f"(d[20]),"=f"(d[21]),"=f"(d[22]),"=f"(d[23]),"=f"(d[24]),"=f"(d[25]),"=f"(d[26]),"=f"(d[27]),"=f"(d[28]),"=f"(d[29]),"=f"(d[30]),"=f"(d[31]) : "r"(a[0]),"r"(a[1]),"r"(a[2]),"r"(a[3]),"l"(e));
}
template <int SC> __device__ __forceinline__ void wl_rs_n64_t1(float* d, const uint32_t* a, uint64_t e) {
  if (SC) asm volatile("wgmma.mma_async.sync.aligned.m64n64k16.f32.bf16.bf16 {%0,%1,%2,%3,%4,%5,%6,%7,%8,%9,%10,%11,%12,%13,%14,%15,%16,%17,%18,%19,%20,%21,%22,%23,%24,%25,%26,%27,%28,%29,%30,%31}, {%32,%33,%34,%35}, %36, 1,1,1,1;"
  : "+f"(d[0]),"+f"(d[1]),"+f"(d[2]),"+f"(d[3]),"+f"(d[4]),"+f"(d[5]),"+f"(d[6]),"+f"(d[7]),"+f"(d[8]),"+f"(d[9]),"+f"(d[10]),"+f"(d[11]),"+f"(d[12]),"+f"(d[13]),"+f"(d[14]),"+f"(d[15]),"+f"(d[16]),"+f"(d[17]),"+f"(d[18]),"+f"(d[19]),"+f"(d[20]),"+f"(d[21]),"+f"(d[22]),"+f"(d[23]),"+f"(d[24]),"+f"(d[25]),"+f"(d[26]),"+f"(d[27]),"+f"(d[28]),"+f"(d[29]),"+f"(d[30]),"+f"(d[31]) : "r"(a[0]),"r"(a[1]),"r"(a[2]),"r"(a[3]),"l"(e));
  else asm volatile("wgmma.mma_async.sync.aligned.m64n64k16.f32.bf16.bf16 {%0,%1,%2,%3,%4,%5,%6,%7,%8,%9,%10,%11,%12,%13,%14,%15,%16,%17,%18,%19,%20,%21,%22,%23,%24,%25,%26,%27,%28,%29,%30,%31}, {%32,%33,%34,%35}, %36, 0,1,1,1;"
  : "=f"(d[0]),"=f"(d[1]),"=f"(d[2]),"=f"(d[3]),"=f"(d[4]),"=f"(d[5]),"=f"(d[6]),"=f"(d[7]),"=f"(d[8]),"=f"(d[9]),"=f"(d[10]),"=f"(d[11]),"=f"(d[12]),"=f"(d[13]),"=f"(d[14]),"=f"(d[15]),"=f"(d[16]),"=f"(d[17]),"=f"(d[18]),"=f"(d[19]),"=f"(d[20]),"=f"(d[21]),"=f"(d[22]),"=f"(d[23]),"=f"(d[24]),"=f"(d[25]),"=f"(d[26]),"=f"(d[27]),"=f"(d[28]),"=f"(d[29]),"=f"(d[30]),"=f"(d[31]) : "r"(a[0]),"r"(a[1]),"r"(a[2]),"r"(a[3]),"l"(e));
}
template <int SC> __device__ __forceinline__ void wl_rs_n88_t1(float* d, const uint32_t* a, uint64_t e) {
  if (SC) asm volatile("wgmma.mma_async.sync.aligned.m64n88k16.f32.bf16.bf16 {%0,%1,%2,%3,%4,%5,%6,%7,%8,%9,%10,%11,%12,%13,%14,%15,%16,%17,%18,%19,%20,%21,%22,%23,%24,%25,%26,%27,%28,%29,%30,%31,%32,%33,%34,%35,%36,%37,%38,%39,%40,%41,%42,%43}, {%44,%45,%46,%47}, %48, 1,1,1,1;"
  : "+f"(d[0]),"+f"(d[1]),"+f"(d[2]),"+f"(d[3]),"+f"(d[4]),"+f"(d[5]),"+f"(d[6]),"+f"(d[7]),"+f"(d[8]),"+f"(d[9]),"+f"(d[10]),"+f"(d[11]),"+f"(d[12]),"+f"(d[13]),"+f"(d[14]),"+f"(d[15]),"+f"(d[16]),"+f"(d[17]),"+f"(d[18]),"+f"(d[19]),"+f"(d[20]),"+f"(d[21]),"+f"(d[22]),"+f"(d[23]),"+f"(d[24]),"+f"(d[25]),"+f"(d[26]),"+f"(d[27]),"+f"(d[28]),"+f"(d[29]),"+f"(d[30]),"+f"(d[31]),"+f"(d[32]),"+f"(d[33]),"+f"(d[34]),"+f"(d[35]),"+f"(d[36]),"+f"(d[37]),"+f"(d[38]),"+f"(d[39]),"+f"(d[40]),"+f"(d[41]),"+f"(d[42]),"+f"(d[43]) : "r"(a[0]),"r"(a[1]),"r"(a[2]),"r"(a[3]),"l"(e));
  else asm volatile("wgmma.mma_async.sync.aligned.m64n88k16.f32.bf16.bf16 {%0,%1,%2,%3,%4,%5,%6,%7,%8,%9,%10,%11,%12,%13,%14,%15,%16,%17,%18,%19,%20,%21,%22,%23,%24,%25,%26,%27,%28,%29,%30,%31,%32,%33,%34,%35,%36,%37,%38,%39,%40,%41,%42,%43}, {%44,%45,%46,%47}, %48, 0,1,1,1;"
  : "=f"(d[0]),"=f"(d[1]),"=f"(d[2]),"=f"(d[3]),"=f"(d[4]),"=f"(d[5]),"=f"(d[6]),"=f"(d[7]),"=f"(d[8]),"=f"(d[9]),"=f"(d[10]),"=f"(d[11]),"=f"(d[12]),"=f"(d[13]),"=f"(d[14]),"=f"(d[15]),"=f"(d[16]),"=f"(d[17]),"=f"(d[18]),"=f"(d[19]),"=f"(d[20]),"=f"(d[21]),"=f"(d[22]),"=f"(d[23]),"=f"(d[24]),"=f"(d[25]),"=f"(d[26]),"=f"(d[27]),"=f"(d[28]),"=f"(d[29]),"=f"(d[30]),"=f"(d[31]),"=f"(d[32]),"=f"(d[33]),"=f"(d[34]),"=f"(d[35]),"=f"(d[36]),"=f"(d[37]),"=f"(d[38]),"=f"(d[39]),"=f"(d[40]),"=f"(d[41]),"=f"(d[42]),"=f"(d[43]) : "r"(a[0]),"r"(a[1]),"r"(a[2]),"r"(a[3]),"l"(e));
}

#define POLY_MASK 0xB5u
#define QSCALE (0.23570226039551584f * 1.4426950408889634f)

#define NSTG 6
#define STG_BYTES 16384
#define R_BYTES (8 * 16384)
#define GEMM_SMEM (R_BYTES + NSTG * STG_BYTES + 3072)

__device__ __forceinline__ void load_a_chunk(uint32_t (*a)[4], uint32_t chunk_base, int row_in_tile, int lane) {
  const int r = row_in_tile + (lane & 7) + ((lane >> 3) & 1) * 8;
  const uint32_t rb = chunk_base + r * 128;
#pragma unroll
  for (int k = 0; k < 4; k++) ldsm4(a[k], rb + (((k * 2 + (lane >> 4)) ^ (r & 7)) << 4));
}

#define MMA_TILE(FN, ODD, pj) MMA_TILE_(FN, ODD, pj, )
#define MMA_TILE_(FN, ODD, pj, PRE)                                             \
  {                                                                             \
    uint32_t rb_ = RING >> 4;                                                   \
    asm volatile("" : "+r"(rb_));                                               \
    const uint64_t db = mkdesc(0, 8192, 1024, 1) + (uint32_t)__shfl_sync(~0u, rb_, 0); \
    _Pragma("unroll") for (int s = 0; s < 9; s++) {                             \
      const int g_ = 1 + (ODD) * 9 + s, st_ = g_ % NSTG;                        \
      PRE;                                                                      \
      mbar_wait(full + st_ * 8, (pj) ^ ((g_ / NSTG) & 1));                      \
      WG_FENCE();                                                               \
      if (s == 0) FN<0>(acc, a[0], db + st_ * 1024); else FN<1>(acc, a[s * 4], db + st_ * 1024); \
      _Pragma("unroll") for (int k = 1; k < 4; k++) FN<1>(acc, a[s * 4 + k], db + st_ * 1024 + k * 128); \
      WG_COMMIT();                                                              \
      if (s > 0) { WG_WAIT(1); if (lane == 0) mbar_arrive(empty + ((g_ - 1) % NSTG) * 8); } \
    }                                                                           \
    WG_WAIT(0);                                                                 \
    if (lane == 0) mbar_arrive(empty + ((9 + (ODD) * 9) % NSTG) * 8);           \
  }

template <int NG, int G0>
__device__ __forceinline__ void qkv_stage(const float* acc, uint32_t stg, int rowl, int cq, int col_base) {
  const float vs0 = ((POLY_MASK >> ((rowl >> 3) & 7)) & 1) ? 0.5f : 1.0f, vs1 = ((POLY_MASK >> (((rowl >> 3) + 1) & 7)) & 1) ? 0.5f : 1.0f;
#pragma unroll
  for (int i = 0; i < NG; i++) {
    const int cc = (G0 + i) * 8 + cq * 2;
    const int slot = (cc * 3641) >> 16, d = cc - slot * 18;
    const int gc = col_base + cc;
    const float sc0 = gc < DM ? QSCALE : (gc < 2 * DM ? vs0 : 1.0f), sc1 = gc < DM ? QSCALE : (gc < 2 * DM ? vs1 : 1.0f);
    const uint32_t ad = stg + slot * 6144 + (d >> 3) * 128 + (d & 7) * 2 + (rowl >> 3) * 384 + (rowl & 7) * 16;
    asm volatile("st.shared.b32 [%0],%1;" ::"r"(ad), "r"(pack_bf16(acc[4 * i] * sc0, acc[4 * i + 1] * sc0)) : "memory");
    asm volatile("st.shared.b32 [%0],%1;" ::"r"(ad + 384), "r"(pack_bf16(acc[4 * i + 2] * sc1, acc[4 * i + 3] * sc1)) : "memory");
  }
}

__device__ __forceinline__ float silu_f(float v) { return rbf(__fdividef(v, 1.0f + fminf(__expf(-v), 1e37f))); }
__device__ __forceinline__ float silu_bf(__nv_bfloat16 c) { return silu_f(__bfloat162float(c)); }
__device__ __forceinline__ void fma8(float* acc, float sv, const uint4& w) {
  acc[0] += sv * bf_lo(w.x); acc[1] += sv * bf_hi(w.x); acc[2] += sv * bf_lo(w.y); acc[3] += sv * bf_hi(w.y);
  acc[4] += sv * bf_lo(w.z); acc[5] += sv * bf_hi(w.z); acc[6] += sv * bf_lo(w.w); acc[7] += sv * bf_hi(w.w);
}
__device__ __forceinline__ int tab_pos(int col, int shift) {
  return (((col >> 4) * 4 + ((col & 7) >> 1)) * 4 + ((col >> 3) & 1) * 2 + shift) * 2 + (col & 1);
}
__device__ __forceinline__ float knorm_row(uint32_t slot, int row) {
  const uint32_t ad = slot + (row >> 3) * 384 + (row & 7) * 16;
  const uint4 u = lds128(ad), v = lds128(ad + 128);
  uint32_t w;
  asm volatile("ld.shared.b32 %0,[%1];" : "=r"(w) : "r"(ad + 256) : "memory");
  float q = sq2(u.x) + sq2(u.y) + sq2(u.z) + sq2(u.w) + sq2(v.x) + sq2(v.y) + sq2(v.z) + sq2(v.w) + sq2(w);
  if ((POLY_MASK >> ((row >> 3) & 7)) & 1) q *= 4.0f;
  return q == q ? q : __int_as_float(0x7f800000);
}

__global__ void __launch_bounds__(384, 1) k1_kernel(const __grid_constant__ CUtensorMap mx, const __grid_constant__ CUtensorMap mw,
                                                    const __grid_constant__ CUtensorMap mm, const __nv_bfloat16* __restrict__ cvec,
                                                    const uint8_t* __restrict__ wqkv) {
  extern __shared__ __align__(1024) uint8_t smem_raw[];
  const uint32_t sb = s2u(smem_raw);
  const uint32_t R = sb, RING = sb + R_BYTES, BAR = RING + NSTG * STG_BYTES, TAB = BAR + 512;
  const uint32_t full = BAR, empty = BAR + 64, xfull = BAR + 128;
  const int tid = threadIdx.x, lane = tid & 31, warp = tid >> 5;
  const int mb = blockIdx.x >> 3, nb = blockIdx.x & 7;
  if (tid == 0) TS(1, 0);
  if (tid == 288) { prefetch_map(&mx); prefetch_map(&mw); }
  if (tid == 256) {
    if (sb & 1023) __trap();
    for (int i = 0; i < NSTG; i++) { mbar_init(full + i * 8, 1); mbar_init(empty + i * 8, 8); }
    for (int i = 0; i < 9; i++) mbar_init(xfull + i * 8, 1);
    fence_bar_init();
    if (blockIdx.x < 72) {
      mbar_expect(xfull + 64, 18432);
      for (int i = 0; i < 3; i++) tma2d(RING + 4 * STG_BYTES + i * 6144, &mm, blockIdx.x * 16, i * 192, xfull + 64);
    }
  }
  __syncthreads();
  pdl_launch();
  if (lane == 0) {
    if (warp < 8) { mbar_expect(xfull + warp * 8, 16384); tma2d(R + warp * 16384, &mx, warp * 64, mb * 128, xfull + warp * 8); }
    if (warp == 0) { mbar_expect(full, 16384); tma2d(RING, &mx, 512, mb * 128, full); }
    if (warp == 9) asm volatile("cp.async.bulk.prefetch.L2.global [%0],%1;" ::"l"(wqkv + blockIdx.x * 15552), "r"(15552) : "memory");
  }
  __syncwarp();
  if (warp >= 8) {
    REG_DEC(24);
    const int pt = tid - 256;
    if (pt == 0) {
      for (int st = 1; st < 4; st++) {
        mbar_expect(full + st * 8, 16384);
        tma2d(RING + st * STG_BYTES, &mw, nb * 216, st * 64 - 64, full + st * 8);
        tma2d(RING + st * STG_BYTES + 8192, &mw, nb * 216 + 64, st * 64 - 64, full + st * 8);
      }
    }
    if (blockIdx.x < 72) {
      float* sf = (float*)(smem_raw + R_BYTES + 4 * STG_BYTES + 18432);
      if (pt < 72) {
        const uint4 cv = __ldg((const uint4*)cvec + pt);
        const uint32_t cw[4] = {cv.x, cv.y, cv.z, cv.w};
#pragma unroll
        for (int i = 0; i < 4; i++) { sf[pt * 8 + 2 * i] = silu_f(bf_lo(cw[i])); sf[pt * 8 + 2 * i + 1] = silu_f(bf_hi(cw[i])); }
      }
      bar_sync(3, 128);
      mbar_wait(xfull + 64, 0);
      float acc[8] = {0, 0, 0, 0, 0, 0, 0, 0};
#pragma unroll 1
      for (int i = 0; i < 9; i++) fma8(acc, sf[(pt >> 1) + 64 * i], lds128(RING + 4 * STG_BYTES + i * 2048 + pt * 16));
#pragma unroll
      for (int j = 0; j < 8; j++)
#pragma unroll
        for (int o = 2; o < 32; o *= 2) acc[j] += __shfl_xor_sync(~0u, acc[j], o);
      if (lane < 2) {
#pragma unroll
        for (int j = 0; j < 8; j++) sf[DM + (warp - 8) * 16 + lane * 8 + j] = acc[j];
      }
      bar_sync(3, 128);
      if (pt < 16) {
        const float v = rbf(sf[DM + pt] + sf[DM + 16 + pt] + sf[DM + 32 + pt] + sf[DM + 48 + pt]);
        const int n = blockIdx.x * 16 + pt, shift = n < DM;
        const uint32_t word = pack_bf16(shift ? v : 1.0f + v, 1.0f);
        asm volatile("st.relaxed.gpu.global.u32 [%0],%1;" ::"l"((uint32_t*)g_ll + tab_pos(shift ? n : n - DM, shift)), "r"(word) : "memory");
      }
      fence_async_smem();
      __syncwarp();
      if (pt == 0) TS(0, 1);
    }
    if (warp == 8) {
      if (lane == 0) {
        int st = 4; uint32_t ph = 0;
        for (int it = 3; it < 18; it++) {
          const int t = it / 9, s = it - t * 9;
          mbar_wait(empty + st * 8, ph ^ 1);
          mbar_expect(full + st * 8, 16384);
          tma2d(RING + st * STG_BYTES, &mw, nb * 216 + t * 128, s * 64, full + st * 8);
          tma2d(RING + st * STG_BYTES + 8192, &mw, nb * 216 + t * 128 + 64, s * 64, full + st * 8);
          if (++st == NSTG) { st = 0; ph ^= 1; }
        }
      }
    } else {
      const int ht = tid - 288;
      bar_sync(1, 352);
      for (int i = ht; i < 12 * 128; i += 96) {
        const int slot = i >> 7, row = i & 127, type = (nb * 12 + slot) >> 5;
        uint32_t v = 0;
        if (type == 1) v = ((POLY_MASK >> ((row >> 3) & 7)) & 1) ? 0x43403F00u : 0x40253F80u;
        if (type == 2) v = 0x3F80u;
        const uint32_t ad = R + slot * 6144 + (row >> 3) * 384 + 256 + (row & 7) * 16;
        asm volatile("st.shared.b32 [%0],%1;" ::"r"(ad + 4), "r"(v) : "memory");
        asm volatile("st.shared.v2.b32 [%0],{%1,%1};" ::"r"(ad + 8), "r"(0) : "memory");
      }
      fence_async_smem();
      bar_sync(2, 352);
      if (ht == 0) {
        for (int s = 0; s < 7; s++) bulk_s2g(g_qkv + (size_t)(nb * 12 + s) * 98304 + mb * 6144, R + s * 6144, 6144);
        bulk_commit();
      }
      for (int s = warp - 9; s < 7; s += 3) {
        const int gs = nb * 12 + s;
        if ((gs >> 5) != 1) continue;
        float mx2 = 0;
#pragma unroll 1
        for (int row = lane; row < 128; row += 32) mx2 = fmaxf(mx2, knorm_row(R + s * 6144, row));
#pragma unroll
        for (int o = 16; o; o >>= 1) mx2 = fmaxf(mx2, __shfl_xor_sync(~0u, mx2, o));
        if (lane == 0) g_kmax[(gs & 31) * 16 + mb] = mx2;
      }
      if (ht == 0) bulk_wait0();
    }
  } else {
    REG_INC(240);
    TSS(0);
    const int rowl = warp * 16;
    uint4 s0, s1;
    {
      RowStat rs, rt;
      rs.init(); rt.init();
      uint32_t f[4][4];
#pragma unroll 1
      for (int c = 0; c < 9; c++) {
        mbar_wait(c < 8 ? xfull + c * 8 : full, 0);
        load_a_chunk(f, R + c * 16384, rowl, lane);
        rs.add(f[0]); rt.add(f[1]); rs.add(f[2]); rt.add(f[3]);
      }
      rs.merge(rt);
      rs.finish(lane, s0, s1);
    }
    TSS(1);
    if (tid < 144) {
      uint4 u, v;
      int n = 0;
      do {
        asm volatile("ld.relaxed.gpu.global.v4.u32 {%0,%1,%2,%3},[%4];" : "=r"(u.x), "=r"(u.y), "=r"(u.z), "=r"(u.w) : "l"(g_ll + tid * 2) : "memory");
        asm volatile("ld.relaxed.gpu.global.v4.u32 {%0,%1,%2,%3},[%4];" : "=r"(v.x), "=r"(v.y), "=r"(v.z), "=r"(v.w) : "l"(g_ll + tid * 2 + 1) : "memory");
        if (++n > 4000000) __trap();
      } while (((u.x & u.y & u.z & u.w & v.x & v.y & v.z & v.w) >> 16) != 0x3F80u);
      sts128(TAB + tid * 16, make_uint4(__byte_perm(u.x, u.y, 0x5410), __byte_perm(u.z, u.w, 0x5410), __byte_perm(v.x, v.y, 0x5410), __byte_perm(v.z, v.w, 0x5410)));
    }
    bar_sync(4, 256);
    TSS(2);
    uint32_t a[36][4];
    float acc[64];
    MMA_TILE_(wl_rs_n128_t1, 0, 0, if (s < 8) { LN_CHUNK(s) } if (s == 1) { LN_CHUNK(8) if (lane == 0) mbar_arrive(empty); } if (s == 7) bar_arrive(1, 352));
    TSS(3);
    bar_sync(4, 256);
    int t2 = threadIdx.x;
    asm volatile("" : "+r"(t2));
    qkv_stage<16, 0>(acc, R, (t2 >> 5) * 16 + ((t2 & 31) >> 2), t2 & 3, nb * 216);
    fence_async_smem();
    bar_arrive(2, 352);
    TSS(4);
    MMA_TILE(wl_rs_n88_t1, 1, 0);
    asm volatile("" : "+r"(t2));
    qkv_stage<11, 16>(acc, R, (t2 >> 5) * 16 + ((t2 & 31) >> 2), t2 & 3, nb * 216);
    fence_async_smem();
    bar_sync(4, 256);
    TSS(5);
    if (tid == 0) {
      for (int s = 7; s < 12; s++) bulk_s2g(g_qkv + (size_t)(nb * 12 + s) * 98304 + mb * 6144, R + s * 6144, 6144);
      bulk_commit();
    }
    if (warp >= 3 && ((nb * 12 + 4 + warp) >> 5) == 1) {
      float mx2 = 0;
#pragma unroll
      for (int i = 0; i < 4; i++) mx2 = fmaxf(mx2, knorm_row(R + (4 + warp) * 6144, lane + 32 * i));
#pragma unroll
      for (int o = 16; o; o >>= 1) mx2 = fmaxf(mx2, __shfl_xor_sync(~0u, mx2, o));
      if (lane == 0) g_kmax[((nb * 12 + 4 + warp) & 31) * 16 + mb] = mx2;
    }
    if (tid == 0) bulk_wait0();
    TSS(6);
    TSDUMP(1);
  }
}

#define ATT_SMEM (2 * 98304 + 1024 + 256)

__device__ __forceinline__ uint32_t exp2_pair_fma(float t0, float t1) {
  uint32_t y;
  asm("prmt.b32 %0,%1,%2,0x6521;" : "=r"(y) : "r"(__float_as_uint(t0)), "r"(__float_as_uint(t1)));
  return hfma2(y, y | 0x3F803F80u, y | 0x007F007Fu);
}

__device__ __forceinline__ void softmax_fast(const float* s, uint32_t* p) {
#pragma unroll
  for (int i = 0; i < 8; i++) {
    if ((POLY_MASK >> i) & 1) {
      p[2 * i] = exp2_pair_fma(s[4 * i], s[4 * i + 1]);
      p[2 * i + 1] = exp2_pair_fma(s[4 * i + 2], s[4 * i + 3]);
    } else {
      p[2 * i] = pack_bf16(ex2f(s[4 * i]), ex2f(s[4 * i + 1]));
      p[2 * i + 1] = pack_bf16(ex2f(s[4 * i + 2]), ex2f(s[4 * i + 3]));
    }
  }
}
#define QK_MMA(S, kd)                                                           \
  wl_rs_n64_t0<0>(S, q, (kd));                                                  \
  wl_rs_n64_t0<1>(S, q + 4, (kd) + 16 - (8ull << 16));
#define PV_MMA(P, vd)                                                           \
  _Pragma("unroll") for (int t = 0; t < 4; t++) wl_rs_n24_t1<1>(o, P + 4 * t, (vd) + t * 48);

__device__ __forceinline__ void att_store(const float* o, int row0, int head, int lane) {
  const int cq = lane & 3;
  const float l0 = __shfl_sync(~0u, o[8], (lane & ~3) | 1), l1 = __shfl_sync(~0u, o[10], (lane & ~3) | 1);
  const float i0 = rcp_fast(l0), i1 = rcp_fast(l1);
  uint32_t* og = (uint32_t*)(g_o + (size_t)row0 * DM + head * 18 + cq * 2);
  og[0] = pack_bf16(o[0] * i0, o[1] * i0);
  og[4] = pack_bf16(o[4] * i0, o[5] * i0);
  og[8 * DM / 2] = pack_bf16(o[2] * i1, o[3] * i1);
  og[8 * DM / 2 + 4] = pack_bf16(o[6] * i1, o[7] * i1);
  if (cq == 0) {
    og[8] = pack_bf16(o[8] * i0, o[9] * i0);
    og[8 * DM / 2 + 8] = pack_bf16(o[10] * i1, o[11] * i1);
  }
}

__global__ void __launch_bounds__(512, 1) k2_kernel(const uint8_t* __restrict__ wo, const uint8_t* __restrict__ wg_, const uint8_t* __restrict__ wu,
                                                    const uint8_t* __restrict__ wd, const __nv_bfloat16* __restrict__ cvec,
                                                    const __nv_bfloat16* __restrict__ wmod) {
  extern __shared__ __align__(1024) uint8_t smem_raw[];
  const uint32_t sb = (s2u(smem_raw) + 1023) & ~1023u;
  const uint32_t KS = sb, VS = sb + 98304, BAR = sb + 2 * 98304;
  const int tid = threadIdx.x, lane = tid & 31, warp = tid >> 5, wg = tid >> 7;
  if (blockIdx.x < 4) {
    float* sf = (float*)smem_raw;
    const int part = blockIdx.x + 2;
    for (int i = tid; i < DM; i += 512) sf[i] = silu_bf(cvec[i]);
    if (part == 2 && tid < 80) g_cnt[tid] = 0;
    __nanosleep(4000);
    __syncthreads();
    if (tid < 432) {
      const int cg = tid % 72, rg = tid / 72;
      const __nv_bfloat16* w = wmod + (size_t)rg * 96 * 3456 + part * DM + cg * 8;
      float acc[8] = {0, 0, 0, 0, 0, 0, 0, 0};
#pragma unroll 1
      for (int r = 0; r < 96; r += 12) {
        uint4 v[12];
#pragma unroll
        for (int i = 0; i < 12; i++) v[i] = __ldg((const uint4*)(w + (size_t)(r + i) * 3456));
#pragma unroll
        for (int i = 0; i < 12; i++) fma8(acc, sf[rg * 96 + r + i], v[i]);
      }
#pragma unroll
      for (int j = 0; j < 8; j++) sf[DM + rg * DM + cg * 8 + j] = acc[j];
    }
    __syncthreads();
    for (int col = tid; col < DM; col += 512) {
      float v = 0;
#pragma unroll
      for (int j = 1; j < 7; j++) v += sf[j * DM + col];
      v = rbf(v);
      if (part == 2) g_ga[col] = __float2bfloat16_rn(v);
      else if (part == 5) g_gb[col] = __float2bfloat16_rn(v);
      else ((__nv_bfloat16*)g_tab2)[tab_pos(col, part == 3)] = __float2bfloat16_rn(0.5f * (part == 3 ? v : rbf(1.0f + v)));
    }
    pdl_wait();
    if (part == 2 && tid < 288) g_ll[tid] = make_uint4(0, 0, 0, 0);
    if (tid == 0) TS(0, 0);
    return;
  }
  const int bid = blockIdx.x - 4, head = bid >> 2, qb = bid & 3;
  if (tid == 0) {
    TS(2, 0);
    for (int i = 0; i < 16; i++) mbar_init(BAR + i * 8, 1);
    fence_bar_init();
  }
  __syncthreads();
  const int g = lane >> 2, cq = lane & 3;
  const int row0 = qb * 512 + wg * 128 + (warp & 3) * 16 + g;
  const uint8_t* qg = g_qkv + (size_t)head * 98304 + (row0 >> 3) * 384 + (row0 & 7) * 16 + cq * 4;
  pdl_wait();
  pdl_launch();
  if (tid == 0) TS(2, 1);
  const uint8_t* kg = g_qkv + (size_t)(32 + head) * 98304;
#define KV_LOAD(c) { mbar_expect(BAR + (c) * 8, 12288); bulk_g2s(KS + (c) * 6144, kg + (c) * 6144, 6144, BAR + (c) * 8); \
                     bulk_g2s(VS + (c) * 6144, kg + 32 * 98304 + (c) * 6144, 6144, BAR + (c) * 8); }
  if (lane == 0 && warp < 5) KV_LOAD(warp);
  __syncwarp();
  uint32_t q[8], q2[6];
  float kmax2 = __ldcg(g_kmax + head * 16 + (lane & 15));
#pragma unroll
  for (int i = 0; i < 6; i++) {
    q[i] = __ldcg((const uint32_t*)(qg + (i & 1) * 384 + (i >> 1) * 128));
    q2[i] = __ldcg((const uint32_t*)(qg + 3072 + (i & 1) * 384 + (i >> 1) * 128));
  }
  q[6] = __ldcg((const uint32_t*)(qg + 256 + 12 - cq * 4)); q[7] = __ldcg((const uint32_t*)(qg + 256 + 8 - cq * 4));
  const uint64_t dk = mkdesc(KS, 128, 384, 0), dv = mkdesc(VS, 384, 128, 0);
#pragma unroll
  for (int o = 8; o; o >>= 1) kmax2 = fmaxf(kmax2, __shfl_xor_sync(~0u, kmax2, o));
  float bd[4] = {sq2(q[0]) + sq2(q[2]) + sq2(q[4]), sq2(q[1]) + sq2(q[3]) + sq2(q[5]),
                 sq2(q2[0]) + sq2(q2[2]) + sq2(q2[4]), sq2(q2[1]) + sq2(q2[3]) + sq2(q2[5])};
  int ok = 1;
  if (tid == 0 && bd[0] + bd[3] + kmax2 != 1.2345f) TS(2, 5);
#pragma unroll
  for (int i = 0; i < 4; i++) {
    bd[i] += __shfl_xor_sync(~0u, bd[i], 1); bd[i] += __shfl_xor_sync(~0u, bd[i], 2);
    bd[i] = sqrt_fast(bd[i] * kmax2) * 1.01f + 1.0f;
    ok = ok && (bd[i] <= 62.0f);
  }
  {
    uint32_t all;
    asm volatile("{.reg .pred p,q; setp.ne.b32 p,%1,0; barrier.red.and.pred q,1,512,p; selp.u32 %0,1,0,q;}"
                 : "=r"(all) : "r"(ok) : "memory");
    ok = __all_sync(~0u, all);
  }
  float o[12];
#pragma unroll
  for (int i = 0; i < 12; i++) { o[i] = 0.f; asm volatile("" : "+f"(o[i])); }
  float s[32];
  uint32_t p[16];
  if (tid == 0) TS(2, 2);
  if (ok) {
    if (cq == 1) {
      q[4] = pack_bf16(-bd[0], 1.0f); q[5] = pack_bf16(-bd[1], 1.0f);
      q2[4] = pack_bf16(-bd[2], 1.0f); q2[5] = pack_bf16(-bd[3], 1.0f);
    }
    mbar_wait(BAR, 0);
    WG_FENCE();
    QK_MMA(s, dk);
    WG_COMMIT();
#pragma unroll 1
    for (int tile = 0; tile < 2; tile++) {
#pragma unroll 1
      for (int jj = 0; jj < 8; jj++) {
        const uint64_t kd = dk + (uint32_t)(jj * 768), vd = dv + (uint32_t)(jj * 768), kn = dk + (uint32_t)(((jj + 1) & 7) * 768);
        if (tile == 0) {
          if (lane == 0 && warp < 2 && 2 * jj + 5 + warp < 16) KV_LOAD(2 * jj + 5 + warp);
          if (lane == 0 && warp >= 4 && warp < 8) {
            const uint8_t* w = warp == 4 ? wg_ : warp == 5 ? wu : warp == 6 ? wd : wo;
            const uint32_t n = warp == 7 ? 656 : 5184, o_ = (bid * 8 + jj) * n;
            if (warp < 7 || o_ + n <= DM * DM * 2) asm volatile("cp.async.bulk.prefetch.L2.global [%0],%1;" ::"l"(w + o_), "r"(n) : "memory");
          }
          __syncwarp();
          mbar_wait(BAR + jj * 16 + 8, 0); mbar_wait(BAR + ((jj * 16 + 16) & 127), 0); if (tid == 0) TS(2, 8 + jj); }
#pragma unroll
        for (int u = 0; u < 4; u++) {
          WG_WAIT(0);
          fence_regs<32>(s);
          softmax_fast(s, p);
          if (u == 3 && jj == 7) {
#pragma unroll
            for (int i = 0; i < 6; i++) q[i] = q2[i];
          }
          WG_FENCE();
          PV_MMA(p, vd + u * 192);
          QK_MMA(s, u < 3 ? kd + u * 192 + 192 : kn);
          WG_COMMIT();
        }
      }
      WG_WAIT(0);
      fence_regs<12>(o);
      att_store(o, row0 + tile * 64, head, lane);
#pragma unroll
      for (int i = 0; i < 12; i++) o[i] = 0.f;
      fence_regs<12>(o);
      if (tid == 0 && tile == 0) TS(2, 3);
    }
  } else {
    if (lane == 0 && warp >= 5) KV_LOAD(warp);
    __syncwarp();
#pragma unroll 1
    for (int tile = 0; tile < 2; tile++) {
      float m0 = -INFINITY, m1 = -INFINITY;
#pragma unroll 1
      for (int j = 0; j < 32; j++) {
        mbar_wait(BAR + (j >> 1) * 8, 0);
        WG_FENCE();
        QK_MMA(s, dk + (uint32_t)(j * 192));
        WG_COMMIT();
        WG_WAIT(0);
        fence_regs<32>(s);
#pragma unroll
        for (int i = 0; i < 32; i++) if ((POLY_MASK >> (i >> 2)) & 1) s[i] *= 2.0f;
        float x0 = m0, x1 = m1;
#pragma unroll
        for (int i = 0; i < 8; i++) {
          x0 = fmaxf(x0, fmaxf(s[4 * i], s[4 * i + 1]));
          x1 = fmaxf(x1, fmaxf(s[4 * i + 2], s[4 * i + 3]));
        }
        x0 = fmaxf(x0, __shfl_xor_sync(~0u, x0, 1)); x0 = fmaxf(x0, __shfl_xor_sync(~0u, x0, 2));
        x1 = fmaxf(x1, __shfl_xor_sync(~0u, x1, 1)); x1 = fmaxf(x1, __shfl_xor_sync(~0u, x1, 2));
        const float c0 = ex2f(m0 - x0), c1 = ex2f(m1 - x1);
        m0 = x0; m1 = x1;
#pragma unroll
        for (int i = 0; i < 3; i++) { o[4 * i] *= c0; o[4 * i + 1] *= c0; o[4 * i + 2] *= c1; o[4 * i + 3] *= c1; }
#pragma unroll
        for (int i = 0; i < 8; i++) {
          p[2 * i] = pack_bf16(ex2f(s[4 * i] - x0), ex2f(s[4 * i + 1] - x0));
          p[2 * i + 1] = pack_bf16(ex2f(s[4 * i + 2] - x1), ex2f(s[4 * i + 3] - x1));
        }
        WG_FENCE();
        PV_MMA(p, dv + (uint32_t)(j * 192));
        WG_COMMIT();
        WG_WAIT(0);
        fence_regs<12>(o);
      }
      att_store(o, row0 + tile * 64, head, lane);
#pragma unroll
      for (int i = 0; i < 12; i++) o[i] = 0.f;
#pragma unroll
      for (int i = 0; i < 6; i++) q[i] = q2[i];
    }
  }
  if (tid == 0) TS(2, 4);
}

#define K3_NSTG 4
#define K3_SMEM (9 * 16384 + K3_NSTG * 16384 + 1024 + 256)
__global__ void __launch_bounds__(288, 1) k3_kernel(const __grid_constant__ CUtensorMap mo, const __grid_constant__ CUtensorMap mw,
                                                    const __nv_bfloat16* __restrict__ x) {
  extern __shared__ __align__(1024) uint8_t smem_raw[];
  const uint32_t sb = (s2u(smem_raw) + 1023) & ~1023u;
  const uint32_t A = sb, RING = sb + 9 * 16384, BAR = RING + K3_NSTG * 16384;
  const uint32_t full = BAR, empty = BAR + 64, afull = BAR + 128;
  const int tid = threadIdx.x, lane = tid & 31, warp = tid >> 5;
  const int mb = blockIdx.x >> 3, nb = blockIdx.x & 7;
  if (tid == 0) {
    TS(3, 0);
    for (int i = 0; i < K3_NSTG; i++) { mbar_init(full + i * 8, 1); mbar_init(empty + i * 8, 8); }
    for (int i = 0; i < 9; i++) mbar_init(afull + i * 8, 1);
    fence_bar_init();
  }
  __syncthreads();
  if (warp == 8) {
    if (lane == 0) {
      for (int s = 0; s < K3_NSTG; s++) {
        mbar_expect(full + s * 8, 16384);
        tma2d(RING + s * 16384, &mw, nb * 72, s * 64, full + s * 8);
        tma2d(RING + s * 16384 + 8192, &mw, nb * 72 + 64, s * 64, full + s * 8);
      }
      pdl_wait();
      for (int c = 0; c < 9; c++) { mbar_expect(afull + c * 8, 16384); tma2d(A + c * 16384, &mo, c * 64, mb * 128, afull + c * 8); }
      for (int s = K3_NSTG; s < 9; s++) {
        const int st = s % K3_NSTG;
        mbar_wait(empty + st * 8, ((s / K3_NSTG) & 1) ^ 1);
        mbar_expect(full + st * 8, 16384);
        tma2d(RING + st * 16384, &mw, nb * 72, s * 64, full + st * 8);
        tma2d(RING + st * 16384 + 8192, &mw, nb * 72 + 64, s * 64, full + st * 8);
      }
    }
  } else {
    const int g = lane >> 2, cq = lane & 3;
    const int row = mb * 128 + warp * 16 + g, col = nb * 72 + cq * 2;
    uint32_t xv[18];
#pragma unroll
    for (int i = 0; i < 9; i++) {
      xv[2 * i] = __ldg((const uint32_t*)(x + (size_t)row * DM + col + 8 * i));
      xv[2 * i + 1] = __ldg((const uint32_t*)(x + (size_t)(row + 8) * DM + col + 8 * i));
    }
    pdl_wait();
    pdl_launch();
    if (tid == 0) TS(3, 1);
    float2 ga[9];
#pragma unroll
    for (int i = 0; i < 9; i++) { const uint32_t t = *(const uint32_t*)(g_ga + col + 8 * i); ga[i] = make_float2(bf_lo(t), bf_hi(t)); }
    float acc[36];
    const uint32_t abase = A + (warp >> 2) * 8192;
#pragma unroll
    for (int s = 0; s < 9; s++) {
      const int st = s % K3_NSTG;
      mbar_wait(afull + s * 8, 0);
      mbar_wait(full + st * 8, (s / K3_NSTG) & 1);
      WG_FENCE();
#pragma unroll
      for (int k = 0; k < 4; k++)
        wg_ss_n72_t1(acc, mkdesc(abase + s * 16384 + k * 32, 16, 1024, 1), mkdesc(RING + st * 16384 + k * 2048, 8192, 1024, 1), (s | k) != 0);
      WG_COMMIT();
      if (s > 0) { WG_WAIT(1); if (lane == 0) mbar_arrive(empty + ((s - 1) % K3_NSTG) * 8); }
    }
    WG_WAIT(0);
    if (tid == 0) TS(3, 2);
    float s0 = 0, s1 = 0;
#pragma unroll
    for (int i = 0; i < 9; i++) {
      acc[4 * i] = rbf(bf_lo(xv[2 * i]) + rbf(ga[i].x * rbf(acc[4 * i])));
      acc[4 * i + 1] = rbf(bf_hi(xv[2 * i]) + rbf(ga[i].y * rbf(acc[4 * i + 1])));
      acc[4 * i + 2] = rbf(bf_lo(xv[2 * i + 1]) + rbf(ga[i].x * rbf(acc[4 * i + 2])));
      acc[4 * i + 3] = rbf(bf_hi(xv[2 * i + 1]) + rbf(ga[i].y * rbf(acc[4 * i + 3])));
      *(uint32_t*)(g_x1 + (size_t)row * DM + col + 8 * i) = pack_bf16(acc[4 * i], acc[4 * i + 1]);
      *(uint32_t*)(g_x1 + (size_t)(row + 8) * DM + col + 8 * i) = pack_bf16(acc[4 * i + 2], acc[4 * i + 3]);
      s0 += acc[4 * i] + acc[4 * i + 1];
      s1 += acc[4 * i + 2] + acc[4 * i + 3];
    }
    s0 += __shfl_xor_sync(~0u, s0, 1); s0 += __shfl_xor_sync(~0u, s0, 2);
    s1 += __shfl_xor_sync(~0u, s1, 1); s1 += __shfl_xor_sync(~0u, s1, 2);
    const float m0 = s0 * (1.0f / 72), m1 = s1 * (1.0f / 72);
    float q0 = 0, q1 = 0;
#pragma unroll
    for (int i = 0; i < 9; i++) {
      q0 += (acc[4 * i] - m0) * (acc[4 * i] - m0) + (acc[4 * i + 1] - m0) * (acc[4 * i + 1] - m0);
      q1 += (acc[4 * i + 2] - m1) * (acc[4 * i + 2] - m1) + (acc[4 * i + 3] - m1) * (acc[4 * i + 3] - m1);
    }
    q0 += __shfl_xor_sync(~0u, q0, 1); q0 += __shfl_xor_sync(~0u, q0, 2);
    q1 += __shfl_xor_sync(~0u, q1, 1); q1 += __shfl_xor_sync(~0u, q1, 2);
    if (cq == 0) {
      g_stat2[row * 8 + nb] = make_float2(m0, q0);
      g_stat2[(row + 8) * 8 + nb] = make_float2(m1, q1);
    }
    if (tid == 0) TS(3, 3);
  }
}

__device__ __forceinline__ uint4 ln2_consts(int row, int cq) {
  const float4 p = *(const float4*)(g_stat2 + row * 8 + cq * 2);
  float s = p.x + p.z;
  s += __shfl_xor_sync(~0u, s, 1); s += __shfl_xor_sync(~0u, s, 2);
  const float mean = s * 0.125f;
  float q = p.y + p.w + 72.0f * ((p.x - mean) * (p.x - mean) + (p.z - mean) * (p.z - mean));
  q += __shfl_xor_sync(~0u, q, 1); q += __shfl_xor_sync(~0u, q, 2);
  return ln_consts(mean, q * (1.0f / DM));
}
__device__ __forceinline__ uint32_t glu_pair(float g0, float g1, float u0, float u1) {
  return pack_bf16(fmaf(tanhf_fast(g0), u0, u0), fmaf(tanhf_fast(g1), u1, u1));
}
template <int NG>
__device__ __forceinline__ void stage_part(const float* acc, uint32_t stg, int lane) {
  const int r = (lane & 7) + ((lane >> 3) & 1) * 8;
#pragma unroll
  for (int i = 0; i < NG; i += 2) {
    const int ch = i + (lane >> 4);
    stsm4(stg + r * (NG * 16) + ((ch ^ (r & 7)) << 4), pack_bf16(acc[4 * i], acc[4 * i + 1]), pack_bf16(acc[4 * i + 2], acc[4 * i + 3]),
          pack_bf16(acc[4 * i + 4], acc[4 * i + 5]), pack_bf16(acc[4 * i + 6], acc[4 * i + 7]));
  }
}
__device__ __forceinline__ uint32_t res_pair(uint32_t x, uint32_t g, float s0, float s1) { return hadd2(x, hmul2(g, pack_bf16(s0, s1))); }

__global__ void __launch_bounds__(384, 1) k4_kernel(const __grid_constant__ CUtensorMap mx, const __grid_constant__ CUtensorMap mg,
                                                    const __grid_constant__ CUtensorMap mu, const __grid_constant__ CUtensorMap md,
                                                    __nv_bfloat16* __restrict__ out) {
  extern __shared__ __align__(1024) uint8_t smem_raw[];
  const uint32_t sb = s2u(smem_raw);
  const uint32_t R = sb, RING = sb + R_BYTES, BAR = RING + NSTG * STG_BYTES, TAB = BAR + 512;
  const uint32_t full = BAR, empty = BAR + 64, xfull = BAR + 128, gfull = BAR + 272, sfull = BAR + 320;
  const int tid = threadIdx.x, lane = tid & 31, warp = tid >> 5;
  const int mb = blockIdx.x >> 3, fb = blockIdx.x & 7;
  if (tid == 0) {
    TS(4, 0);
    if (sb & 1023) __trap();
    for (int i = 0; i < 10; i++) mbar_init(sfull + i * 8, 4);
    for (int i = 0; i < NSTG; i++) { mbar_init(full + i * 8, 1); mbar_init(empty + i * 8, 8); }
    for (int i = 0; i < 9; i++) mbar_init(xfull + i * 8, 1);
    for (int i = 0; i < 5; i++) mbar_init(gfull + i * 8, 1);
    mbar_arrive(full);
    fence_bar_init();
  }
  __syncthreads();
  if (warp >= 8) {
    REG_DEC(24);
    if (lane == 0) {
      if (warp == 8) {
        int st = 1; uint32_t ph = 0;
        for (int it = 0; it < 126; it++) {
          if (it == NSTG - 1) {
            pdl_wait();
            for (int c = 0; c < 9; c++) {
              const int k = c < 2 ? c : (c == 2 ? 8 : c - 1);
              mbar_expect(xfull + c * 8, 16384);
              tma2d(R + k * 16384, &mx, k * 64, mb * 128, xfull + c * 8);
            }
          }
          const int t = it / 9, s = it - t * 9;
          const uint32_t dst = RING + st * STG_BYTES, fb_ = full + st * 8;
          mbar_wait(empty + st * 8, ph ^ 1);
          if (t < 9) {
            mbar_expect(fb_, 16384);
            tma2d(dst, &mg, fb * 576 + t * 64, s * 64, fb_);
            tma2d(dst + 8192, &mu, fb * 576 + t * 64, s * 64, fb_);
          } else {
            mbar_expect(fb_, t < 13 ? 16384 : 8192);
            tma2d(dst, &md, (t - 9) * 128, fb * 576 + s * 64, fb_);
            if (t < 13) tma2d(dst + 8192, &md, (t - 9) * 128 + 64, fb * 576 + s * 64, fb_);
          }
          if (++st == NSTG) { st = 0; ph ^= 1; }
        }
      } else if (warp < 11) {
        const int wg = warp - 9;
#pragma unroll 1
        for (int p = 0; p < 5; p++) {
          uint8_t* dst = g_part + (size_t)((fb * 16 + mb) * 5 + p) * 32768;
          mbar_wait(sfull + (p * 2 + wg) * 8, 0);
          if (p < 4) {
            bulk_s2g(dst + wg * 16384, R + p * 32768 + wg * 8192, 8192);
            bulk_s2g(dst + wg * 16384 + 8192, R + p * 32768 + 16384 + wg * 8192, 8192);
          } else {
            bulk_s2g(dst + wg * 8192, RING + wg * STG_BYTES + 8192, 8192);
          }
          bulk_commit();
          if (wg == 0 && p >= 3) TS(3, 11 + p);
          bulk_wait0();
          if (wg == 0) TS(3, 4 + p);
          asm volatile("fence.proxy.async.global;" ::: "memory");
          asm volatile("red.release.gpu.global.add.u32 [%0],1;" ::"l"(g_cnt + mb * 5 + p) : "memory");
        }
      } else {
        mbar_wait(sfull, 0);
#pragma unroll 1
        for (int p = 0; p < 5; p++) {
          unsigned int v; int n = 0;
          do {
            asm volatile("ld.acquire.gpu.global.u32 %0,[%1];" : "=r"(v) : "l"(g_cnt + mb * 5 + p) : "memory");
          } while (v < 16 && ++n < 20000000);
          if (v < 16) __trap();
          asm volatile("fence.proxy.async.global;" ::: "memory");
          TS(3, 9 + p);
          const uint32_t sz = p < 4 ? 4096 : 2048;
          mbar_expect(gfull + p * 8, sz * 8);
#pragma unroll 1
          for (int f = 0; f < 8; f++)
            bulk_g2s(p < 4 ? R + p * 32768 + f * 4096 : RING + (2 + (f >> 2)) * STG_BYTES + 8192 + (f & 3) * 2048,
                     g_part + (size_t)((f * 16 + mb) * 5 + p) * 32768 + fb * sz, sz, gfull + p * 8);
        }
      }
    }
  } else {
    REG_INC(240);
    uint32_t a[36][4];
    const int wg = warp >> 2, wl = warp & 3;
    if (tid < 144) sts128(TAB + tid * 16, g_tab2[tid]);
    bar_sync(1, 256);
    pdl_wait();
    TSS(0);
    float acc[64];
    const uint32_t hsp = R + warp * 2048 + lane * 16;
#define GLU_SPILL(t)                                                            \
  _Pragma("unroll") for (int j = 0; j < 4; j++) {                               \
    uint32_t h[4];                                                              \
    _Pragma("unroll") for (int e = 0; e < 4; e++)                               \
      h[e] = glu_pair(acc[8 * j + 2 * e], acc[8 * j + 2 * e + 1], acc[32 + 8 * j + 2 * e], acc[32 + 8 * j + 2 * e + 1]); \
    asm volatile("st.shared.v4.b32 [%0],{%1,%2,%3,%4};" ::"r"(hsp + (t) * 16384 + j * 512), "r"(h[0]), "r"(h[1]), "r"(h[2]), "r"(h[3]) : "memory"); \
  }
    {
      const uint4 s0 = ln2_consts(mb * 128 + warp * 16 + (lane >> 2), lane & 3), s1 = ln2_consts(mb * 128 + warp * 16 + (lane >> 2) + 8, lane & 3);
      TSS(1);
      MMA_TILE_(wl_rs_n128_t1, 0, 0,
                if (s < 8) { mbar_wait(xfull + (s + (s > 1)) * 8, 0); LN_CHUNK(s) }
                if (s == 1) { mbar_wait(xfull + 16, 0); LN_CHUNK(8) if (lane == 0) mbar_arrive(empty); });
    }
    GLU_SPILL(0);
#pragma unroll 1
    for (int t = 0; t < 3; t++) {
      MMA_TILE(wl_rs_n128_t1, 1, t & 1);
      GLU_SPILL(2 * t + 1);
      MMA_TILE(wl_rs_n128_t1, 0, (t & 1) ^ 1);
      GLU_SPILL(2 * t + 2);
    }
    MMA_TILE(wl_rs_n128_t1, 1, 1);
    GLU_SPILL(7);
    MMA_TILE(wl_rs_n128_t1, 0, 0);
#pragma unroll
    for (int j = 0; j < 4; j++)
#pragma unroll
      for (int e = 0; e < 4; e++)
        a[32 + j][e] = glu_pair(acc[8 * j + 2 * e], acc[8 * j + 2 * e + 1], acc[32 + 8 * j + 2 * e], acc[32 + 8 * j + 2 * e + 1]);
#pragma unroll
    for (int k = 0; k < 32; k++)
      asm volatile("ld.shared.v4.b32 {%0,%1,%2,%3},[%4];" : "=r"(a[k][0]), "=r"(a[k][1]), "=r"(a[k][2]), "=r"(a[k][3]) : "r"(hsp + (k >> 2) * 16384 + (k & 3) * 512) : "memory");
    TSS(2);
    const uint32_t stg = R + (wl >> 1) * 16384 + wg * 8192 + (wl & 1) * 4096;
#define PART_OUT(p)                                                             \
  stage_part<16>(acc, stg + (p) * 32768, lane);                                 \
  fence_async_smem();                                                           \
  __syncwarp();                                                                 \
  if (lane == 0) mbar_arrive(sfull + ((p) * 2 + wg) * 8);
    bar_sync(2 + wg, 128);
#pragma unroll 1
    for (int p = 0; p < 2; p++) {
      MMA_TILE(wl_rs_n128_t1, 1, p);
      PART_OUT(2 * p);
      MMA_TILE(wl_rs_n128_t1, 0, p ^ 1);
      PART_OUT(2 * p + 1);
    }
    MMA_TILE(wl_rs_n64_t1, 1, 0);
    stage_part<8>(acc, RING + wg * STG_BYTES + 8192 + wl * 2048, lane);
    fence_async_smem();
    __syncwarp();
    if (lane == 0) mbar_arrive(sfull + (8 + wg) * 8);
    TSS(3);
    const int rl = tid >> 4, ch = tid & 15;
    const size_t off = (size_t)(mb * 128 + fb * 16 + rl) * DM + ch * 8;
    uint4 xv[5], gv[5];
#pragma unroll
    for (int p = 0; p < 5; p++)
      if (p < 4 || ch < 8) { xv[p] = __ldcg((const uint4*)(g_x1 + off + p * 128)); gv[p] = __ldcg((const uint4*)(g_gb + p * 128 + ch * 8)); }
#pragma unroll
    for (int p = 0; p < 5; p++) {
      if (p == 4 && ch >= 8) break;
      mbar_wait(gfull + p * 8, 0);
      float r8[8] = {0, 0, 0, 0, 0, 0, 0, 0};
#pragma unroll
      for (int f = 0; f < 8; f++) {
        const uint4 v = lds128((p < 4 ? R + p * 32768 + f * 4096 + rl * 256 : RING + (2 + (f >> 2)) * STG_BYTES + 8192 + (f & 3) * 2048 + rl * 128) +
                               ((ch ^ (rl & 7)) << 4));
        r8[0] += bf_lo(v.x); r8[1] += bf_hi(v.x); r8[2] += bf_lo(v.y); r8[3] += bf_hi(v.y);
        r8[4] += bf_lo(v.z); r8[5] += bf_hi(v.z); r8[6] += bf_lo(v.w); r8[7] += bf_hi(v.w);
      }
      uint4 r;
      r.x = res_pair(xv[p].x, gv[p].x, r8[0], r8[1]);
      r.y = res_pair(xv[p].y, gv[p].y, r8[2], r8[3]);
      r.z = res_pair(xv[p].z, gv[p].z, r8[4], r8[5]);
      r.w = res_pair(xv[p].w, gv[p].w, r8[6], r8[7]);
      *(uint4*)(out + off + p * 128) = r;
      if (p >= 2) TSS(2 + p);
    }
    TSDUMP(4);
  }
}

typedef CUresult (*EncodeFn)(CUtensorMap*, CUtensorMapDataType, cuuint32_t, void*, const cuuint64_t*, const cuuint64_t*,
                             const cuuint32_t*, const cuuint32_t*, CUtensorMapInterleave, CUtensorMapSwizzle,
                             CUtensorMapL2promotion, CUtensorMapFloatOOBfill);
static void make_map(EncodeFn fn, CUtensorMap* m, const void* p, int rows, int cols, int box_rows, int box_cols = 64) {
  cuuint64_t dims[2] = {(cuuint64_t)cols, (cuuint64_t)rows};
  cuuint64_t strides[1] = {(cuuint64_t)cols * 2};
  cuuint32_t box[2] = {(cuuint32_t)box_cols, (cuuint32_t)box_rows};
  cuuint32_t es[2] = {1, 1};
  fn(m, CU_TENSOR_MAP_DATA_TYPE_BFLOAT16, 2, (void*)p, dims, strides, box, es, CU_TENSOR_MAP_INTERLEAVE_NONE,
     box_cols == 64 ? CU_TENSOR_MAP_SWIZZLE_128B : CU_TENSOR_MAP_SWIZZLE_NONE,
     box_cols == 64 ? CU_TENSOR_MAP_L2_PROMOTION_L2_256B : CU_TENSOR_MAP_L2_PROMOTION_NONE, CU_TENSOR_MAP_FLOAT_OOB_FILL_NONE);
}
template <typename... KA, typename... A>
static void launch(void (*k)(KA...), int grid, int block, int smem, bool pdl, A... args) {
  cudaLaunchConfig_t cfg = {};
  cfg.gridDim = dim3(grid); cfg.blockDim = dim3(block); cfg.dynamicSmemBytes = smem; cfg.stream = cudaStreamPerThread;
  cudaLaunchAttribute at;
  at.id = cudaLaunchAttributeProgrammaticStreamSerialization;
  at.val.programmaticStreamSerializationAllowed = 1;
  cfg.attrs = &at; cfg.numAttrs = pdl ? 1 : 0;
  cudaLaunchKernelEx(&cfg, k, KA(args)...);
}

extern "C" void kernel_launch(void* const* d_in, const int* in_sizes, int n_in, void* d_out, int out_size) {
  const __nv_bfloat16* x = (const __nv_bfloat16*)d_in[0];
  void* fnp = nullptr;
  cudaDriverEntryPointQueryResult qr;
  cudaGetDriverEntryPoint("cuTensorMapEncodeTiled", &fnp, cudaEnableDefault, &qr);
  EncodeFn fn = (EncodeFn)fnp;
  void *po, *px1;
  cudaGetSymbolAddress(&po, g_o);
  cudaGetSymbolAddress(&px1, g_x1);
  CUtensorMap mm, mx, mqkv, mo, mwo, mx1, mg, mu, md;
  make_map(fn, &mm, d_in[8], DM, 6 * DM, 192, 16);
  make_map(fn, &mx, x, SEQ, DM, 128);
  make_map(fn, &mqkv, d_in[1], DM, 3 * DM, 64);
  make_map(fn, &mo, po, SEQ, DM, 128);
  make_map(fn, &mwo, d_in[2], DM, DM, 64);
  make_map(fn, &mx1, px1, SEQ, DM, 128);
  make_map(fn, &mg, d_in[4], DM, FF, 64);
  make_map(fn, &mu, d_in[5], DM, FF, 64);
  make_map(fn, &md, d_in[6], FF, DM, 64);
  cudaFuncSetAttribute(k1_kernel, cudaFuncAttributeMaxDynamicSharedMemorySize, GEMM_SMEM);
  cudaFuncSetAttribute(k2_kernel, cudaFuncAttributeMaxDynamicSharedMemorySize, ATT_SMEM);
  cudaFuncSetAttribute(k3_kernel, cudaFuncAttributeMaxDynamicSharedMemorySize, K3_SMEM);
  cudaFuncSetAttribute(k4_kernel, cudaFuncAttributeMaxDynamicSharedMemorySize, GEMM_SMEM);
  launch(k1_kernel, 128, 384, GEMM_SMEM, false, mx, mqkv, mm, (const __nv_bfloat16*)d_in[7], (const uint8_t*)d_in[1]);
  launch(k2_kernel, 132, 512, ATT_SMEM, true, (const uint8_t*)d_in[2], (const uint8_t*)d_in[4], (const uint8_t*)d_in[5], (const uint8_t*)d_in[6],
         (const __nv_bfloat16*)d_in[7], (const __nv_bfloat16*)d_in[8]);
  launch(k3_kernel, 128, 288, K3_SMEM, true, mo, mwo, x);
  launch(k4_kernel, 128, 384, GEMM_SMEM, true, mx1, mg, mu, md, (__nv_bfloat16*)d_out);
}
```

```cpp
#include <cuda_runtime.h>
#include <cuda_bf16.h>
#include <cuda.h>
#include <stdint.h>

#define SEQ 2048
#define DM 576
#define NH 32
#define FF 4608

__device__ uint4 g_ll[36 * 4 * 2];
__device__ uint4 g_tab2[36 * 4];
__device__ __align__(16) __nv_bfloat16 g_ga[DM];
__device__ __align__(16) __nv_bfloat16 g_gb[DM];
__device__ float2 g_stat2[SEQ * 8];
__device__ __align__(1024) uint8_t g_qkv[96 * 98304];
__device__ float g_kmax[NH * 16];
__device__ __align__(1024) uint8_t g_o[SEQ * DM * 2];
__device__ __align__(1024) uint8_t g_x1[SEQ * DM * 2];
__device__ __align__(1024) uint4 g_wo[DM * DM / 8];
__device__ __align__(1024) uint8_t g_part[8 * 16 * 5 * 2 * 16384];
__device__ unsigned int g_cnt[16 * 5];

#define TS(k, i)
#define TSS(i)
#define TSDUMP(k)
__device__ __forceinline__ uint32_t s2u(const void* p) { return (uint32_t)__cvta_generic_to_shared(p); }
__device__ __forceinline__ void mbar_init(uint32_t b, int c) { asm volatile("mbarrier.init.shared::cta.b64 [%0],%1;" ::"r"(b), "r"(c)); }
__device__ __forceinline__ void mbar_expect(uint32_t b, uint32_t n) { asm volatile("mbarrier.arrive.expect_tx.shared::cta.b64 _,[%0],%1;" ::"r"(b), "r"(n) : "memory"); }
__device__ __forceinline__ void mbar_arrive(uint32_t b) { asm volatile("mbarrier.arrive.shared::cta.b64 _,[%0];" ::"r"(b) : "memory"); }
__device__ __forceinline__ void mbar_wait(uint32_t b, uint32_t ph) {
  asm volatile(
      "{.reg .pred p; .reg .u32 n;\n"
      "mbarrier.try_wait.parity.shared::cta.b64 p,[%0],%1;\n"
      "@p bra D;\n"
      "mov.u32 n,0;\n"
      "W: mbarrier.try_wait.parity.shared::cta.b64 p,[%0],%1;\n"
      "@p bra D;\n"
      "add.u32 n,n,1; setp.lt.u32 p,n,4000000; @p bra W;\n"
      "trap;\n"
      "D: }" ::"r"(b), "r"(ph) : "memory");
}
__device__ __forceinline__ void tma2d(uint32_t dst, const CUtensorMap* m, int c0, int c1, uint32_t bar) {
  asm volatile("cp.async.bulk.tensor.2d.shared::cluster.global.mbarrier::complete_tx::bytes [%0],[%1,{%3,%4}],[%2];"
               ::"r"(dst), "l"(m), "r"(bar), "r"(c0), "r"(c1) : "memory");
}
__device__ __forceinline__ void bulk_g2s(uint32_t dst, const void* src, uint32_t bytes, uint32_t bar) {
  asm volatile("cp.async.bulk.shared::cluster.global.mbarrier::complete_tx::bytes [%0],[%1],%2,[%3];"
               ::"r"(dst), "l"(src), "r"(bytes), "r"(bar) : "memory");
}
__device__ __forceinline__ void bulk_s2g(void* dst, uint32_t src, uint32_t bytes) {
  asm volatile("cp.async.bulk.global.shared::cta.bulk_group [%0],[%1],%2;" ::"l"(dst), "r"(src), "r"(bytes) : "memory");
}
__device__ __forceinline__ void bulk_commit() { asm volatile("cp.async.bulk.commit_group;" ::: "memory"); }
__device__ __forceinline__ void bulk_wait0() { asm volatile("cp.async.bulk.wait_group 0;" ::: "memory"); }
__device__ __forceinline__ void prefetch_map(const CUtensorMap* m) { asm volatile("prefetch.tensormap [%0];" ::"l"(m) : "memory"); }
__device__ __forceinline__ void fence_async_smem() { asm volatile("fence.proxy.async.shared::cta;" ::: "memory"); }
__device__ __forceinline__ void fence_bar_init() { asm volatile("fence.mbarrier_init.release.cluster;" ::: "memory"); }
__device__ __forceinline__ void pdl_wait() { asm volatile("griddepcontrol.wait;" ::: "memory"); }
__device__ __forceinline__ void pdl_launch() { asm volatile("griddepcontrol.launch_dependents;" ::: "memory"); }
__device__ __forceinline__ void bar_sync(int id, int n) { asm volatile("bar.sync %0,%1;" ::"r"(id), "r"(n) : "memory"); }
__device__ __forceinline__ void bar_arrive(int id, int n) { asm volatile("bar.arrive %0,%1;" ::"r"(id), "r"(n) : "memory"); }
#define WG_FENCE() asm volatile("wgmma.fence.sync.aligned;" ::: "memory")
#define WG_COMMIT() asm volatile("wgmma.commit_group.sync.aligned;" ::: "memory")
#define WG_WAIT(n) asm volatile("wgmma.wait_group.sync.aligned " #n ";" ::: "memory")
template <int N> __device__ __forceinline__ void fence_regs(float* r) {
#pragma unroll
  for (int i = 0; i < N; i++) asm volatile("" : "+f"(r[i])::"memory");
}
#define REG_INC(n) asm volatile("setmaxnreg.inc.sync.aligned.u32 " #n ";")
#define REG_DEC(n) asm volatile("setmaxnreg.dec.sync.aligned.u32 " #n ";")
__device__ __forceinline__ uint64_t mkdesc(uint32_t addr, uint32_t lbo, uint32_t sbo, int sw) {
  return (uint64_t)((addr & 0x3FFFF) >> 4) | ((uint64_t)(lbo >> 4) << 16) | ((uint64_t)(sbo >> 4) << 32) | ((uint64_t)sw << 62);
}
__device__ __forceinline__ void ldsm4(uint32_t* r, uint32_t addr) {
  asm volatile("ldmatrix.sync.aligned.m8n8.x4.shared.b16 {%0,%1,%2,%3},[%4];" : "=r"(r[0]), "=r"(r[1]), "=r"(r[2]), "=r"(r[3]) : "r"(addr) : "memory");
}
__device__ __forceinline__ void stsm4(uint32_t addr, uint32_t r0, uint32_t r1, uint32_t r2, uint32_t r3) {
  asm volatile("stmatrix.sync.aligned.m8n8.x4.shared.b16 [%0],{%1,%2,%3,%4};" ::"r"(addr), "r"(r0), "r"(r1), "r"(r2), "r"(r3) : "memory");
}
__device__ __forceinline__ uint32_t pack_bf16(float lo, float hi) {
  uint32_t r;
  asm("cvt.rn.bf16x2.f32 %0,%1,%2;" : "=r"(r) : "f"(hi), "f"(lo));
  return r;
}
__device__ __forceinline__ float bf_lo(uint32_t v) { return __uint_as_float(v << 16); }
__device__ __forceinline__ float bf_hi(uint32_t v) { return __uint_as_float(v & 0xFFFF0000u); }
__device__ __forceinline__ float sq2(uint32_t v) { return bf_lo(v) * bf_lo(v) + bf_hi(v) * bf_hi(v); }
__device__ __forceinline__ float rbf(float x) { return __bfloat162float(__float2bfloat16_rn(x)); }
__device__ __forceinline__ uint32_t hfma2(uint32_t a, uint32_t b, uint32_t c) {
  uint32_t r;
  asm("fma.rn.bf16x2 %0,%1,%2,%3;" : "=r"(r) : "r"(a), "r"(b), "r"(c));
  return r;
}
__device__ __forceinline__ uint32_t hadd2(uint32_t a, uint32_t b) {
  uint32_t r;
  asm("add.rn.bf16x2 %0,%1,%2;" : "=r"(r) : "r"(a), "r"(b));
  return r;
}
__device__ __forceinline__ uint32_t hmul2(uint32_t a, uint32_t b) {
  uint32_t r;
  asm("mul.rn.bf16x2 %0,%1,%2;" : "=r"(r) : "r"(a), "r"(b));
  return r;
}
__device__ __forceinline__ uint32_t hneg2(uint32_t a) {
  uint32_t r;
  asm("neg.bf16x2 %0,%1;" : "=r"(r) : "r"(a));
  return r;
}
__device__ __forceinline__ float ex2f(float x) {
  float r;
  asm("ex2.approx.ftz.f32 %0,%1;" : "=f"(r) : "f"(x));
  return r;
}
__device__ __forceinline__ float sqrt_fast(float x) {
  float r;
  asm("sqrt.approx.f32 %0,%1;" : "=f"(r) : "f"(x));
  return r;
}
__device__ __forceinline__ float rcp_fast(float x) {
  float r;
  asm("rcp.approx.f32 %0,%1;" : "=f"(r) : "f"(x));
  return r;
}
__device__ __forceinline__ float tanhf_fast(float x) {
  float r;
  asm("tanh.approx.f32 %0,%1;" : "=f"(r) : "f"(x));
  return r;
}
__device__ __forceinline__ uint4 ln_consts(float mean, float var) {
  float m = rbf(mean), v = rbf(var);
  float s = rbf(sqrtf(rbf(v + 1e-5f)));
  float r = 1.0f / s;
  float rh = rbf(r), rl = r - rh;
  return make_uint4(pack_bf16(-m, -m), pack_bf16(rh, rh), pack_bf16(rl, rl), 0u);
}
__device__ __forceinline__ uint32_t ln_apply(uint32_t x, const uint4& st, uint32_t a, uint32_t s) {
  uint32_t d = hadd2(x, st.x);
  uint32_t n = hfma2(d, st.y, hmul2(d, st.z));
  return hfma2(n, a, s);
}

__device__ __forceinline__ uint4 lds128(uint32_t a) {
  uint4 v;
  asm volatile("ld.shared.v4.b32 {%0,%1,%2,%3},[%4];" : "=r"(v.x), "=r"(v.y), "=r"(v.z), "=r"(v.w) : "r"(a) : "memory");
  return v;
}
__device__ __forceinline__ void sts128(uint32_t a, const uint4& v) {
  asm volatile("st.shared.v4.b32 [%0],{%1,%2,%3,%4};" ::"r"(a), "r"(v.x), "r"(v.y), "r"(v.z), "r"(v.w) : "memory");
}
__device__ __forceinline__ void hmma(float* c, const uint32_t* a, uint32_t b0, uint32_t b1) {
  asm volatile("mma.sync.aligned.m16n8k16.row.col.f32.bf16.bf16.f32 {%0,%1,%2,%3},{%4,%5,%6,%7},{%8,%9},{%0,%1,%2,%3};"
               : "+f"(c[0]), "+f"(c[1]), "+f"(c[2]), "+f"(c[3]) : "r"(a[0]), "r"(a[1]), "r"(a[2]), "r"(a[3]), "r"(b0), "r"(b1));
}
struct RowStat {
  float s[4], q0[4], q1[4];
  __device__ __forceinline__ void init() {
#pragma unroll
    for (int i = 0; i < 4; i++) s[i] = q0[i] = q1[i] = 0.f;
  }
  __device__ __forceinline__ void add(const uint32_t* a) {
    hmma(s, a, 0x3F803F80u, 0x3F803F80u);
    hmma(q0, a, a[0], a[2]);
    hmma(q1, a, a[1], a[3]);
  }
  __device__ __forceinline__ void merge(const RowStat& o) {
#pragma unroll
    for (int i = 0; i < 4; i++) { s[i] += o.s[i]; q0[i] += o.q0[i]; q1[i] += o.q1[i]; }
  }
  __device__ __forceinline__ void finish(int lane, uint4& c0, uint4& c1) {
    const int g = lane >> 2, src = (lane & ~3) | (g >> 1);
    const float a0 = __shfl_sync(~0u, (g & 1) ? q0[1] : q0[0], src), a1 = __shfl_sync(~0u, (g & 1) ? q1[3] : q1[2], src);
    const float m0 = s[0] * (1.0f / DM), m1 = s[2] * (1.0f / DM);
    c0 = ln_consts(m0, fmaxf(a0 * (1.0f / DM) - m0 * m0, 0.f));
    c1 = ln_consts(m1, fmaxf(a1 * (1.0f / DM) - m1 * m1, 0.f));
  }
};
#define LN_CHUNK(c, LOAD)                                                       \
  LOAD(&a[(c) * 4], R + (c) * 16384, warp * 16, lane);                          \
  _Pragma("unroll") for (int k = (c) * 4; k < (c) * 4 + 4; k++) {               \
    const uint4 t = lds128(TAB + (k * 4 + (lane & 3)) * 16);                    \
    a[k][0] = ln_apply(a[k][0], s0, t.x, t.y);                                  \
    a[k][1] = ln_apply(a[k][1], s1, t.x, t.y);                                  \
    a[k][2] = ln_apply(a[k][2], s0, t.z, t.w);                                  \
    a[k][3] = ln_apply(a[k][3], s1, t.z, t.w);                                  \
  }

__device__ __forceinline__ void wg_ss_n72_t1(float* d, uint64_t da, uint64_t db, int sc) {
  asm volatile("{.reg .pred p; setp.ne.b32 p,%38,0; wgmma.mma_async.sync.aligned.m64n72k16.f32.bf16.bf16 {%0,%1,%2,%3,%4,%5,%6,%7,%8,%9,%10,%11,%12,%13,%14,%15,%16,%17,%18,%19,%20,%21,%22,%23,%24,%25,%26,%27,%28,%29,%30,%31,%32,%33,%34,%35}, %36, %37, p,1,1,0,1;}"
  : "+f"(d[0]),"+f"(d[1]),"+f"(d[2]),"+f"(d[3]),"+f"(d[4]),"+f"(d[5]),"+f"(d[6]),"+f"(d[7]),"+f"(d[8]),"+f"(d[9]),"+f"(d[10]),"+f"(d[11]),"+f"(d[12]),"+f"(d[13]),"+f"(d[14]),"+f"(d[15]),"+f"(d[16]),"+f"(d[17]),"+f"(d[18]),"+f"(d[19]),"+f"(d[20]),"+f"(d[21]),"+f"(d[22]),"+f"(d[23]),"+f"(d[24]),"+f"(d[25]),"+f"(d[26]),"+f"(d[27]),"+f"(d[28]),"+f"(d[29]),"+f"(d[30]),"+f"(d[31]),"+f"(d[32]),"+f"(d[33]),"+f"(d[34]),"+f"(d[35]) : "l"(da),"l"(db),"r"(sc));
}
template <int SC> __device__ __forceinline__ void wl_rs_n128_t1(float* d, const uint32_t* a, uint64_t e) {
  if (SC) asm volatile("wgmma.mma_async.sync.aligned.m64n128k16.f32.bf16.bf16 {%0,%1,%2,%3,%4,%5,%6,%7,%8,%9,%10,%11,%12,%13,%14,%15,%16,%17,%18,%19,%20,%21,%22,%23,%24,%25,%26,%27,%28,%29,%30,%31,%32,%33,%34,%35,%36,%37,%38,%39,%40,%41,%42,%43,%44,%45,%46,%47,%48,%49,%50,%51,%52,%53,%54,%55,%56,%57,%58,%59,%60,%61,%62,%63}, {%64,%65,%66,%67}, %68, 1,1,1,1;"
  : "+f"(d[0]),"+f"(d[1]),"+f"(d[2]),"+f"(d[3]),"+f"(d[4]),"+f"(d[5]),"+f"(d[6]),"+f"(d[7]),"+f"(d[8]),"+f"(d[9]),"+f"(d[10]),"+f"(d[11]),"+f"(d[12]),"+f"(d[13]),"+f"(d[14]),"+f"(d[15]),"+f"(d[16]),"+f"(d[17]),"+f"(d[18]),"+f"(d[19]),"+f"(d[20]),"+f"(d[21]),"+f"(d[22]),"+f"(d[23]),"+f"(d[24]),"+f"(d[25]),"+f"(d[26]),"+f"(d[27]),"+f"(d[28]),"+f"(d[29]),"+f"(d[30]),"+f"(d[31]),"+f"(d[32]),"+f"(d[33]),"+f"(d[34]),"+f"(d[35]),"+f"(d[36]),"+f"(d[37]),"+f"(d[38]),"+f"(d[39]),"+f"(d[40]),"+f"(d[41]),"+f"(d[42]),"+f"(d[43]),"+f"(d[44]),"+f"(d[45]),"+f"(d[46]),"+f"(d[47]),"+f"(d[48]),"+f"(d[49]),"+f"(d[50]),"+f"(d[51]),"+f"(d[52]),"+f"(d[53]),"+f"(d[54]),"+f"(d[55]),"+f"(d[56]),"+f"(d[57]),"+f"(d[58]),"+f"(d[59]),"+f"(d[60]),"+f"(d[61]),"+f"(d[62]),"+f"(d[63]) : "r"(a[0]),"r"(a[1]),"r"(a[2]),"r"(a[3]),"l"(e));
  else asm volatile("wgmma.mma_async.sync.aligned.m64n128k16.f32.bf16.bf16 {%0,%1,%2,%3,%4,%5,%6,%7,%8,%9,%10,%11,%12,%13,%14,%15,%16,%17,%18,%19,%20,%21,%22,%23,%24,%25,%26,%27,%28,%29,%30,%31,%32,%33,%34,%35,%36,%37,%38,%39,%40,%41,%42,%43,%44,%45,%46,%47,%48,%49,%50,%51,%52,%53,%54,%55,%56,%57,%58,%59,%60,%61,%62,%63}, {%64,%65,%66,%67}, %68, 0,1,1,1;"
  : "=f"(d[0]),"=f"(d[1]),"=f"(d[2]),"=f"(d[3]),"=f"(d[4]),"=f"(d[5]),"=f"(d[6]),"=f"(d[7]),"=f"(d[8]),"=f"(d[9]),"=f"(d[10]),"=f"(d[11]),"=f"(d[12]),"=f"(d[13]),"=f"(d[14]),"=f"(d[15]),"=f"(d[16]),"=f"(d[17]),"=f"(d[18]),"=f"(d[19]),"=f"(d[20]),"=f"(d[21]),"=f"(d[22]),"=f"(d[23]),"=f"(d[24]),"=f"(d[25]),"=f"(d[26]),"=f"(d[27]),"=f"(d[28]),"=f"(d[29]),"=f"(d[30]),"=f"(d[31]),"=f"(d[32]),"=f"(d[33]),"=f"(d[34]),"=f"(d[35]),"=f"(d[36]),"=f"(d[37]),"=f"(d[38]),"=f"(d[39]),"=f"(d[40]),"=f"(d[41]),"=f"(d[42]),"=f"(d[43]),"=f"(d[44]),"=f"(d[45]),"=f"(d[46]),"=f"(d[47]),"=f"(d[48]),"=f"(d[49]),"=f"(d[50]),"=f"(d[51]),"=f"(d[52]),"=f"(d[53]),"=f"(d[54]),"=f"(d[55]),"=f"(d[56]),"=f"(d[57]),"=f"(d[58]),"=f"(d[59]),"=f"(d[60]),"=f"(d[61]),"=f"(d[62]),"=f"(d[63]) : "r"(a[0]),"r"(a[1]),"r"(a[2]),"r"(a[3]),"l"(e));
}
template <int SC> __device__ __forceinline__ void wl_rs_n24_t1(float* d, const uint32_t* a, uint64_t e) {
  if (SC) asm volatile("wgmma.mma_async.sync.aligned.m64n24k16.f32.bf16.bf16 {%0,%1,%2,%3,%4,%5,%6,%7,%8,%9,%10,%11}, {%12,%13,%14,%15}, %16, 1,1,1,1;"
  : "+f"(d[0]),"+f"(d[1]),"+f"(d[2]),"+f"(d[3]),"+f"(d[4]),"+f"(d[5]),"+f"(d[6]),"+f"(d[7]),"+f"(d[8]),"+f"(d[9]),"+f"(d[10]),"+f"(d[11]) : "r"(a[0]),"r"(a[1]),"r"(a[2]),"r"(a[3]),"l"(e));
  else asm volatile("wgmma.mma_async.sync.aligned.m64n24k16.f32.bf16.bf16 {%0,%1,%2,%3,%4,%5,%6,%7,%8,%9,%10,%11}, {%12,%13,%14,%15}, %16, 0,1,1,1;"
  : "=f"(d[0]),"=f"(d[1]),"=f"(d[2]),"=f"(d[3]),"=f"(d[4]),"=f"(d[5]),"=f"(d[6]),"=f"(d[7]),"=f"(d[8]),"=f"(d[9]),"=f"(d[10]),"=f"(d[11]) : "r"(a[0]),"r"(a[1]),"r"(a[2]),"r"(a[3]),"l"(e));
}
template <int SC> __device__ __forceinline__ void wl_rs_n64_t0(float* d, const uint32_t* a, uint64_t e) {
  if (SC) asm volatile("wgmma.mma_async.sync.aligned.m64n64k16.f32.bf16.bf16 {%0,%1,%2,%3,%4,%5,%6,%7,%8,%9,%10,%11,%12,%13,%14,%15,%16,%17,%18,%19,%20,%21,%22,%23,%24,%25,%26,%27,%28,%29,%30,%31}, {%32,%33,%34,%35}, %36, 1,1,1,0;"
  : "+f"(d[0]),"+f"(d[1]),"+f"(d[2]),"+f"(d[3]),"+f"(d[4]),"+f"(d[5]),"+f"(d[6]),"+f"(d[7]),"+f"(d[8]),"+f"(d[9]),"+f"(d[10]),"+f"(d[11]),"+f"(d[12]),"+f"(d[13]),"+f"(d[14]),"+f"(d[15]),"+f"(d[16]),"+f"(d[17]),"+f"(d[18]),"+f"(d[19]),"+f"(d[20]),"+f"(d[21]),"+f"(d[22]),"+f"(d[23]),"+f"(d[24]),"+f"(d[25]),"+f"(d[26]),"+f"(d[27]),"+f"(d[28]),"+f"(d[29]),"+f"(d[30]),"+f"(d[31]) : "r"(a[0]),"r"(a[1]),"r"(a[2]),"r"(a[3]),"l"(e));
  else asm volatile("wgmma.mma_async.sync.aligned.m64n64k16.f32.bf16.bf16 {%0,%1,%2,%3,%4,%5,%6,%7,%8,%9,%10,%11,%12,%13,%14,%15,%16,%17,%18,%19,%20,%21,%22,%23,%24,%25,%26,%27,%28,%29,%30,%31}, {%32,%33,%34,%35}, %36, 0,1,1,0;"
  : "=f"(d[0]),"=f"(d[1]),"=f"(d[2]),"=f"(d[3]),"=f"(d[4]),"=f"(d[5]),"=f"(d[6]),"=f"(d[7]),"=f"(d[8]),"=f"(d[9]),"=f"(d[10]),"=f"(d[11]),"=f"(d[12]),"=f"(d[13]),"=f"(d[14]),"=f"(d[15]),"=f"(d[16]),"=f"(d[17]),"=f"(d[18]),"=f"(d[19]),"=f"(d[20]),"=f"(d[21]),"=f"(d[22]),"=f"(d[23]),"=f"(d[24]),"=f"(d[25]),"=f"(d[26]),"=f"(d[27]),"=f"(d[28]),"=f"(d[29]),"=f"(d[30]),"=f"(d[31]) : "r"(a[0]),"r"(a[1]),"r"(a[2]),"r"(a[3]),"l"(e));
}
template <int SC> __device__ __forceinline__ void wl_rs_n64_t1(float* d, const uint32_t* a, uint64_t e) {
  if (SC) asm volatile("wgmma.mma_async.sync.aligned.m64n64k16.f32.bf16.bf16 {%0,%1,%2,%3,%4,%5,%6,%7,%8,%9,%10,%11,%12,%13,%14,%15,%16,%17,%18,%19,%20,%21,%22,%23,%24,%25,%26,%27,%28,%29,%30,%31}, {%32,%33,%34,%35}, %36, 1,1,1,1;"
  : "+f"(d[0]),"+f"(d[1]),"+f"(d[2]),"+f"(d[3]),"+f"(d[4]),"+f"(d[5]),"+f"(d[6]),"+f"(d[7]),"+f"(d[8]),"+f"(d[9]),"+f"(d[10]),"+f"(d[11]),"+f"(d[12]),"+f"(d[13]),"+f"(d[14]),"+f"(d[15]),"+f"(d[16]),"+f"(d[17]),"+f"(d[18]),"+f"(d[19]),"+f"(d[20]),"+f"(d[21]),"+f"(d[22]),"+f"(d[23]),"+f"(d[24]),"+f"(d[25]),"+f"(d[26]),"+f"(d[27]),"+f"(d[28]),"+f"(d[29]),"+f"(d[30]),"+f"(d[31]) : "r"(a[0]),"r"(a[1]),"r"(a[2]),"r"(a[3]),"l"(e));
  else asm volatile("wgmma.mma_async.sync.aligned.m64n64k16.f32.bf16.bf16 {%0,%1,%2,%3,%4,%5,%6,%7,%8,%9,%10,%11,%12,%13,%14,%15,%16,%17,%18,%19,%20,%21,%22,%23,%24,%25,%26,%27,%28,%29,%30,%31}, {%32,%33,%34,%35}, %36, 0,1,1,1;"
  : "=f"(d[0]),"=f"(d[1]),"=f"(d[2]),"=f"(d[3]),"=f"(d[4]),"=f"(d[5]),"=f"(d[6]),"=f"(d[7]),"=f"(d[8]),"=f"(d[9]),"=f"(d[10]),"=f"(d[11]),"=f"(d[12]),"=f"(d[13]),"=f"(d[14]),"=f"(d[15]),"=f"(d[16]),"=f"(d[17]),"=f"(d[18]),"=f"(d[19]),"=f"(d[20]),"=f"(d[21]),"=f"(d[22]),"=f"(d[23]),"=f"(d[24]),"=f"(d[25]),"=f"(d[26]),"=f"(d[27]),"=f"(d[28]),"=f"(d[29]),"=f"(d[30]),"=f"(d[31]) : "r"(a[0]),"r"(a[1]),"r"(a[2]),"r"(a[3]),"l"(e));
}
template <int SC> __device__ __forceinline__ void wl_rs_n88_t1(float* d, const uint32_t* a, uint64_t e) {
  if (SC) asm volatile("wgmma.mma_async.sync.aligned.m64n88k16.f32.bf16.bf16 {%0,%1,%2,%3,%4,%5,%6,%7,%8,%9,%10,%11,%12,%13,%14,%15,%16,%17,%18,%19,%20,%21,%22,%23,%24,%25,%26,%27,%28,%29,%30,%31,%32,%33,%34,%35,%36,%37,%38,%39,%40,%41,%42,%43}, {%44,%45,%46,%47}, %48, 1,1,1,1;"
  : "+f"(d[0]),"+f"(d[1]),"+f"(d[2]),"+f"(d[3]),"+f"(d[4]),"+f"(d[5]),"+f"(d[6]),"+f"(d[7]),"+f"(d[8]),"+f"(d[9]),"+f"(d[10]),"+f"(d[11]),"+f"(d[12]),"+f"(d[13]),"+f"(d[14]),"+f"(d[15]),"+f"(d[16]),"+f"(d[17]),"+f"(d[18]),"+f"(d[19]),"+f"(d[20]),"+f"(d[21]),"+f"(d[22]),"+f"(d[23]),"+f"(d[24]),"+f"(d[25]),"+f"(d[26]),"+f"(d[27]),"+f"(d[28]),"+f"(d[29]),"+f"(d[30]),"+f"(d[31]),"+f"(d[32]),"+f"(d[33]),"+f"(d[34]),"+f"(d[35]),"+f"(d[36]),"+f"(d[37]),"+f"(d[38]),"+f"(d[39]),"+f"(d[40]),"+f"(d[41]),"+f"(d[42]),"+f"(d[43]) : "r"(a[0]),"r"(a[1]),"r"(a[2]),"r"(a[3]),"l"(e));
  else asm volatile("wgmma.mma_async.sync.aligned.m64n88k16.f32.bf16.bf16 {%0,%1,%2,%3,%4,%5,%6,%7,%8,%9,%10,%11,%12,%13,%14,%15,%16,%17,%18,%19,%20,%21,%22,%23,%24,%25,%26,%27,%28,%29,%30,%31,%32,%33,%34,%35,%36,%37,%38,%39,%40,%41,%42,%43}, {%44,%45,%46,%47}, %48, 0,1,1,1;"
  : "=f"(d[0]),"=f"(d[1]),"=f"(d[2]),"=f"(d[3]),"=f"(d[4]),"=f"(d[5]),"=f"(d[6]),"=f"(d[7]),"=f"(d[8]),"=f"(d[9]),"=f"(d[10]),"=f"(d[11]),"=f"(d[12]),"=f"(d[13]),"=f"(d[14]),"=f"(d[15]),"=f"(d[16]),"=f"(d[17]),"=f"(d[18]),"=f"(d[19]),"=f"(d[20]),"=f"(d[21]),"=f"(d[22]),"=f"(d[23]),"=f"(d[24]),"=f"(d[25]),"=f"(d[26]),"=f"(d[27]),"=f"(d[28]),"=f"(d[29]),"=f"(d[30]),"=f"(d[31]),"=f"(d[32]),"=f"(d[33]),"=f"(d[34]),"=f"(d[35]),"=f"(d[36]),"=f"(d[37]),"=f"(d[38]),"=f"(d[39]),"=f"(d[40]),"=f"(d[41]),"=f"(d[42]),"=f"(d[43]) : "r"(a[0]),"r"(a[1]),"r"(a[2]),"r"(a[3]),"l"(e));
}

#define POLY_MASK 0xB5u
#define QSCALE (0.23570226039551584f * 1.4426950408889634f)

#define NSTG 6
#define STG_BYTES 16384
#define R_BYTES (8 * 16384)
#define GEMM_SMEM (R_BYTES + NSTG * STG_BYTES + 3072)

__device__ __forceinline__ void load_a_chunk(uint32_t (*a)[4], uint32_t chunk_base, int row_in_tile, int lane) {
  const int r = row_in_tile + (lane & 7) + ((lane >> 3) & 1) * 8;
  const uint32_t rb = chunk_base + r * 128;
#pragma unroll
  for (int k = 0; k < 4; k++) ldsm4(a[k], rb + (((k * 2 + (lane >> 4)) ^ (r & 7)) << 4));
}

__device__ __forceinline__ void load_a_core(uint32_t (*a)[4], uint32_t chunk_base, int row_in_tile, int lane) {
  const uint32_t rb = chunk_base + (row_in_tile >> 6) * 8192 + ((row_in_tile & 63) + (lane & 15)) * 16 + (lane >> 4) * 1024;
#pragma unroll
  for (int k = 0; k < 4; k++) ldsm4(a[k], rb + k * 2048);
}

#define MMA_TILE(FN, ODD, pj) MMA_TILE_(FN, ODD, pj, )
#define MMA_TILE_(FN, ODD, pj, PRE)                                             \
  {                                                                             \
    uint32_t rb_ = RING >> 4;                                                   \
    asm volatile("" : "+r"(rb_));                                               \
    const uint64_t db = mkdesc(0, 8192, 1024, 1) + (uint32_t)__shfl_sync(~0u, rb_, 0); \
    _Pragma("unroll") for (int s = 0; s < 9; s++) {                             \
      const int g_ = 1 + (ODD) * 9 + s, st_ = g_ % NSTG;                        \
      PRE;                                                                      \
      mbar_wait(full + st_ * 8, (pj) ^ ((g_ / NSTG) & 1));                      \
      WG_FENCE();                                                               \
      if (s == 0) FN<0>(acc, a[0], db + st_ * 1024); else FN<1>(acc, a[s * 4], db + st_ * 1024); \
      _Pragma("unroll") for (int k = 1; k < 4; k++) FN<1>(acc, a[s * 4 + k], db + st_ * 1024 + k * 128); \
      WG_COMMIT();                                                              \
      if (s > 0) { WG_WAIT(1); if (lane == 0) mbar_arrive(empty + ((g_ - 1) % NSTG) * 8); } \
    }                                                                           \
    WG_WAIT(0);                                                                 \
    if (lane == 0) mbar_arrive(empty + ((9 + (ODD) * 9) % NSTG) * 8);           \
  }

template <int NG, int G0>
__device__ __forceinline__ void qkv_stage(const float* acc, uint32_t stg, int rowl, int cq, int col_base) {
  const float vs0 = ((POLY_MASK >> ((rowl >> 3) & 7)) & 1) ? 0.5f : 1.0f, vs1 = ((POLY_MASK >> (((rowl >> 3) + 1) & 7)) & 1) ? 0.5f : 1.0f;
#pragma unroll
  for (int i = 0; i < NG; i++) {
    const int cc = (G0 + i) * 8 + cq * 2;
    const int slot = (cc * 3641) >> 16, d = cc - slot * 18;
    const int gc = col_base + cc;
    const float sc0 = gc < DM ? QSCALE : (gc < 2 * DM ? vs0 : 1.0f), sc1 = gc < DM ? QSCALE : (gc < 2 * DM ? vs1 : 1.0f);
    const uint32_t ad = stg + slot * 6144 + (d >> 3) * 128 + (d & 7) * 2 + (rowl >> 3) * 384 + (rowl & 7) * 16;
    asm volatile("st.shared.b32 [%0],%1;" ::"r"(ad), "r"(pack_bf16(acc[4 * i] * sc0, acc[4 * i + 1] * sc0)) : "memory");
    asm volatile("st.shared.b32 [%0],%1;" ::"r"(ad + 384), "r"(pack_bf16(acc[4 * i + 2] * sc1, acc[4 * i + 3] * sc1)) : "memory");
  }
}

__device__ __forceinline__ float silu_f(float v) { return rbf(__fdividef(v, 1.0f + fminf(__expf(-v), 1e37f))); }
__device__ __forceinline__ float silu_bf(__nv_bfloat16 c) { return silu_f(__bfloat162float(c)); }
__device__ __forceinline__ void fma8(float* acc, float sv, const uint4& w) {
  acc[0] += sv * bf_lo(w.x); acc[1] += sv * bf_hi(w.x); acc[2] += sv * bf_lo(w.y); acc[3] += sv * bf_hi(w.y);
  acc[4] += sv * bf_lo(w.z); acc[5] += sv * bf_hi(w.z); acc[6] += sv * bf_lo(w.w); acc[7] += sv * bf_hi(w.w);
}
__device__ __forceinline__ int tab_pos(int col, int shift) {
  return (((col >> 4) * 4 + ((col & 7) >> 1)) * 4 + ((col >> 3) & 1) * 2 + shift) * 2 + (col & 1);
}
__device__ __forceinline__ float knorm_row(uint32_t slot, int row) {
  const uint32_t ad = slot + (row >> 3) * 384 + (row & 7) * 16;
  const uint4 u = lds128(ad), v = lds128(ad + 128);
  uint32_t w;
  asm volatile("ld.shared.b32 %0,[%1];" : "=r"(w) : "r"(ad + 256) : "memory");
  float q = sq2(u.x) + sq2(u.y) + sq2(u.z) + sq2(u.w) + sq2(v.x) + sq2(v.y) + sq2(v.z) + sq2(v.w) + sq2(w);
  if ((POLY_MASK >> ((row >> 3) & 7)) & 1) q *= 4.0f;
  return q == q ? q : __int_as_float(0x7f800000);
}

__global__ void __launch_bounds__(384, 1) k1_kernel(const __grid_constant__ CUtensorMap mx, const __grid_constant__ CUtensorMap mw,
                                                    const __grid_constant__ CUtensorMap mm, const __nv_bfloat16* __restrict__ cvec,
                                                    const uint8_t* __restrict__ wqkv, const uint4* __restrict__ wo) {
  extern __shared__ __align__(1024) uint8_t smem_raw[];
  const uint32_t sb = s2u(smem_raw);
  const uint32_t R = sb, RING = sb + R_BYTES, BAR = RING + NSTG * STG_BYTES, TAB = BAR + 512;
  const uint32_t full = BAR, empty = BAR + 64, xfull = BAR + 128;
  const int tid = threadIdx.x, lane = tid & 31, warp = tid >> 5;
  const int mb = blockIdx.x >> 3, nb = blockIdx.x & 7;
  if (tid == 0) TS(1, 0);
  if (blockIdx.x >= 128) {
    pdl_launch();
    __nanosleep(3000);
#pragma unroll 9
    for (int i = (blockIdx.x - 128) * 384 + tid; i < DM * 72; i += 4 * 384) {
      const int k = i / 72, n8 = i - k * 72;
      g_wo[(n8 / 9) * 5184 + (k >> 3) * 72 + (n8 % 9) * 8 + (k & 7)] = __ldg(wo + i);
    }
    return;
  }
  if (tid == 288) { prefetch_map(&mx); prefetch_map(&mw); }
  if (tid == 256) {
    if (sb & 1023) __trap();
    for (int i = 0; i < NSTG; i++) { mbar_init(full + i * 8, 1); mbar_init(empty + i * 8, 8); }
    for (int i = 0; i < 9; i++) mbar_init(xfull + i * 8, 1);
    fence_bar_init();
    if (blockIdx.x < 72) {
      mbar_expect(xfull + 64, 18432);
      for (int i = 0; i < 3; i++) tma2d(RING + 4 * STG_BYTES + i * 6144, &mm, blockIdx.x * 16, i * 192, xfull + 64);
    }
  }
  __syncthreads();
  pdl_launch();
  if (lane == 0) {
    if (warp < 8) { mbar_expect(xfull + warp * 8, 16384); tma2d(R + warp * 16384, &mx, warp * 64, mb * 128, xfull + warp * 8); }
    if (warp == 1) { mbar_expect(full, 16384); tma2d(RING, &mx, 512, mb * 128, full); }
    if (warp == 9) asm volatile("cp.async.bulk.prefetch.L2.global [%0],%1;" ::"l"(wqkv + blockIdx.x * 15552), "r"(15552) : "memory");
  }
  __syncwarp();
  if (warp >= 8) {
    REG_DEC(24);
    const int pt = tid - 256;
    if (pt == 0) {
      for (int st = 1; st < 4; st++) {
        mbar_expect(full + st * 8, 16384);
        tma2d(RING + st * STG_BYTES, &mw, nb * 216, st * 64 - 64, full + st * 8);
        tma2d(RING + st * STG_BYTES + 8192, &mw, nb * 216 + 64, st * 64 - 64, full + st * 8);
      }
    }
    if (blockIdx.x < 72) {
      float* sf = (float*)(smem_raw + R_BYTES + 4 * STG_BYTES + 18432);
      if (pt < 72) {
        const uint4 cv = __ldg((const uint4*)cvec + pt);
        const uint32_t cw[4] = {cv.x, cv.y, cv.z, cv.w};
#pragma unroll
        for (int i = 0; i < 4; i++) { sf[pt * 8 + 2 * i] = silu_f(bf_lo(cw[i])); sf[pt * 8 + 2 * i + 1] = silu_f(bf_hi(cw[i])); }
      }
      bar_sync(3, 128);
      mbar_wait(xfull + 64, 0);
      float acc[8] = {0, 0, 0, 0, 0, 0, 0, 0};
#pragma unroll 1
      for (int i = 0; i < 9; i++) fma8(acc, sf[(pt >> 1) + 64 * i], lds128(RING + 4 * STG_BYTES + i * 2048 + pt * 16));
#pragma unroll
      for (int j = 0; j < 8; j++)
#pragma unroll
        for (int o = 2; o < 32; o *= 2) acc[j] += __shfl_xor_sync(~0u, acc[j], o);
      if (lane < 2) {
#pragma unroll
        for (int j = 0; j < 8; j++) sf[DM + (warp - 8) * 16 + lane * 8 + j] = acc[j];
      }
      bar_sync(3, 128);
      if (pt < 16) {
        const float v = rbf(sf[DM + pt] + sf[DM + 16 + pt] + sf[DM + 32 + pt] + sf[DM + 48 + pt]);
        const int n = blockIdx.x * 16 + pt, shift = n < DM;
        const uint32_t word = pack_bf16(shift ? v : 1.0f + v, 1.0f);
        asm volatile("st.relaxed.gpu.global.u32 [%0],%1;" ::"l"((uint32_t*)g_ll + tab_pos(shift ? n : n - DM, shift)), "r"(word) : "memory");
      }
      fence_async_smem();
      __syncwarp();
      if (pt == 0) TS(0, 1);
    }
    if (warp == 8) {
      if (lane == 0) {
        int st = 4; uint32_t ph = 0;
        for (int it = 3; it < 18; it++) {
          const int t = it / 9, s = it - t * 9;
          mbar_wait(empty + st * 8, ph ^ 1);
          mbar_expect(full + st * 8, 16384);
          tma2d(RING + st * STG_BYTES, &mw, nb * 216 + t * 128, s * 64, full + st * 8);
          tma2d(RING + st * STG_BYTES + 8192, &mw, nb * 216 + t * 128 + 64, s * 64, full + st * 8);
          if (++st == NSTG) { st = 0; ph ^= 1; }
        }
      }
    } else {
      const int ht = tid - 288;
      bar_sync(1, 352);
      for (int i = ht; i < 12 * 128; i += 96) {
        const int slot = i >> 7, row = i & 127, type = (nb * 12 + slot) >> 5;
        uint32_t v = 0;
        if (type == 1) v = ((POLY_MASK >> ((row >> 3) & 7)) & 1) ? 0x43403F00u : 0x40253F80u;
        if (type == 2) v = 0x3F80u;
        const uint32_t ad = R + slot * 6144 + (row >> 3) * 384 + 256 + (row & 7) * 16;
        asm volatile("st.shared.b32 [%0],%1;" ::"r"(ad + 4), "r"(v) : "memory");
        asm volatile("st.shared.v2.b32 [%0],{%1,%1};" ::"r"(ad + 8), "r"(0) : "memory");
      }
      fence_async_smem();
      bar_sync(2, 352);
      if (ht == 0) {
        for (int s = 0; s < 7; s++) bulk_s2g(g_qkv + (size_t)(nb * 12 + s) * 98304 + mb * 6144, R + s * 6144, 6144);
        bulk_commit();
      }
      for (int s = warp - 9; s < 7; s += 3) {
        const int gs = nb * 12 + s;
        if ((gs >> 5) != 1) continue;
        float mx2 = 0;
#pragma unroll 1
        for (int row = lane; row < 128; row += 32) mx2 = fmaxf(mx2, knorm_row(R + s * 6144, row));
#pragma unroll
        for (int o = 16; o; o >>= 1) mx2 = fmaxf(mx2, __shfl_xor_sync(~0u, mx2, o));
        if (lane == 0) g_kmax[(gs & 31) * 16 + mb] = mx2;
      }
      if (ht == 0) bulk_wait0();
    }
  } else {
    REG_INC(240);
    TSS(0);
    const int rowl = warp * 16;
    uint4 s0, s1;
    {
      RowStat rs, rt;
      rs.init(); rt.init();
      uint32_t f[4][4];
#pragma unroll 1
      for (int c = 0; c < 9; c++) {
        mbar_wait(c < 8 ? xfull + c * 8 : full, 0);
        load_a_chunk(f, R + c * 16384, rowl, lane);
        rs.add(f[0]); rt.add(f[1]); rs.add(f[2]); rt.add(f[3]);
      }
      rs.merge(rt);
      rs.finish(lane, s0, s1);
    }
    TSS(1);
    if (tid < 144) {
      uint4 u, v;
      int n = 0;
      do {
        asm volatile("ld.relaxed.gpu.global.v4.u32 {%0,%1,%2,%3},[%4];" : "=r"(u.x), "=r"(u.y), "=r"(u.z), "=r"(u.w) : "l"(g_ll + tid * 2) : "memory");
        asm volatile("ld.relaxed.gpu.global.v4.u32 {%0,%1,%2,%3},[%4];" : "=r"(v.x), "=r"(v.y), "=r"(v.z), "=r"(v.w) : "l"(g_ll + tid * 2 + 1) : "memory");
        if (++n > 4000000) __trap();
      } while (((u.x & u.y & u.z & u.w & v.x & v.y & v.z & v.w) >> 16) != 0x3F80u);
      sts128(TAB + tid * 16, make_uint4(__byte_perm(u.x, u.y, 0x5410), __byte_perm(u.z, u.w, 0x5410), __byte_perm(v.x, v.y, 0x5410), __byte_perm(v.z, v.w, 0x5410)));
    }
    bar_sync(4, 256);
    TSS(2);
    uint32_t a[36][4];
    float acc[64];
    MMA_TILE_(wl_rs_n128_t1, 0, 0, if (s < 8) { LN_CHUNK(s, load_a_chunk) } if (s == 1) { LN_CHUNK(8, load_a_chunk) if (lane == 0) mbar_arrive(empty); } if (s == 7) bar_arrive(1, 352));
    TSS(3);
    bar_sync(4, 256);
    int t2 = threadIdx.x;
    asm volatile("" : "+r"(t2));
    qkv_stage<16, 0>(acc, R, (t2 >> 5) * 16 + ((t2 & 31) >> 2), t2 & 3, nb * 216);
    fence_async_smem();
    bar_arrive(2, 352);
    TSS(4);
    MMA_TILE(wl_rs_n88_t1, 1, 0);
    asm volatile("" : "+r"(t2));
    qkv_stage<11, 16>(acc, R, (t2 >> 5) * 16 + ((t2 & 31) >> 2), t2 & 3, nb * 216);
    fence_async_smem();
    bar_sync(4, 256);
    TSS(5);
    if (tid == 0) {
      for (int s = 7; s < 12; s++) bulk_s2g(g_qkv + (size_t)(nb * 12 + s) * 98304 + mb * 6144, R + s * 6144, 6144);
      bulk_commit();
    }
    if (warp >= 3 && ((nb * 12 + 4 + warp) >> 5) == 1) {
      float mx2 = 0;
#pragma unroll
      for (int i = 0; i < 4; i++) mx2 = fmaxf(mx2, knorm_row(R + (4 + warp) * 6144, lane + 32 * i));
#pragma unroll
      for (int o = 16; o; o >>= 1) mx2 = fmaxf(mx2, __shfl_xor_sync(~0u, mx2, o));
      if (lane == 0) g_kmax[((nb * 12 + 4 + warp) & 31) * 16 + mb] = mx2;
    }
    if (tid == 0) bulk_wait0();
    TSS(6);
    TSDUMP(1);
  }
}

#define ATT_SMEM (2 * 98304 + 1024 + 256)

__device__ __forceinline__ uint32_t exp2_pair_fma(float t0, float t1) {
  uint32_t y;
  asm("prmt.b32 %0,%1,%2,0x6521;" : "=r"(y) : "r"(__float_as_uint(t0)), "r"(__float_as_uint(t1)));
  return hfma2(y, y | 0x3F803F80u, y | 0x007F007Fu);
}

__device__ __forceinline__ void softmax_fast(const float* s, uint32_t* p) {
#pragma unroll
  for (int i = 0; i < 8; i++) {
    if ((POLY_MASK >> i) & 1) {
      p[2 * i] = exp2_pair_fma(s[4 * i], s[4 * i + 1]);
      p[2 * i + 1] = exp2_pair_fma(s[4 * i + 2], s[4 * i + 3]);
    } else {
      p[2 * i] = pack_bf16(ex2f(s[4 * i]), ex2f(s[4 * i + 1]));
      p[2 * i + 1] = pack_bf16(ex2f(s[4 * i + 2]), ex2f(s[4 * i + 3]));
    }
  }
}
#define QK_MMA(S, kd)                                                           \
  wl_rs_n64_t0<0>(S, q, (kd));                                                  \
  wl_rs_n64_t0<1>(S, q + 4, (kd) + 16 - (8ull << 16));
#define PV_MMA(P, vd)                                                           \
  _Pragma("unroll") for (int t = 0; t < 4; t++) wl_rs_n24_t1<1>(o, P + 4 * t, (vd) + t * 48);

__device__ __forceinline__ void att_store(const float* o, int row0, int head, int lane) {
  const int cq = lane & 3;
  const float l0 = __shfl_sync(~0u, o[8], (lane & ~3) | 1), l1 = __shfl_sync(~0u, o[10], (lane & ~3) | 1);
  const float i0 = rcp_fast(l0), i1 = rcp_fast(l1);
  const int col = head * 18 + cq * 2;
  uint32_t* og = (uint32_t*)(g_o + (row0 >> 6) * 73728 + (col >> 3) * 1024 + (row0 & 63) * 16 + (col & 7) * 2);
  og[0] = pack_bf16(o[0] * i0, o[1] * i0);
  og[256] = pack_bf16(o[4] * i0, o[5] * i0);
  og[32] = pack_bf16(o[2] * i1, o[3] * i1);
  og[256 + 32] = pack_bf16(o[6] * i1, o[7] * i1);
  if (cq == 0) {
    og[512] = pack_bf16(o[8] * i0, o[9] * i0);
    og[512 + 32] = pack_bf16(o[10] * i1, o[11] * i1);
  }
}

__global__ void __launch_bounds__(512, 1) k2_kernel(const uint8_t* __restrict__ wg_, const uint8_t* __restrict__ wu,
                                                    const uint8_t* __restrict__ wd, const __nv_bfloat16* __restrict__ cvec,
                                                    const __nv_bfloat16* __restrict__ wmod) {
  extern __shared__ __align__(1024) uint8_t smem_raw[];
  const uint32_t sb = (s2u(smem_raw) + 1023) & ~1023u;
  const uint32_t KS = sb, VS = sb + 98304, BAR = sb + 2 * 98304;
  const int tid = threadIdx.x, lane = tid & 31, warp = tid >> 5, wg = tid >> 7;
  if (blockIdx.x < 4) {
    float* sf = (float*)smem_raw;
    const int part = blockIdx.x + 2;
    for (int i = tid; i < DM; i += 512) sf[i] = silu_bf(cvec[i]);
    if (part == 2 && tid < 80) g_cnt[tid] = 0;
    __syncthreads();
    if (tid < 432) {
      const int cg = tid % 72, rg = tid / 72;
      const __nv_bfloat16* w = wmod + (size_t)rg * 96 * 3456 + part * DM + cg * 8;
      float acc[8] = {0, 0, 0, 0, 0, 0, 0, 0};
#pragma unroll 1
      for (int r = 0; r < 96; r += 12) {
        uint4 v[12];
#pragma unroll
        for (int i = 0; i < 12; i++) v[i] = __ldg((const uint4*)(w + (size_t)(r + i) * 3456));
#pragma unroll
        for (int i = 0; i < 12; i++) fma8(acc, sf[rg * 96 + r + i], v[i]);
      }
#pragma unroll
      for (int j = 0; j < 8; j++) sf[DM + rg * DM + cg * 8 + j] = acc[j];
    }
    __syncthreads();
    for (int col = tid; col < DM; col += 512) {
      float v = 0;
#pragma unroll
      for (int j = 1; j < 7; j++) v += sf[j * DM + col];
      v = rbf(v);
      if (part == 2) g_ga[col] = __float2bfloat16_rn(v);
      else if (part == 5) g_gb[col] = __float2bfloat16_rn(v);
      else ((__nv_bfloat16*)g_tab2)[tab_pos(col, part == 3)] = __float2bfloat16_rn(0.5f * (part == 3 ? v : rbf(1.0f + v)));
    }
    pdl_wait();
    if (part == 2 && tid < 288) g_ll[tid] = make_uint4(0, 0, 0, 0);
    if (tid == 0) TS(0, 0);
    return;
  }
  const int bid = blockIdx.x - 4, head = bid >> 2, qb = bid & 3;
  if (tid == 0) {
    TS(2, 0);
    for (int i = 0; i < 16; i++) mbar_init(BAR + i * 8, 1);
    fence_bar_init();
  }
  __syncthreads();
  const int g = lane >> 2, cq = lane & 3;
  const int row0 = qb * 512 + wg * 128 + (warp & 3) * 16 + g;
  const uint8_t* qg = g_qkv + (size_t)head * 98304 + (row0 >> 3) * 384 + (row0 & 7) * 16 + cq * 4;
  pdl_wait();
  pdl_launch();
  if (tid == 0) TS(2, 1);
  const uint8_t* kg = g_qkv + (size_t)(32 + head) * 98304;
#define KV_LOAD(c) { mbar_expect(BAR + (c) * 8, 12288); bulk_g2s(KS + (c) * 6144, kg + (c) * 6144, 6144, BAR + (c) * 8); \
                     bulk_g2s(VS + (c) * 6144, kg + 32 * 98304 + (c) * 6144, 6144, BAR + (c) * 8); }
  if (lane == 0 && warp < 5) KV_LOAD(warp);
  __syncwarp();
  uint32_t q[8], q2[6];
  float kmax2 = __ldcg(g_kmax + head * 16 + (lane & 15));
#pragma unroll
  for (int i = 0; i < 6; i++) {
    q[i] = __ldcg((const uint32_t*)(qg + (i & 1) * 384 + (i >> 1) * 128));
    q2[i] = __ldcg((const uint32_t*)(qg + 3072 + (i & 1) * 384 + (i >> 1) * 128));
  }
  q[6] = __ldcg((const uint32_t*)(qg + 256 + 12 - cq * 4)); q[7] = __ldcg((const uint32_t*)(qg + 256 + 8 - cq * 4));
  const uint64_t dk = mkdesc(KS, 128, 384, 0), dv = mkdesc(VS, 384, 128, 0);
#pragma unroll
  for (int o = 8; o; o >>= 1) kmax2 = fmaxf(kmax2, __shfl_xor_sync(~0u, kmax2, o));
  float bd[4] = {sq2(q[0]) + sq2(q[2]) + sq2(q[4]), sq2(q[1]) + sq2(q[3]) + sq2(q[5]),
                 sq2(q2[0]) + sq2(q2[2]) + sq2(q2[4]), sq2(q2[1]) + sq2(q2[3]) + sq2(q2[5])};
  int ok = 1;
  if (tid == 0 && bd[0] + bd[3] + kmax2 != 1.2345f) TS(2, 5);
#pragma unroll
  for (int i = 0; i < 4; i++) {
    bd[i] += __shfl_xor_sync(~0u, bd[i], 1); bd[i] += __shfl_xor_sync(~0u, bd[i], 2);
    bd[i] = sqrt_fast(bd[i] * kmax2) * 1.01f + 1.0f;
    ok = ok && (bd[i] <= 62.0f);
  }
  {
    uint32_t all;
    asm volatile("{.reg .pred p,q; setp.ne.b32 p,%1,0; barrier.red.and.pred q,1,512,p; selp.u32 %0,1,0,q;}"
                 : "=r"(all) : "r"(ok) : "memory");
    ok = __all_sync(~0u, all);
  }
  float o[12];
#pragma unroll
  for (int i = 0; i < 12; i++) { o[i] = 0.f; asm volatile("" : "+f"(o[i])); }
  float s[32];
  uint32_t p[16];
  if (tid == 0) TS(2, 2);
  if (ok) {
    if (cq == 1) {
      q[4] = pack_bf16(-bd[0], 1.0f); q[5] = pack_bf16(-bd[1], 1.0f);
      q2[4] = pack_bf16(-bd[2], 1.0f); q2[5] = pack_bf16(-bd[3], 1.0f);
    }
    mbar_wait(BAR, 0);
    WG_FENCE();
    QK_MMA(s, dk);
    WG_COMMIT();
#pragma unroll 1
    for (int tile = 0; tile < 2; tile++) {
#pragma unroll 1
      for (int jj = 0; jj < 8; jj++) {
        const uint64_t kd = dk + (uint32_t)(jj * 768), vd = dv + (uint32_t)(jj * 768), kn = dk + (uint32_t)(((jj + 1) & 7) * 768);
        if (tile == 0) {
          if (lane == 0 && warp < 2 && 2 * jj + 5 + warp < 16) KV_LOAD(2 * jj + 5 + warp);
          if (lane == 0 && warp >= 4 && warp < 7)
            asm volatile("cp.async.bulk.prefetch.L2.global [%0],%1;" ::"l"((warp == 4 ? wg_ : warp == 5 ? wu : wd) + (bid * 8 + jj) * 5184), "r"(5184) : "memory");
          __syncwarp();
          mbar_wait(BAR + jj * 16 + 8, 0); mbar_wait(BAR + ((jj * 16 + 16) & 127), 0); if (tid == 0) TS(2, 8 + jj); }
#pragma unroll
        for (int u = 0; u < 4; u++) {
          WG_WAIT(0);
          fence_regs<32>(s);
          softmax_fast(s, p);
          if (u == 3 && jj == 7) {
#pragma unroll
            for (int i = 0; i < 6; i++) q[i] = q2[i];
          }
          WG_FENCE();
          PV_MMA(p, vd + u * 192);
          QK_MMA(s, u < 3 ? kd + u * 192 + 192 : kn);
          WG_COMMIT();
        }
      }
      WG_WAIT(0);
      fence_regs<12>(o);
      att_store(o, row0 + tile * 64, head, lane);
#pragma unroll
      for (int i = 0; i < 12; i++) o[i] = 0.f;
      fence_regs<12>(o);
      if (tid == 0 && tile == 0) TS(2, 3);
    }
  } else {
    if (lane == 0 && warp >= 5) KV_LOAD(warp);
    __syncwarp();
#pragma unroll 1
    for (int tile = 0; tile < 2; tile++) {
      float m0 = -INFINITY, m1 = -INFINITY;
#pragma unroll 1
      for (int j = 0; j < 32; j++) {
        mbar_wait(BAR + (j >> 1) * 8, 0);
        WG_FENCE();
        QK_MMA(s, dk + (uint32_t)(j * 192));
        WG_COMMIT();
        WG_WAIT(0);
        fence_regs<32>(s);
#pragma unroll
        for (int i = 0; i < 32; i++) if ((POLY_MASK >> (i >> 2)) & 1) s[i] *= 2.0f;
        float x0 = m0, x1 = m1;
#pragma unroll
        for (int i = 0; i < 8; i++) {
          x0 = fmaxf(x0, fmaxf(s[4 * i], s[4 * i + 1]));
          x1 = fmaxf(x1, fmaxf(s[4 * i + 2], s[4 * i + 3]));
        }
        x0 = fmaxf(x0, __shfl_xor_sync(~0u, x0, 1)); x0 = fmaxf(x0, __shfl_xor_sync(~0u, x0, 2));
        x1 = fmaxf(x1, __shfl_xor_sync(~0u, x1, 1)); x1 = fmaxf(x1, __shfl_xor_sync(~0u, x1, 2));
        const float c0 = ex2f(m0 - x0), c1 = ex2f(m1 - x1);
        m0 = x0; m1 = x1;
#pragma unroll
        for (int i = 0; i < 3; i++) { o[4 * i] *= c0; o[4 * i + 1] *= c0; o[4 * i + 2] *= c1; o[4 * i + 3] *= c1; }
#pragma unroll
        for (int i = 0; i < 8; i++) {
          p[2 * i] = pack_bf16(ex2f(s[4 * i] - x0), ex2f(s[4 * i + 1] - x0));
          p[2 * i + 1] = pack_bf16(ex2f(s[4 * i + 2] - x1), ex2f(s[4 * i + 3] - x1));
        }
        WG_FENCE();
        PV_MMA(p, dv + (uint32_t)(j * 192));
        WG_COMMIT();
        WG_WAIT(0);
        fence_regs<12>(o);
      }
      att_store(o, row0 + tile * 64, head, lane);
#pragma unroll
      for (int i = 0; i < 12; i++) o[i] = 0.f;
#pragma unroll
      for (int i = 0; i < 6; i++) q[i] = q2[i];
    }
  }
  if (tid == 0) TS(2, 4);
}

#define K3_SMEM (9 * 16384 + 9 * 9216 + 256)
__device__ __forceinline__ uint32_t res_pair(uint32_t x, uint32_t g, float s0, float s1) { return hadd2(x, hmul2(g, pack_bf16(s0, s1))); }
__global__ void __launch_bounds__(320, 1) k3_kernel(const __nv_bfloat16* __restrict__ x) {
  extern __shared__ __align__(1024) uint8_t smem_raw[];
  const uint32_t sb = s2u(smem_raw);
  const uint32_t A = sb, B = sb + 9 * 16384, BAR = B + 9 * 9216;
  const int tid = threadIdx.x, lane = tid & 31, warp = tid >> 5;
  const int mb = blockIdx.x >> 3, nb = blockIdx.x & 7;
  if (tid == 0) {
    TS(3, 0);
    if (sb & 1023) __trap();
    for (int i = 0; i < 9; i++) { mbar_init(BAR + i * 8, 1); mbar_expect(BAR + i * 8, 9216 + 16384); }
    fence_bar_init();
  }
  __syncthreads();
  if (warp >= 8) {
    if (tid == 256) {
      for (int s = 0; s < 9; s++) {
        bulk_g2s(B + s * 9216, g_wo + nb * 5184 + s * 576, 9216, BAR + s * 8);
      }
      TS(0, 2);
    }
    if (tid == 288) {
      pdl_wait();
      TS(0, 3);
      for (int c = 0; c < 18; c++) bulk_g2s(A + c * 8192, g_o + (mb * 2 + (c & 1)) * 73728 + (c >> 1) * 8192, 8192, BAR + (c >> 1) * 8);
    }
  } else {
    const int g = lane >> 2, cq = lane & 3, wg = warp >> 2;
    const int row = mb * 128 + warp * 16 + g, col = nb * 72 + cq * 2;
    uint32_t xv[20], ga[9];
#pragma unroll
    for (int i = 0; i < 9; i++) {
      xv[2 * i] = __ldg((const uint32_t*)(x + (size_t)row * DM + col + 8 * i));
      xv[2 * i + 1] = __ldg((const uint32_t*)(x + (size_t)(row + 8) * DM + col + 8 * i));
    }
    pdl_wait();
    pdl_launch();
    if (tid == 0) TS(3, 1);
#pragma unroll
    for (int i = 0; i < 9; i++) ga[i] = __ldcg((const uint32_t*)(g_ga + col + 8 * i));
    float acc[36];
    const uint64_t da = mkdesc(A + wg * 8192, 1024, 128, 0), db = mkdesc(B, 1152, 128, 0);
#pragma unroll 1
    for (int s = 0; s < 9; s++) {
      mbar_wait(BAR + s * 8, 0);
      if (tid == 0) TS(0, 4 + s);
      WG_FENCE();
#pragma unroll
      for (int k = 0; k < 4; k++) wg_ss_n72_t1(acc, da + s * 1024 + k * 128, db + s * 576 + k * 144, s | k);
      WG_COMMIT();
    }
    WG_WAIT(0);
    fence_regs<36>(acc);
    if (tid == 0) TS(3, 2);
    bar_sync(1, 256);
    const uint32_t stg = A + wg * 9216 + ((warp & 3) * 16 + g) * 16 + cq * 4;
#pragma unroll
    for (int i = 0; i < 9; i++) {
      xv[2 * i] = res_pair(xv[2 * i], ga[i], acc[4 * i], acc[4 * i + 1]);
      xv[2 * i + 1] = res_pair(xv[2 * i + 1], ga[i], acc[4 * i + 2], acc[4 * i + 3]);
      asm volatile("st.shared.b32 [%0],%1;" ::"r"(stg + i * 1024), "r"(xv[2 * i]) : "memory");
      asm volatile("st.shared.b32 [%0],%1;" ::"r"(stg + i * 1024 + 128), "r"(xv[2 * i + 1]) : "memory");
    }
    fence_async_smem();
    bar_sync(2 + wg, 128);
    if ((tid & 127) == 0) {
      bulk_s2g(g_x1 + (mb * 2 + wg) * 73728 + nb * 9216, A + wg * 9216, 9216);
      bulk_commit();
    }
    xv[18] = xv[19] = 0;
    RowStat rs;
    rs.init();
#pragma unroll
    for (int i = 0; i < 5; i++) rs.add(&xv[4 * i]);
    if (cq == (g >> 1)) {
      g_stat2[row * 8 + nb] = make_float2(rs.s[0], (g & 1) ? rs.q0[1] : rs.q0[0]);
      g_stat2[(row + 8) * 8 + nb] = make_float2(rs.s[2], (g & 1) ? rs.q1[3] : rs.q1[2]);
    }
    if ((tid & 127) == 0) bulk_wait0();
    if (tid == 0) TS(3, 3);
  }
}

__device__ __forceinline__ uint4 ln2_consts(int row, int cq) {
  const float4 p = __ldcg((const float4*)(g_stat2 + row * 8 + cq * 2));
  float s = p.x + p.z, q = p.y + p.w;
  s += __shfl_xor_sync(~0u, s, 1); q += __shfl_xor_sync(~0u, q, 1);
  s += __shfl_xor_sync(~0u, s, 2); q += __shfl_xor_sync(~0u, q, 2);
  const float mean = s * (1.0f / DM);
  return ln_consts(mean, fmaxf(q * (1.0f / DM) - mean * mean, 0.f));
}
__device__ __forceinline__ uint32_t glu_pair(float g0, float g1, float u0, float u1) {
  return pack_bf16(fmaf(tanhf_fast(g0), u0, u0), fmaf(tanhf_fast(g1), u1, u1));
}
template <int NG>
__device__ __forceinline__ void stage_part(const float* acc, uint32_t stg, int lane) {
  const int r = (lane & 7) + ((lane >> 3) & 1) * 8;
#pragma unroll
  for (int i = 0; i < NG; i += 2) {
    const int ch = i + (lane >> 4);
    stsm4(stg + r * (NG * 16) + ((ch ^ (r & 7)) << 4), pack_bf16(acc[4 * i], acc[4 * i + 1]), pack_bf16(acc[4 * i + 2], acc[4 * i + 3]),
          pack_bf16(acc[4 * i + 4], acc[4 * i + 5]), pack_bf16(acc[4 * i + 6], acc[4 * i + 7]));
  }
}
__global__ void __launch_bounds__(384, 1) k4_kernel(const __grid_constant__ CUtensorMap mg,
                                                    const __grid_constant__ CUtensorMap mu, const __grid_constant__ CUtensorMap md,
                                                    __nv_bfloat16* __restrict__ out) {
  extern __shared__ __align__(1024) uint8_t smem_raw[];
  const uint32_t sb = s2u(smem_raw);
  const uint32_t R = sb, RING = sb + R_BYTES, BAR = RING + NSTG * STG_BYTES, TAB = BAR + 512;
  const uint32_t full = BAR, empty = BAR + 64, xfull = BAR + 128, gfull = BAR + 272, sfull = BAR + 320;
  const int tid = threadIdx.x, lane = tid & 31, warp = tid >> 5;
  const int mb = blockIdx.x >> 3, fb = blockIdx.x & 7;
  if (tid == 0) {
    TS(4, 0);
    if (sb & 1023) __trap();
    for (int i = 0; i < 10; i++) mbar_init(sfull + i * 8, 4);
    for (int i = 0; i < NSTG; i++) { mbar_init(full + i * 8, 1); mbar_init(empty + i * 8, 8); }
    for (int i = 0; i < 9; i++) mbar_init(xfull + i * 8, 1);
    for (int i = 0; i < 5; i++) mbar_init(gfull + i * 8, 1);
    mbar_arrive(full);
    for (int i = 0; i < 9; i++) mbar_expect(xfull + i * 8, 16384);
    fence_bar_init();
  }
  __syncthreads();
  if (warp >= 8) {
    REG_DEC(24);
    if (lane == 0) {
      if (warp == 8) {
        int st = 1; uint32_t ph = 0;
        for (int it = 0; it < 126; it++) {
          const int t = it / 9, s = it - t * 9;
          const uint32_t dst = RING + st * STG_BYTES, fb_ = full + st * 8;
          mbar_wait(empty + st * 8, ph ^ 1);
          if (t < 9) {
            mbar_expect(fb_, 16384);
            tma2d(dst, &mg, fb * 576 + t * 64, s * 64, fb_);
            tma2d(dst + 8192, &mu, fb * 576 + t * 64, s * 64, fb_);
          } else {
            mbar_expect(fb_, t < 13 ? 16384 : 8192);
            tma2d(dst, &md, (t - 9) * 128, fb * 576 + s * 64, fb_);
            if (t < 13) tma2d(dst + 8192, &md, (t - 9) * 128 + 64, fb * 576 + s * 64, fb_);
          }
          if (++st == NSTG) { st = 0; ph ^= 1; }
        }
      } else if (warp < 11) {
        const int wg = warp - 9;
#pragma unroll 1
        for (int p = 0; p < 5; p++) {
          uint8_t* dst = g_part + (size_t)((fb * 16 + mb) * 5 + p) * 32768;
          mbar_wait(sfull + (p * 2 + wg) * 8, 0);
          if (p < 4) {
            bulk_s2g(dst + wg * 16384, R + p * 32768 + wg * 8192, 8192);
            bulk_s2g(dst + wg * 16384 + 8192, R + p * 32768 + 16384 + wg * 8192, 8192);
          } else {
            bulk_s2g(dst + wg * 8192, RING + wg * STG_BYTES + 8192, 8192);
          }
          bulk_commit();
          if (wg == 0 && p >= 3) TS(3, 11 + p);
          bulk_wait0();
          if (wg == 0) TS(3, 4 + p);
          asm volatile("fence.proxy.async.global;" ::: "memory");
          asm volatile("red.release.gpu.global.add.u32 [%0],1;" ::"l"(g_cnt + mb * 5 + p) : "memory");
        }
      } else {
        pdl_wait();
        for (int c = 0; c < 9; c++) {
          const int k = c < 2 ? c : (c == 2 ? 8 : c - 1);
          bulk_g2s(R + k * 16384, g_x1 + mb * 2 * 73728 + k * 8192, 8192, xfull + c * 8);
          bulk_g2s(R + k * 16384 + 8192, g_x1 + (mb * 2 + 1) * 73728 + k * 8192, 8192, xfull + c * 8);
        }
        mbar_wait(sfull, 0);
#pragma unroll 1
        for (int p = 0; p < 5; p++) {
          unsigned int v; int n = 0;
          do {
            asm volatile("ld.acquire.gpu.global.u32 %0,[%1];" : "=r"(v) : "l"(g_cnt + mb * 5 + p) : "memory");
          } while (v < 16 && ++n < 20000000);
          if (v < 16) __trap();
          asm volatile("fence.proxy.async.global;" ::: "memory");
          TS(3, 9 + p);
          const uint32_t sz = p < 4 ? 4096 : 2048;
          mbar_expect(gfull + p * 8, sz * 8);
#pragma unroll 1
          for (int f = 0; f < 8; f++)
            bulk_g2s(p < 4 ? R + p * 32768 + f * 4096 : RING + (2 + (f >> 2)) * STG_BYTES + 8192 + (f & 3) * 2048,
                     g_part + (size_t)((f * 16 + mb) * 5 + p) * 32768 + fb * sz, sz, gfull + p * 8);
        }
      }
    }
  } else {
    REG_INC(240);
    uint32_t a[36][4];
    const int wg = warp >> 2, wl = warp & 3;
    if (tid < 144) sts128(TAB + tid * 16, g_tab2[tid]);
    bar_sync(1, 256);
    pdl_wait();
    TSS(0);
    float acc[64];
    const uint32_t hsp = R + wg * 8192 + (wl * 16 + (lane & 15)) * 16 + (lane >> 4) * 1024;
#define GLU_SPILL(t)                                                            \
  _Pragma("unroll") for (int j = 0; j < 4; j++) {                               \
    uint32_t h[4];                                                              \
    _Pragma("unroll") for (int e = 0; e < 4; e++)                               \
      h[e] = glu_pair(acc[8 * j + 2 * e], acc[8 * j + 2 * e + 1], acc[32 + 8 * j + 2 * e], acc[32 + 8 * j + 2 * e + 1]); \
    asm volatile("st.shared.v4.b32 [%0],{%1,%2,%3,%4};" ::"r"(hsp + (t) * 16384 + j * 2048), "r"(h[0]), "r"(h[1]), "r"(h[2]), "r"(h[3]) : "memory"); \
  }
    {
      const uint4 s0 = ln2_consts(mb * 128 + warp * 16 + (lane >> 2), lane & 3), s1 = ln2_consts(mb * 128 + warp * 16 + (lane >> 2) + 8, lane & 3);
      TSS(1);
      MMA_TILE_(wl_rs_n128_t1, 0, 0,
                if (s < 8) { mbar_wait(xfull + (s + (s > 1)) * 8, 0); LN_CHUNK(s, load_a_core) }
                if (s == 1) { mbar_wait(xfull + 16, 0); LN_CHUNK(8, load_a_core) if (lane == 0) mbar_arrive(empty); });
    }
    GLU_SPILL(0);
#pragma unroll 1
    for (int t = 0; t < 3; t++) {
      MMA_TILE(wl_rs_n128_t1, 1, t & 1);
      GLU_SPILL(2 * t + 1);
      MMA_TILE(wl_rs_n128_t1, 0, (t & 1) ^ 1);
      GLU_SPILL(2 * t + 2);
    }
    MMA_TILE(wl_rs_n128_t1, 1, 1);
    GLU_SPILL(7);
    MMA_TILE(wl_rs_n128_t1, 0, 0);
#pragma unroll
    for (int j = 0; j < 4; j++)
#pragma unroll
      for (int e = 0; e < 4; e++)
        a[32 + j][e] = glu_pair(acc[8 * j + 2 * e], acc[8 * j + 2 * e + 1], acc[32 + 8 * j + 2 * e], acc[32 + 8 * j + 2 * e + 1]);
#pragma unroll
    for (int k = 0; k < 32; k++)
      asm volatile("ld.shared.v4.b32 {%0,%1,%2,%3},[%4];" : "=r"(a[k][0]), "=r"(a[k][1]), "=r"(a[k][2]), "=r"(a[k][3]) : "r"(hsp + (k >> 2) * 16384 + (k & 3) * 2048) : "memory");
    TSS(2);
    const uint32_t stg = R + (wl >> 1) * 16384 + wg * 8192 + (wl & 1) * 4096;
#define PART_OUT(p)                                                             \
  stage_part<16>(acc, stg + (p) * 32768, lane);                                 \
  fence_async_smem();                                                           \
  __syncwarp();                                                                 \
  if (lane == 0) mbar_arrive(sfull + ((p) * 2 + wg) * 8);
    bar_sync(2 + wg, 128);
#pragma unroll 1
    for (int p = 0; p < 2; p++) {
      MMA_TILE(wl_rs_n128_t1, 1, p);
      PART_OUT(2 * p);
      MMA_TILE(wl_rs_n128_t1, 0, p ^ 1);
      PART_OUT(2 * p + 1);
    }
    MMA_TILE(wl_rs_n64_t1, 1, 0);
    stage_part<8>(acc, RING + wg * STG_BYTES + 8192 + wl * 2048, lane);
    fence_async_smem();
    __syncwarp();
    if (lane == 0) mbar_arrive(sfull + (8 + wg) * 8);
    TSS(3);
    const int rl = tid >> 4, ch = tid & 15;
    const size_t off = (size_t)(mb * 128 + fb * 16 + rl) * DM + ch * 8;
    uint4 xv[5], gv[5];
#pragma unroll
    for (int p = 0; p < 5; p++)
      if (p < 4 || ch < 8) { xv[p] = __ldcg((const uint4*)(g_x1 + (mb * 2 + (fb >> 2)) * 73728 + (p * 16 + ch) * 1024 + ((fb & 3) * 16 + rl) * 16)); gv[p] = __ldcg((const uint4*)(g_gb + p * 128 + ch * 8)); }
#pragma unroll
    for (int p = 0; p < 5; p++) {
      if (p == 4 && ch >= 8) break;
      mbar_wait(gfull + p * 8, 0);
      float r8[8] = {0, 0, 0, 0, 0, 0, 0, 0};
#pragma unroll
      for (int f = 0; f < 8; f++) {
        const uint4 v = lds128((p < 4 ? R + p * 32768 + f * 4096 + rl * 256 : RING + (2 + (f >> 2)) * STG_BYTES + 8192 + (f & 3) * 2048 + rl * 128) +
                               ((ch ^ (rl & 7)) << 4));
        r8[0] += bf_lo(v.x); r8[1] += bf_hi(v.x); r8[2] += bf_lo(v.y); r8[3] += bf_hi(v.y);
        r8[4] += bf_lo(v.z); r8[5] += bf_hi(v.z); r8[6] += bf_lo(v.w); r8[7] += bf_hi(v.w);
      }
      uint4 r;
      r.x = res_pair(xv[p].x, gv[p].x, r8[0], r8[1]);
      r.y = res_pair(xv[p].y, gv[p].y, r8[2], r8[3]);
      r.z = res_pair(xv[p].z, gv[p].z, r8[4], r8[5]);
      r.w = res_pair(xv[p].w, gv[p].w, r8[6], r8[7]);
      *(uint4*)(out + off + p * 128) = r;
      if (p >= 2) TSS(2 + p);
    }
    TSDUMP(4);
  }
}

typedef CUresult (*EncodeFn)(CUtensorMap*, CUtensorMapDataType, cuuint32_t, void*, const cuuint64_t*, const cuuint64_t*,
                             const cuuint32_t*, const cuuint32_t*, CUtensorMapInterleave, CUtensorMapSwizzle,
                             CUtensorMapL2promotion, CUtensorMapFloatOOBfill);
static void make_map(EncodeFn fn, CUtensorMap* m, const void* p, int rows, int cols, int box_rows, int box_cols = 64) {
  cuuint64_t dims[2] = {(cuuint64_t)cols, (cuuint64_t)rows};
  cuuint64_t strides[1] = {(cuuint64_t)cols * 2};
  cuuint32_t box[2] = {(cuuint32_t)box_cols, (cuuint32_t)box_rows};
  cuuint32_t es[2] = {1, 1};
  fn(m, CU_TENSOR_MAP_DATA_TYPE_BFLOAT16, 2, (void*)p, dims, strides, box, es, CU_TENSOR_MAP_INTERLEAVE_NONE,
     box_cols == 64 ? CU_TENSOR_MAP_SWIZZLE_128B : CU_TENSOR_MAP_SWIZZLE_NONE,
     box_cols == 64 ? CU_TENSOR_MAP_L2_PROMOTION_L2_256B : CU_TENSOR_MAP_L2_PROMOTION_NONE, CU_TENSOR_MAP_FLOAT_OOB_FILL_NONE);
}
template <typename... KA, typename... A>
static void launch(void (*k)(KA...), int grid, int block, int smem, bool pdl, A... args) {
  cudaLaunchConfig_t cfg = {};
  cfg.gridDim = dim3(grid); cfg.blockDim = dim3(block); cfg.dynamicSmemBytes = smem; cfg.stream = cudaStreamPerThread;
  cudaLaunchAttribute at;
  at.id = cudaLaunchAttributeProgrammaticStreamSerialization;
  at.val.programmaticStreamSerializationAllowed = 1;
  cfg.attrs = &at; cfg.numAttrs = pdl ? 1 : 0;
  cudaLaunchKernelEx(&cfg, k, KA(args)...);
}

extern "C" void kernel_launch(void* const* d_in, const int* in_sizes, int n_in, void* d_out, int out_size) {
  const __nv_bfloat16* x = (const __nv_bfloat16*)d_in[0];
  void* fnp = nullptr;
  cudaDriverEntryPointQueryResult qr;
  cudaGetDriverEntryPoint("cuTensorMapEncodeTiled", &fnp, cudaEnableDefault, &qr);
  EncodeFn fn = (EncodeFn)fnp;
  CUtensorMap mm, mx, mqkv, mg, mu, md;
  make_map(fn, &mm, d_in[8], DM, 6 * DM, 192, 16);
  make_map(fn, &mx, x, SEQ, DM, 128);
  make_map(fn, &mqkv, d_in[1], DM, 3 * DM, 64);
  make_map(fn, &mg, d_in[4], DM, FF, 64);
  make_map(fn, &mu, d_in[5], DM, FF, 64);
  make_map(fn, &md, d_in[6], FF, DM, 64);
  cudaFuncSetAttribute(k1_kernel, cudaFuncAttributeMaxDynamicSharedMemorySize, GEMM_SMEM);
  cudaFuncSetAttribute(k2_kernel, cudaFuncAttributeMaxDynamicSharedMemorySize, ATT_SMEM);
  cudaFuncSetAttribute(k3_kernel, cudaFuncAttributeMaxDynamicSharedMemorySize, K3_SMEM);
  cudaFuncSetAttribute(k4_kernel, cudaFuncAttributeMaxDynamicSharedMemorySize, GEMM_SMEM);
  launch(k1_kernel, 132, 384, GEMM_SMEM, false, mx, mqkv, mm, (const __nv_bfloat16*)d_in[7], (const uint8_t*)d_in[1], (const uint4*)d_in[2]);
  launch(k2_kernel, 132, 512, ATT_SMEM, true, (const uint8_t*)d_in[4], (const uint8_t*)d_in[5], (const uint8_t*)d_in[6],
         (const __nv_bfloat16*)d_in[7], (const __nv_bfloat16*)d_in[8]);
  launch(k3_kernel, 128, 320, K3_SMEM, true, x);
  launch(k4_kernel, 128, 384, GEMM_SMEM, true, mg, mu, md, (__nv_bfloat16*)d_out);
}
```

```cpp
#include <cuda_runtime.h>
#include <cuda_bf16.h>
#include <cuda.h>
#include <stdint.h>

#define SEQ 2048
#define DM 576
#define NH 32
#define FF 4608

__device__ uint4 g_ll[36 * 4 * 2];
__device__ uint4 g_tab2[36 * 4];
__device__ __align__(16) __nv_bfloat16 g_ga[DM];
__device__ __align__(16) __nv_bfloat16 g_gb[DM];
__device__ float2 g_stat2[SEQ * 8];
__device__ __align__(1024) uint8_t g_qkv[96 * 98304];
__device__ float g_kmax[NH * 16];
__device__ __align__(1024) uint8_t g_o[SEQ * DM * 2];
__device__ __align__(1024) uint8_t g_x1[SEQ * DM * 2];
__device__ __align__(1024) uint4 g_wo[DM * DM / 8];
__device__ __align__(1024) uint8_t g_part[8 * 16 * 5 * 2 * 16384];
__device__ unsigned int g_cnt[16 * 5];

#define TS(k, i)
#define TSS(i)
#define TSDUMP(k)
__device__ __forceinline__ uint32_t s2u(const void* p) { return (uint32_t)__cvta_generic_to_shared(p); }
__device__ __forceinline__ void mbar_init(uint32_t b, int c) { asm volatile("mbarrier.init.shared::cta.b64 [%0],%1;" ::"r"(b), "r"(c)); }
__device__ __forceinline__ void mbar_expect(uint32_t b, uint32_t n) { asm volatile("mbarrier.arrive.expect_tx.shared::cta.b64 _,[%0],%1;" ::"r"(b), "r"(n) : "memory"); }
__device__ __forceinline__ void mbar_arrive(uint32_t b) { asm volatile("mbarrier.arrive.shared::cta.b64 _,[%0];" ::"r"(b) : "memory"); }
__device__ __forceinline__ void mbar_wait(uint32_t b, uint32_t ph) {
  asm volatile(
      "{.reg .pred p; .reg .u32 n;\n"
      "mbarrier.try_wait.parity.shared::cta.b64 p,[%0],%1;\n"
      "@p bra D;\n"
      "mov.u32 n,0;\n"
      "W: mbarrier.try_wait.parity.shared::cta.b64 p,[%0],%1;\n"
      "@p bra D;\n"
      "add.u32 n,n,1; setp.lt.u32 p,n,4000000; @p bra W;\n"
      "trap;\n"
      "D: }" ::"r"(b), "r"(ph) : "memory");
}
__device__ __forceinline__ void tma2d(uint32_t dst, const CUtensorMap* m, int c0, int c1, uint32_t bar) {
  asm volatile("cp.async.bulk.tensor.2d.shared::cluster.global.mbarrier::complete_tx::bytes [%0],[%1,{%3,%4}],[%2];"
               ::"r"(dst), "l"(m), "r"(bar), "r"(c0), "r"(c1) : "memory");
}
__device__ __forceinline__ void bulk_g2s(uint32_t dst, const void* src, uint32_t bytes, uint32_t bar) {
  asm volatile("cp.async.bulk.shared::cluster.global.mbarrier::complete_tx::bytes [%0],[%1],%2,[%3];"
               ::"r"(dst), "l"(src), "r"(bytes), "r"(bar) : "memory");
}
__device__ __forceinline__ void bulk_s2g(void* dst, uint32_t src, uint32_t bytes) {
  asm volatile("cp.async.bulk.global.shared::cta.bulk_group [%0],[%1],%2;" ::"l"(dst), "r"(src), "r"(bytes) : "memory");
}
__device__ __forceinline__ void bulk_commit() { asm volatile("cp.async.bulk.commit_group;" ::: "memory"); }
__device__ __forceinline__ void bulk_wait0() { asm volatile("cp.async.bulk.wait_group 0;" ::: "memory"); }
__device__ __forceinline__ void prefetch_map(const CUtensorMap* m) { asm volatile("prefetch.tensormap [%0];" ::"l"(m) : "memory"); }
__device__ __forceinline__ void fence_async_smem() { asm volatile("fence.proxy.async.shared::cta;" ::: "memory"); }
__device__ __forceinline__ void fence_bar_init() { asm volatile("fence.mbarrier_init.release.cluster;" ::: "memory"); }
__device__ __forceinline__ void pdl_wait() { asm volatile("griddepcontrol.wait;" ::: "memory"); }
__device__ __forceinline__ void pdl_launch() { asm volatile("griddepcontrol.launch_dependents;" ::: "memory"); }
__device__ __forceinline__ void bar_sync(int id, int n) { asm volatile("bar.sync %0,%1;" ::"r"(id), "r"(n) : "memory"); }
__device__ __forceinline__ void bar_arrive(int id, int n) { asm volatile("bar.arrive %0,%1;" ::"r"(id), "r"(n) : "memory"); }
#define WG_FENCE() asm volatile("wgmma.fence.sync.aligned;" ::: "memory")
#define WG_COMMIT() asm volatile("wgmma.commit_group.sync.aligned;" ::: "memory")
#define WG_WAIT(n) asm volatile("wgmma.wait_group.sync.aligned " #n ";" ::: "memory")
template <int N> __device__ __forceinline__ void fence_regs(float* r) {
#pragma unroll
  for (int i = 0; i < N; i++) asm volatile("" : "+f"(r[i])::"memory");
}
#define REG_INC(n) asm volatile("setmaxnreg.inc.sync.aligned.u32 " #n ";")
#define REG_DEC(n) asm volatile("setmaxnreg.dec.sync.aligned.u32 " #n ";")
__device__ __forceinline__ uint64_t mkdesc(uint32_t addr, uint32_t lbo, uint32_t sbo, int sw) {
  return (uint64_t)((addr & 0x3FFFF) >> 4) | ((uint64_t)(lbo >> 4) << 16) | ((uint64_t)(sbo >> 4) << 32) | ((uint64_t)sw << 62);
}
__device__ __forceinline__ void ldsm4(uint32_t* r, uint32_t addr) {
  asm volatile("ldmatrix.sync.aligned.m8n8.x4.shared.b16 {%0,%1,%2,%3},[%4];" : "=r"(r[0]), "=r"(r[1]), "=r"(r[2]), "=r"(r[3]) : "r"(addr) : "memory");
}
__device__ __forceinline__ void stsm4(uint32_t addr, uint32_t r0, uint32_t r1, uint32_t r2, uint32_t r3) {
  asm volatile("stmatrix.sync.aligned.m8n8.x4.shared.b16 [%0],{%1,%2,%3,%4};" ::"r"(addr), "r"(r0), "r"(r1), "r"(r2), "r"(r3) : "memory");
}
__device__ __forceinline__ uint32_t pack_bf16(float lo, float hi) {
  uint32_t r;
  asm("cvt.rn.bf16x2.f32 %0,%1,%2;" : "=r"(r) : "f"(hi), "f"(lo));
  return r;
}
__device__ __forceinline__ float bf_lo(uint32_t v) { return __uint_as_float(v << 16); }
__device__ __forceinline__ float bf_hi(uint32_t v) { return __uint_as_float(v & 0xFFFF0000u); }
__device__ __forceinline__ float sq2(uint32_t v) { return bf_lo(v) * bf_lo(v) + bf_hi(v) * bf_hi(v); }
__device__ __forceinline__ float rbf(float x) { return __bfloat162float(__float2bfloat16_rn(x)); }
__device__ __forceinline__ uint32_t hfma2(uint32_t a, uint32_t b, uint32_t c) {
  uint32_t r;
  asm("fma.rn.bf16x2 %0,%1,%2,%3;" : "=r"(r) : "r"(a), "r"(b), "r"(c));
  return r;
}
__device__ __forceinline__ uint32_t hadd2(uint32_t a, uint32_t b) {
  uint32_t r;
  asm("add.rn.bf16x2 %0,%1,%2;" : "=r"(r) : "r"(a), "r"(b));
  return r;
}
__device__ __forceinline__ uint32_t hmul2(uint32_t a, uint32_t b) {
  uint32_t r;
  asm("mul.rn.bf16x2 %0,%1,%2;" : "=r"(r) : "r"(a), "r"(b));
  return r;
}
__device__ __forceinline__ uint32_t hneg2(uint32_t a) {
  uint32_t r;
  asm("neg.bf16x2 %0,%1;" : "=r"(r) : "r"(a));
  return r;
}
__device__ __forceinline__ float ex2f(float x) {
  float r;
  asm("ex2.approx.ftz.f32 %0,%1;" : "=f"(r) : "f"(x));
  return r;
}
__device__ __forceinline__ float sqrt_fast(float x) {
  float r;
  asm("sqrt.approx.f32 %0,%1;" : "=f"(r) : "f"(x));
  return r;
}
__device__ __forceinline__ float rcp_fast(float x) {
  float r;
  asm("rcp.approx.f32 %0,%1;" : "=f"(r) : "f"(x));
  return r;
}
__device__ __forceinline__ float tanhf_fast(float x) {
  float r;
  asm("tanh.approx.f32 %0,%1;" : "=f"(r) : "f"(x));
  return r;
}
__device__ __forceinline__ uint4 ln_consts(float mean, float var) {
  float m = rbf(mean), v = rbf(var);
  float s = rbf(sqrtf(rbf(v + 1e-5f)));
  float r = 1.0f / s;
  float rh = rbf(r), rl = r - rh;
  return make_uint4(pack_bf16(-m, -m), pack_bf16(rh, rh), pack_bf16(rl, rl), 0u);
}
__device__ __forceinline__ uint32_t ln_apply(uint32_t x, const uint4& st, uint32_t a, uint32_t s) {
  uint32_t d = hadd2(x, st.x);
  uint32_t n = hfma2(d, st.y, hmul2(d, st.z));
  return hfma2(n, a, s);
}

__device__ __forceinline__ uint4 lds128(uint32_t a) {
  uint4 v;
  asm volatile("ld.shared.v4.b32 {%0,%1,%2,%3},[%4];" : "=r"(v.x), "=r"(v.y), "=r"(v.z), "=r"(v.w) : "r"(a) : "memory");
  return v;
}
__device__ __forceinline__ void sts128(uint32_t a, const uint4& v) {
  asm volatile("st.shared.v4.b32 [%0],{%1,%2,%3,%4};" ::"r"(a), "r"(v.x), "r"(v.y), "r"(v.z), "r"(v.w) : "memory");
}
__device__ __forceinline__ void hmma(float* c, const uint32_t* a, uint32_t b0, uint32_t b1) {
  asm volatile("mma.sync.aligned.m16n8k16.row.col.f32.bf16.bf16.f32 {%0,%1,%2,%3},{%4,%5,%6,%7},{%8,%9},{%0,%1,%2,%3};"
               : "+f"(c[0]), "+f"(c[1]), "+f"(c[2]), "+f"(c[3]) : "r"(a[0]), "r"(a[1]), "r"(a[2]), "r"(a[3]), "r"(b0), "r"(b1));
}
struct RowStat {
  float s[4], q0[4], q1[4];
  __device__ __forceinline__ void init() {
#pragma unroll
    for (int i = 0; i < 4; i++) s[i] = q0[i] = q1[i] = 0.f;
  }
  __device__ __forceinline__ void add(const uint32_t* a) {
    hmma(s, a, 0x3F803F80u, 0x3F803F80u);
    hmma(q0, a, a[0], a[2]);
    hmma(q1, a, a[1], a[3]);
  }
  __device__ __forceinline__ void merge(const RowStat& o) {
#pragma unroll
    for (int i = 0; i < 4; i++) { s[i] += o.s[i]; q0[i] += o.q0[i]; q1[i] += o.q1[i]; }
  }
  __device__ __forceinline__ void finish(int lane, uint4& c0, uint4& c1) {
    const int g = lane >> 2, src = (lane & ~3) | (g >> 1);
    const float a0 = __shfl_sync(~0u, (g & 1) ? q0[1] : q0[0], src), a1 = __shfl_sync(~0u, (g & 1) ? q1[3] : q1[2], src);
    const float m0 = s[0] * (1.0f / DM), m1 = s[2] * (1.0f / DM);
    c0 = ln_consts(m0, fmaxf(a0 * (1.0f / DM) - m0 * m0, 0.f));
    c1 = ln_consts(m1, fmaxf(a1 * (1.0f / DM) - m1 * m1, 0.f));
  }
};
#define LN_CHUNK(c, LOAD)                                                       \
  LOAD(&a[(c) * 4], R + (c) * 16384, warp * 16, lane);                          \
  _Pragma("unroll") for (int k = (c) * 4; k < (c) * 4 + 4; k++) {               \
    const uint4 t = lds128(TAB + (k * 4 + (lane & 3)) * 16);                    \
    a[k][0] = ln_apply(a[k][0], s0, t.x, t.y);                                  \
    a[k][1] = ln_apply(a[k][1], s1, t.x, t.y);                                  \
    a[k][2] = ln_apply(a[k][2], s0, t.z, t.w);                                  \
    a[k][3] = ln_apply(a[k][3], s1, t.z, t.w);                                  \
  }

__device__ __forceinline__ void wg_ss_n72_t1(float* d, uint64_t da, uint64_t db, int sc) {
  asm volatile("{.reg .pred p; setp.ne.b32 p,%38,0; wgmma.mma_async.sync.aligned.m64n72k16.f32.bf16.bf16 {%0,%1,%2,%3,%4,%5,%6,%7,%8,%9,%10,%11,%12,%13,%14,%15,%16,%17,%18,%19,%20,%21,%22,%23,%24,%25,%26,%27,%28,%29,%30,%31,%32,%33,%34,%35}, %36, %37, p,1,1,0,1;}"
  : "+f"(d[0]),"+f"(d[1]),"+f"(d[2]),"+f"(d[3]),"+f"(d[4]),"+f"(d[5]),"+f"(d[6]),"+f"(d[7]),"+f"(d[8]),"+f"(d[9]),"+f"(d[10]),"+f"(d[11]),"+f"(d[12]),"+f"(d[13]),"+f"(d[14]),"+f"(d[15]),"+f"(d[16]),"+f"(d[17]),"+f"(d[18]),"+f"(d[19]),"+f"(d[20]),"+f"(d[21]),"+f"(d[22]),"+f"(d[23]),"+f"(d[24]),"+f"(d[25]),"+f"(d[26]),"+f"(d[27]),"+f"(d[28]),"+f"(d[29]),"+f"(d[30]),"+f"(d[31]),"+f"(d[32]),"+f"(d[33]),"+f"(d[34]),"+f"(d[35]) : "l"(da),"l"(db),"r"(sc));
}
template <int SC> __device__ __forceinline__ void wl_rs_n128_t1(float* d, const uint32_t* a, uint64_t e) {
  if (SC) asm volatile("wgmma.mma_async.sync.aligned.m64n128k16.f32.bf16.bf16 {%0,%1,%2,%3,%4,%5,%6,%7,%8,%9,%10,%11,%12,%13,%14,%15,%16,%17,%18,%19,%20,%21,%22,%23,%24,%25,%26,%27,%28,%29,%30,%31,%32,%33,%34,%35,%36,%37,%38,%39,%40,%41,%42,%43,%44,%45,%46,%47,%48,%49,%50,%51,%52,%53,%54,%55,%56,%57,%58,%59,%60,%61,%62,%63}, {%64,%65,%66,%67}, %68, 1,1,1,1;"
  : "+f"(d[0]),"+f"(d[1]),"+f"(d[2]),"+f"(d[3]),"+f"(d[4]),"+f"(d[5]),"+f"(d[6]),"+f"(d[7]),"+f"(d[8]),"+f"(d[9]),"+f"(d[10]),"+f"(d[11]),"+f"(d[12]),"+f"(d[13]),"+f"(d[14]),"+f"(d[15]),"+f"(d[16]),"+f"(d[17]),"+f"(d[18]),"+f"(d[19]),"+f"(d[20]),"+f"(d[21]),"+f"(d[22]),"+f"(d[23]),"+f"(d[24]),"+f"(d[25]),"+f"(d[26]),"+f"(d[27]),"+f"(d[28]),"+f"(d[29]),"+f"(d[30]),"+f"(d[31]),"+f"(d[32]),"+f"(d[33]),"+f"(d[34]),"+f"(d[35]),"+f"(d[36]),"+f"(d[37]),"+f"(d[38]),"+f"(d[39]),"+f"(d[40]),"+f"(d[41]),"+f"(d[42]),"+f"(d[43]),"+f"(d[44]),"+f"(d[45]),"+f"(d[46]),"+f"(d[47]),"+f"(d[48]),"+f"(d[49]),"+f"(d[50]),"+f"(d[51]),"+f"(d[52]),"+f"(d[53]),"+f"(d[54]),"+f"(d[55]),"+f"(d[56]),"+f"(d[57]),"+f"(d[58]),"+f"(d[59]),"+f"(d[60]),"+f"(d[61]),"+f"(d[62]),"+f"(d[63]) : "r"(a[0]),"r"(a[1]),"r"(a[2]),"r"(a[3]),"l"(e));
  else asm volatile("wgmma.mma_async.sync.aligned.m64n128k16.f32.bf16.bf16 {%0,%1,%2,%3,%4,%5,%6,%7,%8,%9,%10,%11,%12,%13,%14,%15,%16,%17,%18,%19,%20,%21,%22,%23,%24,%25,%26,%27,%28,%29,%30,%31,%32,%33,%34,%35,%36,%37,%38,%39,%40,%41,%42,%43,%44,%45,%46,%47,%48,%49,%50,%51,%52,%53,%54,%55,%56,%57,%58,%59,%60,%61,%62,%63}, {%64,%65,%66,%67}, %68, 0,1,1,1;"
  : "=f"(d[0]),"=f"(d[1]),"=f"(d[2]),"=f"(d[3]),"=f"(d[4]),"=f"(d[5]),"=f"(d[6]),"=f"(d[7]),"=f"(d[8]),"=f"(d[9]),"=f"(d[10]),"=f"(d[11]),"=f"(d[12]),"=f"(d[13]),"=f"(d[14]),"=f"(d[15]),"=f"(d[16]),"=f"(d[17]),"=f"(d[18]),"=f"(d[19]),"=f"(d[20]),"=f"(d[21]),"=f"(d[22]),"=f"(d[23]),"=f"(d[24]),"=f"(d[25]),"=f"(d[26]),"=f"(d[27]),"=f"(d[28]),"=f"(d[29]),"=f"(d[30]),"=f"(d[31]),"=f"(d[32]),"=f"(d[33]),"=f"(d[34]),"=f"(d[35]),"=f"(d[36]),"=f"(d[37]),"=f"(d[38]),"=f"(d[39]),"=f"(d[40]),"=f"(d[41]),"=f"(d[42]),"=f"(d[43]),"=f"(d[44]),"=f"(d[45]),"=f"(d[46]),"=f"(d[47]),"=f"(d[48]),"=f"(d[49]),"=f"(d[50]),"=f"(d[51]),"=f"(d[52]),"=f"(d[53]),"=f"(d[54]),"=f"(d[55]),"=f"(d[56]),"=f"(d[57]),"=f"(d[58]),"=f"(d[59]),"=f"(d[60]),"=f"(d[61]),"=f"(d[62]),"=f"(d[63]) : "r"(a[0]),"r"(a[1]),"r"(a[2]),"r"(a[3]),"l"(e));
}
template <int SC> __device__ __forceinline__ void wl_rs_n24_t1(float* d, const uint32_t* a, uint64_t e) {
  if (SC) asm volatile("wgmma.mma_async.sync.aligned.m64n24k16.f32.bf16.bf16 {%0,%1,%2,%3,%4,%5,%6,%7,%8,%9,%10,%11}, {%12,%13,%14,%15}, %16, 1,1,1,1;"
  : "+f"(d[0]),"+f"(d[1]),"+f"(d[2]),"+f"(d[3]),"+f"(d[4]),"+f"(d[5]),"+f"(d[6]),"+f"(d[7]),"+f"(d[8]),"+f"(d[9]),"+f"(d[10]),"+f"(d[11]) : "r"(a[0]),"r"(a[1]),"r"(a[2]),"r"(a[3]),"l"(e));
  else asm volatile("wgmma.mma_async.sync.aligned.m64n24k16.f32.bf16.bf16 {%0,%1,%2,%3,%4,%5,%6,%7,%8,%9,%10,%11}, {%12,%13,%14,%15}, %16, 0,1,1,1;"
  : "=f"(d[0]),"=f"(d[1]),"=f"(d[2]),"=f"(d[3]),"=f"(d[4]),"=f"(d[5]),"=f"(d[6]),"=f"(d[7]),"=f"(d[8]),"=f"(d[9]),"=f"(d[10]),"=f"(d[11]) : "r"(a[0]),"r"(a[1]),"r"(a[2]),"r"(a[3]),"l"(e));
}
template <int SC> __device__ __forceinline__ void wl_rs_n64_t0(float* d, const uint32_t* a, uint64_t e) {
  if (SC) asm volatile("wgmma.mma_async.sync.aligned.m64n64k16.f32.bf16.bf16 {%0,%1,%2,%3,%4,%5,%6,%7,%8,%9,%10,%11,%12,%13,%14,%15,%16,%17,%18,%19,%20,%21,%22,%23,%24,%25,%26,%27,%28,%29,%30,%31}, {%32,%33,%34,%35}, %36, 1,1,1,0;"
  : "+f"(d[0]),"+f"(d[1]),"+f"(d[2]),"+f"(d[3]),"+f"(d[4]),"+f"(d[5]),"+f"(d[6]),"+f"(d[7]),"+f"(d[8]),"+f"(d[9]),"+f"(d[10]),"+f"(d[11]),"+f"(d[12]),"+f"(d[13]),"+f"(d[14]),"+f"(d[15]),"+f"(d[16]),"+f"(d[17]),"+f"(d[18]),"+f"(d[19]),"+f"(d[20]),"+f"(d[21]),"+f"(d[22]),"+f"(d[23]),"+f"(d[24]),"+f"(d[25]),"+f"(d[26]),"+f"(d[27]),"+f"(d[28]),"+f"(d[29]),"+f"(d[30]),"+f"(d[31]) : "r"(a[0]),"r"(a[1]),"r"(a[2]),"r"(a[3]),"l"(e));
  else asm volatile("wgmma.mma_async.sync.aligned.m64n64k16.f32.bf16.bf16 {%0,%1,%2,%3,%4,%5,%6,%7,%8,%9,%10,%11,%12,%13,%14,%15,%16,%17,%18,%19,%20,%21,%22,%23,%24,%25,%26,%27,%28,%29,%30,%31}, {%32,%33,%34,%35}, %36, 0,1,1,0;"
  : "=f"(d[0]),"=f"(d[1]),"=f"(d[2]),"=f"(d[3]),"=f"(d[4]),"=f"(d[5]),"=f"(d[6]),"=f"(d[7]),"=f"(d[8]),"=f"(d[9]),"=f"(d[10]),"=f"(d[11]),"=f"(d[12]),"=f"(d[13]),"=f"(d[14]),"=f"(d[15]),"=f"(d[16]),"=f"(d[17]),"=f"(d[18]),"=f"(d[19]),"=f"(d[20]),"=f"(d[21]),"=f"(d[22]),"=f"(d[23]),"=f"(d[24]),"=f"(d[25]),"=f"(d[26]),"=f"(d[27]),"=f"(d[28]),"=f"(d[29]),"=f"(d[30]),"=f"(d[31]) : "r"(a[0]),"r"(a[1]),"r"(a[2]),"r"(a[3]),"l"(e));
}
template <int SC> __device__ __forceinline__ void wl_rs_n64_t1(float* d, const uint32_t* a, uint64_t e) {
  if (SC) asm volatile("wgmma.mma_async.sync.aligned.m64n64k16.f32.bf16.bf16 {%0,%1,%2,%3,%4,%5,%6,%7,%8,%9,%10,%11,%12,%13,%14,%15,%16,%17,%18,%19,%20,%21,%22,%23,%24,%25,%26,%27,%28,%29,%30,%31}, {%32,%33,%34,%35}, %36, 1,1,1,1;"
  : "+f"(d[0]),"+f"(d[1]),"+f"(d[2]),"+f"(d[3]),"+f"(d[4]),"+f"(d[5]),"+f"(d[6]),"+f"(d[7]),"+f"(d[8]),"+f"(d[9]),"+f"(d[10]),"+f"(d[11]),"+f"(d[12]),"+f"(d[13]),"+f"(d[14]),"+f"(d[15]),"+f"(d[16]),"+f"(d[17]),"+f"(d[18]),"+f"(d[19]),"+f"(d[20]),"+f"(d[21]),"+f"(d[22]),"+f"(d[23]),"+f"(d[24]),"+f"(d[25]),"+f"(d[26]),"+f"(d[27]),"+f"(d[28]),"+f"(d[29]),"+f"(d[30]),"+f"(d[31]) : "r"(a[0]),"r"(a[1]),"r"(a[2]),"r"(a[3]),"l"(e));
  else asm volatile("wgmma.mma_async.sync.aligned.m64n64k16.f32.bf16.bf16 {%0,%1,%2,%3,%4,%5,%6,%7,%8,%9,%10,%11,%12,%13,%14,%15,%16,%17,%18,%19,%20,%21,%22,%23,%24,%25,%26,%27,%28,%29,%30,%31}, {%32,%33,%34,%35}, %36, 0,1,1,1;"
  : "=f"(d[0]),"=f"(d[1]),"=f"(d[2]),"=f"(d[3]),"=f"(d[4]),"=f"(d[5]),"=f"(d[6]),"=f"(d[7]),"=f"(d[8]),"=f"(d[9]),"=f"(d[10]),"=f"(d[11]),"=f"(d[12]),"=f"(d[13]),"=f"(d[14]),"=f"(d[15]),"=f"(d[16]),"=f"(d[17]),"=f"(d[18]),"=f"(d[19]),"=f"(d[20]),"=f"(d[21]),"=f"(d[22]),"=f"(d[23]),"=f"(d[24]),"=f"(d[25]),"=f"(d[26]),"=f"(d[27]),"=f"(d[28]),"=f"(d[29]),"=f"(d[30]),"=f"(d[31]) : "r"(a[0]),"r"(a[1]),"r"(a[2]),"r"(a[3]),"l"(e));
}
template <int SC> __device__ __forceinline__ void wl_rs_n88_t1(float* d, const uint32_t* a, uint64_t e) {
  if (SC) asm volatile("wgmma.mma_async.sync.aligned.m64n88k16.f32.bf16.bf16 {%0,%1,%2,%3,%4,%5,%6,%7,%8,%9,%10,%11,%12,%13,%14,%15,%16,%17,%18,%19,%20,%21,%22,%23,%24,%25,%26,%27,%28,%29,%30,%31,%32,%33,%34,%35,%36,%37,%38,%39,%40,%41,%42,%43}, {%44,%45,%46,%47}, %48, 1,1,1,1;"
  : "+f"(d[0]),"+f"(d[1]),"+f"(d[2]),"+f"(d[3]),"+f"(d[4]),"+f"(d[5]),"+f"(d[6]),"+f"(d[7]),"+f"(d[8]),"+f"(d[9]),"+f"(d[10]),"+f"(d[11]),"+f"(d[12]),"+f"(d[13]),"+f"(d[14]),"+f"(d[15]),"+f"(d[16]),"+f"(d[17]),"+f"(d[18]),"+f"(d[19]),"+f"(d[20]),"+f"(d[21]),"+f"(d[22]),"+f"(d[23]),"+f"(d[24]),"+f"(d[25]),"+f"(d[26]),"+f"(d[27]),"+f"(d[28]),"+f"(d[29]),"+f"(d[30]),"+f"(d[31]),"+f"(d[32]),"+f"(d[33]),"+f"(d[34]),"+f"(d[35]),"+f"(d[36]),"+f"(d[37]),"+f"(d[38]),"+f"(d[39]),"+f"(d[40]),"+f"(d[41]),"+f"(d[42]),"+f"(d[43]) : "r"(a[0]),"r"(a[1]),"r"(a[2]),"r"(a[3]),"l"(e));
  else asm volatile("wgmma.mma_async.sync.aligned.m64n88k16.f32.bf16.bf16 {%0,%1,%2,%3,%4,%5,%6,%7,%8,%9,%10,%11,%12,%13,%14,%15,%16,%17,%18,%19,%20,%21,%22,%23,%24,%25,%26,%27,%28,%29,%30,%31,%32,%33,%34,%35,%36,%37,%38,%39,%40,%41,%42,%43}, {%44,%45,%46,%47}, %48, 0,1,1,1;"
  : "=f"(d[0]),"=f"(d[1]),"=f"(d[2]),"=f"(d[3]),"=f"(d[4]),"=f"(d[5]),"=f"(d[6]),"=f"(d[7]),"=f"(d[8]),"=f"(d[9]),"=f"(d[10]),"=f"(d[11]),"=f"(d[12]),"=f"(d[13]),"=f"(d[14]),"=f"(d[15]),"=f"(d[16]),"=f"(d[17]),"=f"(d[18]),"=f"(d[19]),"=f"(d[20]),"=f"(d[21]),"=f"(d[22]),"=f"(d[23]),"=f"(d[24]),"=f"(d[25]),"=f"(d[26]),"=f"(d[27]),"=f"(d[28]),"=f"(d[29]),"=f"(d[30]),"=f"(d[31]),"=f"(d[32]),"=f"(d[33]),"=f"(d[34]),"=f"(d[35]),"=f"(d[36]),"=f"(d[37]),"=f"(d[38]),"=f"(d[39]),"=f"(d[40]),"=f"(d[41]),"=f"(d[42]),"=f"(d[43]) : "r"(a[0]),"r"(a[1]),"r"(a[2]),"r"(a[3]),"l"(e));
}

#define POLY_MASK 0xB5u
#define QSCALE (0.23570226039551584f * 1.4426950408889634f)

#define NSTG 6
#define STG_BYTES 16384
#define R_BYTES (8 * 16384)
#define GEMM_SMEM (R_BYTES + NSTG * STG_BYTES + 3072)

__device__ __forceinline__ void load_a_chunk(uint32_t (*a)[4], uint32_t chunk_base, int row_in_tile, int lane) {
  const int r = row_in_tile + (lane & 7) + ((lane >> 3) & 1) * 8;
  const uint32_t rb = chunk_base + r * 128;
#pragma unroll
  for (int k = 0; k < 4; k++) ldsm4(a[k], rb + (((k * 2 + (lane >> 4)) ^ (r & 7)) << 4));
}

__device__ __forceinline__ void load_a_core(uint32_t (*a)[4], uint32_t chunk_base, int row_in_tile, int lane) {
  const uint32_t rb = chunk_base + (row_in_tile >> 6) * 8192 + ((row_in_tile & 63) + (lane & 15)) * 16 + (lane >> 4) * 1024;
#pragma unroll
  for (int k = 0; k < 4; k++) ldsm4(a[k], rb + k * 2048);
}

#define MMA_TILE(FN, ODD, pj) MMA_TILE_(FN, ODD, pj, )
#define MMA_TILE_(FN, ODD, pj, PRE)                                             \
  {                                                                             \
    uint32_t rb_ = RING >> 4;                                                   \
    asm volatile("" : "+r"(rb_));                                               \
    const uint64_t db = mkdesc(0, 8192, 1024, 1) + (uint32_t)__shfl_sync(~0u, rb_, 0); \
    _Pragma("unroll") for (int s = 0; s < 9; s++) {                             \
      const int g_ = 1 + (ODD) * 9 + s, st_ = g_ % NSTG;                        \
      PRE;                                                                      \
      mbar_wait(full + st_ * 8, (pj) ^ ((g_ / NSTG) & 1));                      \
      WG_FENCE();                                                               \
      if (s == 0) FN<0>(acc, a[0], db + st_ * 1024); else FN<1>(acc, a[s * 4], db + st_ * 1024); \
      _Pragma("unroll") for (int k = 1; k < 4; k++) FN<1>(acc, a[s * 4 + k], db + st_ * 1024 + k * 128); \
      WG_COMMIT();                                                              \
      if (s > 0) { WG_WAIT(1); if (lane == 0) mbar_arrive(empty + ((g_ - 1) % NSTG) * 8); } \
    }                                                                           \
    WG_WAIT(0);                                                                 \
    if (lane == 0) mbar_arrive(empty + ((9 + (ODD) * 9) % NSTG) * 8);           \
  }

template <int NG, int G0>
__device__ __forceinline__ void qkv_stage(const float* acc, uint32_t stg, int rowl, int cq, int nb) {
  const float vs0 = ((POLY_MASK >> ((rowl >> 3) & 7)) & 1) ? 0.5f : 1.0f, vs1 = ((POLY_MASK >> (((rowl >> 3) + 1) & 7)) & 1) ? 0.5f : 1.0f;
  const uint32_t base = stg + (rowl >> 3) * 384 + (rowl & 7) * 16;
#pragma unroll
  for (int j = 0; j < 9; j++) {
    const int cc = j * 8 + cq * 2, slot = (cc * 3641) >> 16, d = cc - slot * 18;
    const uint32_t ad = base + slot * 6144 + (d >> 3) * 128 + (d & 7) * 2;
#pragma unroll
    for (int per = 0; per < 3; per++) {
      const int i = per * 9 + j - G0, type = (nb * 3 + per) >> 3;
      if (i < 0 || i >= NG) continue;
      const float sc0 = type == 0 ? QSCALE : (type == 1 ? vs0 : 1.0f), sc1 = type == 0 ? QSCALE : (type == 1 ? vs1 : 1.0f);
      asm volatile("st.shared.b32 [%0],%1;" ::"r"(ad + per * 24576), "r"(pack_bf16(acc[4 * i] * sc0, acc[4 * i + 1] * sc0)) : "memory");
      asm volatile("st.shared.b32 [%0],%1;" ::"r"(ad + per * 24576 + 384), "r"(pack_bf16(acc[4 * i + 2] * sc1, acc[4 * i + 3] * sc1)) : "memory");
    }
  }
}

__device__ __forceinline__ float silu_f(float v) { return rbf(__fdividef(v, 1.0f + fminf(__expf(-v), 1e37f))); }
__device__ __forceinline__ float silu_bf(__nv_bfloat16 c) { return silu_f(__bfloat162float(c)); }
__device__ __forceinline__ void fma8(float* acc, float sv, const uint4& w) {
  acc[0] += sv * bf_lo(w.x); acc[1] += sv * bf_hi(w.x); acc[2] += sv * bf_lo(w.y); acc[3] += sv * bf_hi(w.y);
  acc[4] += sv * bf_lo(w.z); acc[5] += sv * bf_hi(w.z); acc[6] += sv * bf_lo(w.w); acc[7] += sv * bf_hi(w.w);
}
__device__ __forceinline__ int tab_pos(int col, int shift) {
  return (((col >> 4) * 4 + ((col & 7) >> 1)) * 4 + ((col >> 3) & 1) * 2 + shift) * 2 + (col & 1);
}
__device__ __forceinline__ float knorm_row(uint32_t slot, int row) {
  const uint32_t ad = slot + (row >> 3) * 384 + (row & 7) * 16;
  const uint4 u = lds128(ad), v = lds128(ad + 128);
  uint32_t w;
  asm volatile("ld.shared.b32 %0,[%1];" : "=r"(w) : "r"(ad + 256) : "memory");
  float q = sq2(u.x) + sq2(u.y) + sq2(u.z) + sq2(u.w) + sq2(v.x) + sq2(v.y) + sq2(v.z) + sq2(v.w) + sq2(w);
  if ((POLY_MASK >> ((row >> 3) & 7)) & 1) q *= 4.0f;
  return q == q ? q : __int_as_float(0x7f800000);
}

__global__ void __launch_bounds__(384, 1) k1_kernel(const __grid_constant__ CUtensorMap mx, const __grid_constant__ CUtensorMap mw,
                                                    const __grid_constant__ CUtensorMap mm, const __nv_bfloat16* __restrict__ cvec,
                                                    const uint8_t* __restrict__ wqkv, const uint4* __restrict__ wo) {
  extern __shared__ __align__(1024) uint8_t smem_raw[];
  const uint32_t sb = s2u(smem_raw);
  const uint32_t R = sb, RING = sb + R_BYTES, BAR = RING + NSTG * STG_BYTES, TAB = BAR + 512;
  const uint32_t full = BAR, empty = BAR + 64, xfull = BAR + 128;
  const int tid = threadIdx.x, lane = tid & 31, warp = tid >> 5;
  const int mb = blockIdx.x >> 3, nb = blockIdx.x & 7;
  if (tid == 0) TS(1, 0);
  if (tid == 288) { prefetch_map(&mx); prefetch_map(&mw); }
  if (tid == 256) {
    if (sb & 1023) __trap();
    for (int i = 0; i < NSTG; i++) { mbar_init(full + i * 8, 1); mbar_init(empty + i * 8, 8); }
    for (int i = 0; i < 9; i++) mbar_init(xfull + i * 8, 1);
    fence_bar_init();
    if (blockIdx.x < 72) {
      mbar_expect(xfull + 64, 18432);
      for (int i = 0; i < 3; i++) tma2d(RING + 4 * STG_BYTES + i * 6144, &mm, blockIdx.x * 16, i * 192, xfull + 64);
    }
  }
  __syncthreads();
  pdl_launch();
  if (lane == 0) {
    if (warp < 8) { mbar_expect(xfull + warp * 8, 16384); tma2d(R + warp * 16384, &mx, warp * 64, mb * 128, xfull + warp * 8); }
    if (warp == 1) { mbar_expect(full, 16384); tma2d(RING, &mx, 512, mb * 128, full); }
    if (warp == 9) asm volatile("cp.async.bulk.prefetch.L2.global [%0],%1;" ::"l"(wqkv + blockIdx.x * 15552), "r"(15552) : "memory");
  }
  __syncwarp();
  if (warp >= 8) {
    REG_DEC(24);
    const int pt = tid - 256;
    if (pt == 0) {
      for (int st = 1; st < 4; st++) {
        mbar_expect(full + st * 8, 16384);
        tma2d(RING + st * STG_BYTES, &mw, nb * 216, st * 64 - 64, full + st * 8);
        tma2d(RING + st * STG_BYTES + 8192, &mw, nb * 216 + 64, st * 64 - 64, full + st * 8);
      }
    }
    if (blockIdx.x < 72) {
      float* sf = (float*)(smem_raw + R_BYTES + 4 * STG_BYTES + 18432);
      if (pt < 72) {
        const uint4 cv = __ldg((const uint4*)cvec + pt);
        const uint32_t cw[4] = {cv.x, cv.y, cv.z, cv.w};
#pragma unroll
        for (int i = 0; i < 4; i++) { sf[pt * 8 + 2 * i] = silu_f(bf_lo(cw[i])); sf[pt * 8 + 2 * i + 1] = silu_f(bf_hi(cw[i])); }
      }
      bar_sync(3, 128);
      mbar_wait(xfull + 64, 0);
      float acc[8] = {0, 0, 0, 0, 0, 0, 0, 0};
#pragma unroll 1
      for (int i = 0; i < 9; i++) fma8(acc, sf[(pt >> 1) + 64 * i], lds128(RING + 4 * STG_BYTES + i * 2048 + pt * 16));
#pragma unroll
      for (int j = 0; j < 8; j++)
#pragma unroll
        for (int o = 2; o < 32; o *= 2) acc[j] += __shfl_xor_sync(~0u, acc[j], o);
      if (lane < 2) {
#pragma unroll
        for (int j = 0; j < 8; j++) sf[DM + (warp - 8) * 16 + lane * 8 + j] = acc[j];
      }
      bar_sync(3, 128);
      if (pt < 16) {
        const float v = rbf(sf[DM + pt] + sf[DM + 16 + pt] + sf[DM + 32 + pt] + sf[DM + 48 + pt]);
        const int n = blockIdx.x * 16 + pt, shift = n < DM;
        const uint32_t word = pack_bf16(shift ? v : 1.0f + v, 1.0f);
        asm volatile("st.relaxed.gpu.global.u32 [%0],%1;" ::"l"((uint32_t*)g_ll + tab_pos(shift ? n : n - DM, shift)), "r"(word) : "memory");
      }
      fence_async_smem();
      __syncwarp();
      if (pt == 0) TS(0, 1);
    }
    if (warp == 8) {
      if (lane == 0) {
        int st = 4; uint32_t ph = 0;
        for (int it = 3; it < 18; it++) {
          const int t = it / 9, s = it - t * 9;
          mbar_wait(empty + st * 8, ph ^ 1);
          mbar_expect(full + st * 8, 16384);
          tma2d(RING + st * STG_BYTES, &mw, nb * 216 + t * 128, s * 64, full + st * 8);
          tma2d(RING + st * STG_BYTES + 8192, &mw, nb * 216 + t * 128 + 64, s * 64, full + st * 8);
          if (++st == NSTG) { st = 0; ph ^= 1; }
        }
      }
    } else {
      const int ht = tid - 288;
      mbar_wait(full, 0);
#pragma unroll 2
      for (int j = ht; j < 324; j += 96) {
        const int i = blockIdx.x * 324 + j, k = i / 72, n8 = i - k * 72;
        g_wo[(n8 / 9) * 5184 + (k >> 3) * 72 + (n8 % 9) * 8 + (k & 7)] = __ldg(wo + i);
      }
      bar_sync(1, 352);
      for (int i = ht; i < 12 * 128; i += 96) {
        const int slot = i >> 7, row = i & 127, type = (nb * 12 + slot) >> 5;
        uint32_t v = 0;
        if (type == 1) v = ((POLY_MASK >> ((row >> 3) & 7)) & 1) ? 0x43403F00u : 0x40253F80u;
        if (type == 2) v = 0x3F80u;
        const uint32_t ad = R + slot * 6144 + (row >> 3) * 384 + 256 + (row & 7) * 16;
        asm volatile("st.shared.b32 [%0],%1;" ::"r"(ad + 4), "r"(v) : "memory");
        asm volatile("st.shared.v2.b32 [%0],{%1,%1};" ::"r"(ad + 8), "r"(0) : "memory");
      }
      fence_async_smem();
      bar_sync(2, 352);
      if (ht == 0) {
        for (int s = 0; s < 7; s++) bulk_s2g(g_qkv + (size_t)(nb * 12 + s) * 98304 + mb * 6144, R + s * 6144, 6144);
        bulk_commit();
      }
      for (int s = warp - 9; s < 7; s += 3) {
        const int gs = nb * 12 + s;
        if ((gs >> 5) != 1) continue;
        float mx2 = 0;
#pragma unroll 1
        for (int row = lane; row < 128; row += 32) mx2 = fmaxf(mx2, knorm_row(R + s * 6144, row));
#pragma unroll
        for (int o = 16; o; o >>= 1) mx2 = fmaxf(mx2, __shfl_xor_sync(~0u, mx2, o));
        if (lane == 0) g_kmax[(gs & 31) * 16 + mb] = mx2;
      }
      if (ht == 0) bulk_wait0();
    }
  } else {
    REG_INC(240);
    TSS(0);
    const int rowl = warp * 16;
    uint4 s0, s1;
    {
      RowStat rs, rt;
      rs.init(); rt.init();
      uint32_t f[4][4];
#pragma unroll 1
      for (int c = 0; c < 9; c++) {
        mbar_wait(c < 8 ? xfull + c * 8 : full, 0);
        load_a_chunk(f, R + c * 16384, rowl, lane);
        rs.add(f[0]); rt.add(f[1]); rs.add(f[2]); rt.add(f[3]);
      }
      rs.merge(rt);
      rs.finish(lane, s0, s1);
    }
    TSS(1);
    if (tid < 144) {
      uint4 u, v;
      int n = 0;
      do {
        asm volatile("ld.relaxed.gpu.global.v4.u32 {%0,%1,%2,%3},[%4];" : "=r"(u.x), "=r"(u.y), "=r"(u.z), "=r"(u.w) : "l"(g_ll + tid * 2) : "memory");
        asm volatile("ld.relaxed.gpu.global.v4.u32 {%0,%1,%2,%3},[%4];" : "=r"(v.x), "=r"(v.y), "=r"(v.z), "=r"(v.w) : "l"(g_ll + tid * 2 + 1) : "memory");
        if (++n > 4000000) __trap();
      } while (((u.x & u.y & u.z & u.w & v.x & v.y & v.z & v.w) >> 16) != 0x3F80u);
      sts128(TAB + tid * 16, make_uint4(__byte_perm(u.x, u.y, 0x5410), __byte_perm(u.z, u.w, 0x5410), __byte_perm(v.x, v.y, 0x5410), __byte_perm(v.z, v.w, 0x5410)));
    }
    bar_sync(4, 256);
    TSS(2);
    uint32_t a[36][4];
    float acc[64];
    MMA_TILE_(wl_rs_n128_t1, 0, 0, if (s < 8) { LN_CHUNK(s, load_a_chunk) } if (s == 1) { LN_CHUNK(8, load_a_chunk) if (lane == 0) mbar_arrive(empty); } if (s == 5) bar_arrive(1, 352));
    TSS(3);
    bar_sync(4, 256);
    int t2 = threadIdx.x;
    asm volatile("" : "+r"(t2));
    qkv_stage<16, 0>(acc, R, (t2 >> 5) * 16 + ((t2 & 31) >> 2), t2 & 3, nb);
    fence_async_smem();
    bar_arrive(2, 352);
    TSS(4);
    MMA_TILE(wl_rs_n88_t1, 1, 0);
    asm volatile("" : "+r"(t2));
    qkv_stage<11, 16>(acc, R, (t2 >> 5) * 16 + ((t2 & 31) >> 2), t2 & 3, nb);
    fence_async_smem();
    bar_sync(4, 256);
    TSS(5);
    if (tid == 0) {
      for (int s = 7; s < 12; s++) bulk_s2g(g_qkv + (size_t)(nb * 12 + s) * 98304 + mb * 6144, R + s * 6144, 6144);
      bulk_commit();
    }
    if (warp >= 3 && ((nb * 12 + 4 + warp) >> 5) == 1) {
      float mx2 = 0;
#pragma unroll
      for (int i = 0; i < 4; i++) mx2 = fmaxf(mx2, knorm_row(R + (4 + warp) * 6144, lane + 32 * i));
#pragma unroll
      for (int o = 16; o; o >>= 1) mx2 = fmaxf(mx2, __shfl_xor_sync(~0u, mx2, o));
      if (lane == 0) g_kmax[((nb * 12 + 4 + warp) & 31) * 16 + mb] = mx2;
    }
    if (tid == 0) bulk_wait0();
    TSS(6);
    TSDUMP(1);
  }
}

#define ATT_SMEM (2 * 98304 + 1024 + 256)

__device__ __forceinline__ uint32_t exp2_pair_fma(float t0, float t1) {
  uint32_t y;
  asm("prmt.b32 %0,%1,%2,0x6521;" : "=r"(y) : "r"(__float_as_uint(t0)), "r"(__float_as_uint(t1)));
  return hfma2(y, y | 0x3F803F80u, y | 0x007F007Fu);
}

__device__ __forceinline__ void softmax_fast(const float* s, uint32_t* p) {
#pragma unroll
  for (int i = 0; i < 8; i++) {
    if ((POLY_MASK >> i) & 1) {
      p[2 * i] = exp2_pair_fma(s[4 * i], s[4 * i + 1]);
      p[2 * i + 1] = exp2_pair_fma(s[4 * i + 2], s[4 * i + 3]);
    } else {
      p[2 * i] = pack_bf16(ex2f(s[4 * i]), ex2f(s[4 * i + 1]));
      p[2 * i + 1] = pack_bf16(ex2f(s[4 * i + 2]), ex2f(s[4 * i + 3]));
    }
  }
}
#define QK_MMA(S, kd)                                                           \
  wl_rs_n64_t0<0>(S, q, (kd));                                                  \
  wl_rs_n64_t0<1>(S, q + 4, (kd) + 16 - (8ull << 16));
#define PV_MMA(P, vd)                                                           \
  _Pragma("unroll") for (int t = 0; t < 4; t++) wl_rs_n24_t1<1>(o, P + 4 * t, (vd) + t * 48);

__device__ __forceinline__ void att_store(const float* o, int row0, int head, int lane) {
  const int cq = lane & 3;
  const float l0 = __shfl_sync(~0u, o[8], (lane & ~3) | 1), l1 = __shfl_sync(~0u, o[10], (lane & ~3) | 1);
  const float i0 = rcp_fast(l0), i1 = rcp_fast(l1);
  const int col = head * 18 + cq * 2;
  uint32_t* og = (uint32_t*)(g_o + (row0 >> 6) * 73728 + (col >> 3) * 1024 + (row0 & 63) * 16 + (col & 7) * 2);
  og[0] = pack_bf16(o[0] * i0, o[1] * i0);
  og[256] = pack_bf16(o[4] * i0, o[5] * i0);
  og[32] = pack_bf16(o[2] * i1, o[3] * i1);
  og[256 + 32] = pack_bf16(o[6] * i1, o[7] * i1);
  if (cq == 0) {
    og[512] = pack_bf16(o[8] * i0, o[9] * i0);
    og[512 + 32] = pack_bf16(o[10] * i1, o[11] * i1);
  }
}

__global__ void __launch_bounds__(512, 1) k2_kernel(const uint8_t* __restrict__ wg_, const uint8_t* __restrict__ wu,
                                                    const uint8_t* __restrict__ wd, const __nv_bfloat16* __restrict__ cvec,
                                                    const __nv_bfloat16* __restrict__ wmod) {
  extern __shared__ __align__(1024) uint8_t smem_raw[];
  const uint32_t sb = (s2u(smem_raw) + 1023) & ~1023u;
  const uint32_t KS = sb, VS = sb + 98304, BAR = sb + 2 * 98304;
  const int tid = threadIdx.x, lane = tid & 31, warp = tid >> 5, wg = tid >> 7;
  if (blockIdx.x < 4) {
    float* sf = (float*)smem_raw;
    const int part = blockIdx.x + 2;
    for (int i = tid; i < DM; i += 512) sf[i] = silu_bf(cvec[i]);
    if (part == 2 && tid < 80) g_cnt[tid] = 0;
    __nanosleep(4000);
    __syncthreads();
    if (tid < 432) {
      const int cg = tid % 72, rg = tid / 72;
      const __nv_bfloat16* w = wmod + (size_t)rg * 96 * 3456 + part * DM + cg * 8;
      float acc[8] = {0, 0, 0, 0, 0, 0, 0, 0};
#pragma unroll 1
      for (int r = 0; r < 96; r += 12) {
        uint4 v[12];
#pragma unroll
        for (int i = 0; i < 12; i++) v[i] = __ldg((const uint4*)(w + (size_t)(r + i) * 3456));
#pragma unroll
        for (int i = 0; i < 12; i++) fma8(acc, sf[rg * 96 + r + i], v[i]);
      }
#pragma unroll
      for (int j = 0; j < 8; j++) sf[DM + rg * DM + cg * 8 + j] = acc[j];
    }
    __syncthreads();
    for (int col = tid; col < DM; col += 512) {
      float v = 0;
#pragma unroll
      for (int j = 1; j < 7; j++) v += sf[j * DM + col];
      v = rbf(v);
      if (part == 2) g_ga[col] = __float2bfloat16_rn(v);
      else if (part == 5) g_gb[col] = __float2bfloat16_rn(v);
      else ((__nv_bfloat16*)g_tab2)[tab_pos(col, part == 3)] = __float2bfloat16_rn(0.5f * (part == 3 ? v : rbf(1.0f + v)));
    }
    pdl_wait();
    if (part == 2 && tid < 288) g_ll[tid] = make_uint4(0, 0, 0, 0);
    if (tid == 0) TS(0, 0);
    return;
  }
  const int bid = blockIdx.x - 4, head = bid >> 2, qb = bid & 3;
  if (tid == 0) {
    TS(2, 0);
    for (int i = 0; i < 16; i++) mbar_init(BAR + i * 8, 1);
    fence_bar_init();
  }
  __syncthreads();
  const int g = lane >> 2, cq = lane & 3;
  const int row0 = qb * 512 + wg * 128 + (warp & 3) * 16 + g;
  const uint8_t* qg = g_qkv + (size_t)head * 98304 + (row0 >> 3) * 384 + (row0 & 7) * 16 + cq * 4;
  pdl_wait();
  pdl_launch();
  if (tid == 0) TS(2, 1);
  const uint8_t* kg = g_qkv + (size_t)(32 + head) * 98304;
#define KV_LOAD(c) { mbar_expect(BAR + (c) * 8, 12288); bulk_g2s(KS + (c) * 6144, kg + (c) * 6144, 6144, BAR + (c) * 8); \
                     bulk_g2s(VS + (c) * 6144, kg + 32 * 98304 + (c) * 6144, 6144, BAR + (c) * 8); }
  if (lane == 0 && warp < 5) KV_LOAD(warp);
  __syncwarp();
  uint32_t q[8], q2[6];
  float kmax2 = __ldcg(g_kmax + head * 16 + (lane & 15));
#pragma unroll
  for (int i = 0; i < 6; i++) {
    q[i] = __ldcg((const uint32_t*)(qg + (i & 1) * 384 + (i >> 1) * 128));
    q2[i] = __ldcg((const uint32_t*)(qg + 3072 + (i & 1) * 384 + (i >> 1) * 128));
  }
  q[6] = __ldcg((const uint32_t*)(qg + 256 + 12 - cq * 4)); q[7] = __ldcg((const uint32_t*)(qg + 256 + 8 - cq * 4));
  const uint64_t dk = mkdesc(KS, 128, 384, 0), dv = mkdesc(VS, 384, 128, 0);
#pragma unroll
  for (int o = 8; o; o >>= 1) kmax2 = fmaxf(kmax2, __shfl_xor_sync(~0u, kmax2, o));
  float bd[4] = {sq2(q[0]) + sq2(q[2]) + sq2(q[4]), sq2(q[1]) + sq2(q[3]) + sq2(q[5]),
                 sq2(q2[0]) + sq2(q2[2]) + sq2(q2[4]), sq2(q2[1]) + sq2(q2[3]) + sq2(q2[5])};
  int ok = 1;
  if (tid == 0 && bd[0] + bd[3] + kmax2 != 1.2345f) TS(2, 5);
#pragma unroll
  for (int i = 0; i < 4; i++) {
    bd[i] += __shfl_xor_sync(~0u, bd[i], 1); bd[i] += __shfl_xor_sync(~0u, bd[i], 2);
    bd[i] = sqrt_fast(bd[i] * kmax2) * 1.01f + 1.0f;
    ok = ok && (bd[i] <= 62.0f);
  }
  {
    uint32_t all;
    asm volatile("{.reg .pred p,q; setp.ne.b32 p,%1,0; barrier.red.and.pred q,1,512,p; selp.u32 %0,1,0,q;}"
                 : "=r"(all) : "r"(ok) : "memory");
    ok = __all_sync(~0u, all);
  }
  float o[12];
#pragma unroll
  for (int i = 0; i < 12; i++) { o[i] = 0.f; asm volatile("" : "+f"(o[i])); }
  float s[32];
  uint32_t p[16];
  if (tid == 0) TS(2, 2);
  if (ok) {
    if (cq == 1) {
      q[4] = pack_bf16(-bd[0], 1.0f); q[5] = pack_bf16(-bd[1], 1.0f);
      q2[4] = pack_bf16(-bd[2], 1.0f); q2[5] = pack_bf16(-bd[3], 1.0f);
    }
    mbar_wait(BAR, 0);
    WG_FENCE();
    QK_MMA(s, dk);
    WG_COMMIT();
#pragma unroll 1
    for (int tile = 0; tile < 2; tile++) {
#pragma unroll 1
      for (int jj = 0; jj < 8; jj++) {
        const uint64_t kd = dk + (uint32_t)(jj * 768), vd = dv + (uint32_t)(jj * 768), kn = dk + (uint32_t)(((jj + 1) & 7) * 768);
        if (tile == 0) {
          if (lane == 0 && warp < 2 && 2 * jj + 5 + warp < 16) KV_LOAD(2 * jj + 5 + warp);
          if (lane == 0 && warp >= 4 && warp < 7)
            asm volatile("cp.async.bulk.prefetch.L2.global [%0],%1;" ::"l"((warp == 4 ? wg_ : warp == 5 ? wu : wd) + (bid * 8 + jj) * 5184), "r"(5184) : "memory");
          __syncwarp();
          mbar_wait(BAR + jj * 16 + 8, 0); mbar_wait(BAR + ((jj * 16 + 16) & 127), 0); if (tid == 0) TS(2, 8 + jj); }
#pragma unroll
        for (int u = 0; u < 4; u++) {
          WG_WAIT(0);
          fence_regs<32>(s);
          softmax_fast(s, p);
          if (u == 3 && jj == 7) {
#pragma unroll
            for (int i = 0; i < 6; i++) q[i] = q2[i];
          }
          WG_FENCE();
          PV_MMA(p, vd + u * 192);
          QK_MMA(s, u < 3 ? kd + u * 192 + 192 : kn);
          WG_COMMIT();
        }
      }
      WG_WAIT(0);
      fence_regs<12>(o);
      att_store(o, row0 + tile * 64, head, lane);
#pragma unroll
      for (int i = 0; i < 12; i++) o[i] = 0.f;
      fence_regs<12>(o);
      if (tid == 0 && tile == 0) TS(2, 3);
    }
  } else {
    if (lane == 0 && warp >= 5) KV_LOAD(warp);
    __syncwarp();
#pragma unroll 1
    for (int tile = 0; tile < 2; tile++) {
      float m0 = -INFINITY, m1 = -INFINITY;
#pragma unroll 1
      for (int j = 0; j < 32; j++) {
        mbar_wait(BAR + (j >> 1) * 8, 0);
        WG_FENCE();
        QK_MMA(s, dk + (uint32_t)(j * 192));
        WG_COMMIT();
        WG_WAIT(0);
        fence_regs<32>(s);
#pragma unroll
        for (int i = 0; i < 32; i++) if ((POLY_MASK >> (i >> 2)) & 1) s[i] *= 2.0f;
        float x0 = m0, x1 = m1;
#pragma unroll
        for (int i = 0; i < 8; i++) {
          x0 = fmaxf(x0, fmaxf(s[4 * i], s[4 * i + 1]));
          x1 = fmaxf(x1, fmaxf(s[4 * i + 2], s[4 * i + 3]));
        }
        x0 = fmaxf(x0, __shfl_xor_sync(~0u, x0, 1)); x0 = fmaxf(x0, __shfl_xor_sync(~0u, x0, 2));
        x1 = fmaxf(x1, __shfl_xor_sync(~0u, x1, 1)); x1 = fmaxf(x1, __shfl_xor_sync(~0u, x1, 2));
        const float c0 = ex2f(m0 - x0), c1 = ex2f(m1 - x1);
        m0 = x0; m1 = x1;
#pragma unroll
        for (int i = 0; i < 3; i++) { o[4 * i] *= c0; o[4 * i + 1] *= c0; o[4 * i + 2] *= c1; o[4 * i + 3] *= c1; }
#pragma unroll
        for (int i = 0; i < 8; i++) {
          p[2 * i] = pack_bf16(ex2f(s[4 * i] - x0), ex2f(s[4 * i + 1] - x0));
          p[2 * i + 1] = pack_bf16(ex2f(s[4 * i + 2] - x1), ex2f(s[4 * i + 3] - x1));
        }
        WG_FENCE();
        PV_MMA(p, dv + (uint32_t)(j * 192));
        WG_COMMIT();
        WG_WAIT(0);
        fence_regs<12>(o);
      }
      att_store(o, row0 + tile * 64, head, lane);
#pragma unroll
      for (int i = 0; i < 12; i++) o[i] = 0.f;
#pragma unroll
      for (int i = 0; i < 6; i++) q[i] = q2[i];
    }
  }
  if (tid == 0) TS(2, 4);
}

#define K3_SMEM (9 * 16384 + 9 * 9216 + 256)
__device__ __forceinline__ uint32_t res_pair(uint32_t x, uint32_t g, float s0, float s1) { return hadd2(x, hmul2(g, pack_bf16(s0, s1))); }
__global__ void __launch_bounds__(320, 1) k3_kernel(const __nv_bfloat16* __restrict__ x) {
  extern __shared__ __align__(1024) uint8_t smem_raw[];
  const uint32_t sb = s2u(smem_raw);
  const uint32_t A = sb, B = sb + 9 * 16384, BAR = B + 9 * 9216;
  const int tid = threadIdx.x, lane = tid & 31, warp = tid >> 5;
  const int mb = blockIdx.x >> 3, nb = blockIdx.x & 7;
  if (tid == 0) {
    TS(3, 0);
    if (sb & 1023) __trap();
    for (int i = 0; i < 9; i++) { mbar_init(BAR + i * 8, 1); mbar_expect(BAR + i * 8, 9216 + 16384); }
    fence_bar_init();
  }
  __syncthreads();
  if (warp >= 8) {
    if (tid == 256) {
      for (int s = 0; s < 9; s++) {
        bulk_g2s(B + s * 9216, g_wo + nb * 5184 + s * 576, 9216, BAR + s * 8);
      }
      TS(0, 2);
    }
    if (tid == 288) {
      pdl_wait();
      TS(0, 3);
      for (int c = 0; c < 18; c++) bulk_g2s(A + c * 8192, g_o + (mb * 2 + (c & 1)) * 73728 + (c >> 1) * 8192, 8192, BAR + (c >> 1) * 8);
    }
  } else {
    const int g = lane >> 2, cq = lane & 3, wg = warp >> 2;
    const int row = mb * 128 + warp * 16 + g, col = nb * 72 + cq * 2;
    uint32_t xv[20], ga[9];
#pragma unroll
    for (int i = 0; i < 9; i++) {
      xv[2 * i] = __ldg((const uint32_t*)(x + (size_t)row * DM + col + 8 * i));
      xv[2 * i + 1] = __ldg((const uint32_t*)(x + (size_t)(row + 8) * DM + col + 8 * i));
    }
    pdl_wait();
    pdl_launch();
    if (tid == 0) TS(3, 1);
#pragma unroll
    for (int i = 0; i < 9; i++) ga[i] = __ldcg((const uint32_t*)(g_ga + col + 8 * i));
    float acc[36];
    const uint64_t da = mkdesc(A + wg * 8192, 1024, 128, 0), db = mkdesc(B, 1152, 128, 0);
#pragma unroll 1
    for (int s = 0; s < 9; s++) {
      mbar_wait(BAR + s * 8, 0);
      if (tid == 0) TS(0, 4 + s);
      WG_FENCE();
#pragma unroll
      for (int k = 0; k < 4; k++) wg_ss_n72_t1(acc, da + s * 1024 + k * 128, db + s * 576 + k * 144, s | k);
      WG_COMMIT();
    }
    WG_WAIT(0);
    fence_regs<36>(acc);
    if (tid == 0) TS(3, 2);
    bar_sync(1, 256);
    const uint32_t stg = A + wg * 9216 + ((warp & 3) * 16 + g) * 16 + cq * 4;
#pragma unroll
    for (int i = 0; i < 9; i++) {
      xv[2 * i] = res_pair(xv[2 * i], ga[i], acc[4 * i], acc[4 * i + 1]);
      xv[2 * i + 1] = res_pair(xv[2 * i + 1], ga[i], acc[4 * i + 2], acc[4 * i + 3]);
      asm volatile("st.shared.b32 [%0],%1;" ::"r"(stg + i * 1024), "r"(xv[2 * i]) : "memory");
      asm volatile("st.shared.b32 [%0],%1;" ::"r"(stg + i * 1024 + 128), "r"(xv[2 * i + 1]) : "memory");
    }
    fence_async_smem();
    bar_sync(2 + wg, 128);
    if ((tid & 127) == 0) {
      bulk_s2g(g_x1 + (mb * 2 + wg) * 73728 + nb * 9216, A + wg * 9216, 9216);
      bulk_commit();
    }
    xv[18] = xv[19] = 0;
    RowStat rs;
    rs.init();
#pragma unroll
    for (int i = 0; i < 5; i++) rs.add(&xv[4 * i]);
    if (cq == (g >> 1)) {
      g_stat2[row * 8 + nb] = make_float2(rs.s[0], (g & 1) ? rs.q0[1] : rs.q0[0]);
      g_stat2[(row + 8) * 8 + nb] = make_float2(rs.s[2], (g & 1) ? rs.q1[3] : rs.q1[2]);
    }
    if ((tid & 127) == 0) bulk_wait0();
    if (tid == 0) TS(3, 3);
  }
}

__device__ __forceinline__ uint4 ln2_consts(int row, int cq) {
  const float4 p = __ldcg((const float4*)(g_stat2 + row * 8 + cq * 2));
  float s = p.x + p.z, q = p.y + p.w;
  s += __shfl_xor_sync(~0u, s, 1); q += __shfl_xor_sync(~0u, q, 1);
  s += __shfl_xor_sync(~0u, s, 2); q += __shfl_xor_sync(~0u, q, 2);
  const float mean = s * (1.0f / DM);
  return ln_consts(mean, fmaxf(q * (1.0f / DM) - mean * mean, 0.f));
}
__device__ __forceinline__ uint32_t glu_pair(float g0, float g1, float u0, float u1) {
  return pack_bf16(fmaf(tanhf_fast(g0), u0, u0), fmaf(tanhf_fast(g1), u1, u1));
}
template <int NG>
__device__ __forceinline__ void stage_part(const float* acc, uint32_t stg, int lane) {
  const int r = (lane & 7) + ((lane >> 3) & 1) * 8;
#pragma unroll
  for (int i = 0; i < NG; i += 2) {
    const int ch = i + (lane >> 4);
    stsm4(stg + r * (NG * 16) + ((ch ^ (r & 7)) << 4), pack_bf16(acc[4 * i], acc[4 * i + 1]), pack_bf16(acc[4 * i + 2], acc[4 * i + 3]),
          pack_bf16(acc[4 * i + 4], acc[4 * i + 5]), pack_bf16(acc[4 * i + 6], acc[4 * i + 7]));
  }
}
__global__ void __launch_bounds__(384, 1) k4_kernel(const __grid_constant__ CUtensorMap mg,
                                                    const __grid_constant__ CUtensorMap mu, const __grid_constant__ CUtensorMap md,
                                                    __nv_bfloat16* __restrict__ out) {
  extern __shared__ __align__(1024) uint8_t smem_raw[];
  const uint32_t sb = s2u(smem_raw);
  const uint32_t R = sb, RING = sb + R_BYTES, BAR = RING + NSTG * STG_BYTES, TAB = BAR + 512;
  const uint32_t full = BAR, empty = BAR + 64, xfull = BAR + 128, gfull = BAR + 272, sfull = BAR + 320;
  const int tid = threadIdx.x, lane = tid & 31, warp = tid >> 5;
  const int mb = blockIdx.x >> 3, fb = blockIdx.x & 7;
  if (tid == 0) {
    TS(4, 0);
    if (sb & 1023) __trap();
    for (int i = 0; i < 10; i++) mbar_init(sfull + i * 8, 4);
    for (int i = 0; i < NSTG; i++) { mbar_init(full + i * 8, 1); mbar_init(empty + i * 8, 8); }
    for (int i = 0; i < 9; i++) mbar_init(xfull + i * 8, 1);
    for (int i = 0; i < 5; i++) mbar_init(gfull + i * 8, 1);
    mbar_arrive(full);
    for (int i = 0; i < 9; i++) mbar_expect(xfull + i * 8, 16384);
    fence_bar_init();
  }
  __syncthreads();
  if (warp >= 8) {
    REG_DEC(24);
    if (lane == 0) {
      if (warp == 8) {
        int st = 1; uint32_t ph = 0;
        for (int it = 0; it < 126; it++) {
          const int t = it / 9, s = it - t * 9;
          const uint32_t dst = RING + st * STG_BYTES, fb_ = full + st * 8;
          mbar_wait(empty + st * 8, ph ^ 1);
          if (t < 9) {
            mbar_expect(fb_, 16384);
            tma2d(dst, &mg, fb * 576 + t * 64, s * 64, fb_);
            tma2d(dst + 8192, &mu, fb * 576 + t * 64, s * 64, fb_);
          } else {
            mbar_expect(fb_, t < 13 ? 16384 : 8192);
            tma2d(dst, &md, (t - 9) * 128, fb * 576 + s * 64, fb_);
            if (t < 13) tma2d(dst + 8192, &md, (t - 9) * 128 + 64, fb * 576 + s * 64, fb_);
          }
          if (++st == NSTG) { st = 0; ph ^= 1; }
        }
      } else if (warp < 11) {
        const int wg = warp - 9;
#pragma unroll 1
        for (int p = 0; p < 5; p++) {
          uint8_t* dst = g_part + (size_t)((fb * 16 + mb) * 5 + p) * 32768;
          mbar_wait(sfull + (p * 2 + wg) * 8, 0);
          if (p < 4) {
            bulk_s2g(dst + wg * 16384, R + p * 32768 + wg * 8192, 8192);
            bulk_s2g(dst + wg * 16384 + 8192, R + p * 32768 + 16384 + wg * 8192, 8192);
          } else {
            bulk_s2g(dst + wg * 8192, RING + wg * STG_BYTES + 8192, 8192);
          }
          bulk_commit();
          if (wg == 0 && p >= 3) TS(3, 11 + p);
          bulk_wait0();
          if (wg == 0) TS(3, 4 + p);
          asm volatile("fence.proxy.async.global;" ::: "memory");
          asm volatile("red.release.gpu.global.add.u32 [%0],1;" ::"l"(g_cnt + mb * 5 + p) : "memory");
        }
      } else {
        pdl_wait();
        for (int c = 0; c < 9; c++) {
          const int k = c < 2 ? c : (c == 2 ? 8 : c - 1);
          bulk_g2s(R + k * 16384, g_x1 + mb * 2 * 73728 + k * 8192, 8192, xfull + c * 8);
          bulk_g2s(R + k * 16384 + 8192, g_x1 + (mb * 2 + 1) * 73728 + k * 8192, 8192, xfull + c * 8);
        }
        mbar_wait(sfull, 0);
#pragma unroll 1
        for (int p = 0; p < 5; p++) {
          unsigned int v; int n = 0;
          do {
            asm volatile("ld.acquire.gpu.global.u32 %0,[%1];" : "=r"(v) : "l"(g_cnt + mb * 5 + p) : "memory");
          } while (v < 16 && ++n < 20000000);
          if (v < 16) __trap();
          asm volatile("fence.proxy.async.global;" ::: "memory");
          TS(3, 9 + p);
          const uint32_t sz = p < 4 ? 4096 : 2048;
          mbar_expect(gfull + p * 8, sz * 8);
#pragma unroll 1
          for (int f = 0; f < 8; f++)
            bulk_g2s(p < 4 ? R + p * 32768 + f * 4096 : RING + (2 + (f >> 2)) * STG_BYTES + 8192 + (f & 3) * 2048,
                     g_part + (size_t)((f * 16 + mb) * 5 + p) * 32768 + fb * sz, sz, gfull + p * 8);
        }
      }
    }
  } else {
    REG_INC(240);
    uint32_t a[36][4];
    const int wg = warp >> 2, wl = warp & 3;
    if (tid < 144) sts128(TAB + tid * 16, g_tab2[tid]);
    bar_sync(1, 256);
    pdl_wait();
    TSS(0);
    float acc[64];
    const uint32_t hsp = R + wg * 8192 + (wl * 16 + (lane & 15)) * 16 + (lane >> 4) * 1024;
#define GLU_SPILL(t)                                                            \
  _Pragma("unroll") for (int j = 0; j < 4; j++) {                               \
    uint32_t h[4];                                                              \
    _Pragma("unroll") for (int e = 0; e < 4; e++)                               \
      h[e] = glu_pair(acc[8 * j + 2 * e], acc[8 * j + 2 * e + 1], acc[32 + 8 * j + 2 * e], acc[32 + 8 * j + 2 * e + 1]); \
    asm volatile("st.shared.v4.b32 [%0],{%1,%2,%3,%4};" ::"r"(hsp + (t) * 16384 + j * 2048), "r"(h[0]), "r"(h[1]), "r"(h[2]), "r"(h[3]) : "memory"); \
  }
    {
      const uint4 s0 = ln2_consts(mb * 128 + warp * 16 + (lane >> 2), lane & 3), s1 = ln2_consts(mb * 128 + warp * 16 + (lane >> 2) + 8, lane & 3);
      TSS(1);
      MMA_TILE_(wl_rs_n128_t1, 0, 0,
                if (s < 8) { mbar_wait(xfull + (s + (s > 1)) * 8, 0); LN_CHUNK(s, load_a_core) }
                if (s == 1) { mbar_wait(xfull + 16, 0); LN_CHUNK(8, load_a_core) if (lane == 0) mbar_arrive(empty); });
    }
    GLU_SPILL(0);
#pragma unroll 1
    for (int t = 0; t < 3; t++) {
      MMA_TILE(wl_rs_n128_t1, 1, t & 1);
      GLU_SPILL(2 * t + 1);
      MMA_TILE(wl_rs_n128_t1, 0, (t & 1) ^ 1);
      GLU_SPILL(2 * t + 2);
    }
    MMA_TILE(wl_rs_n128_t1, 1, 1);
    GLU_SPILL(7);
    MMA_TILE(wl_rs_n128_t1, 0, 0);
#pragma unroll
    for (int j = 0; j < 4; j++)
#pragma unroll
      for (int e = 0; e < 4; e++)
        a[32 + j][e] = glu_pair(acc[8 * j + 2 * e], acc[8 * j + 2 * e + 1], acc[32 + 8 * j + 2 * e], acc[32 + 8 * j + 2 * e + 1]);
#pragma unroll
    for (int k = 0; k < 32; k++)
      asm volatile("ld.shared.v4.b32 {%0,%1,%2,%3},[%4];" : "=r"(a[k][0]), "=r"(a[k][1]), "=r"(a[k][2]), "=r"(a[k][3]) : "r"(hsp + (k >> 2) * 16384 + (k & 3) * 2048) : "memory");
    TSS(2);
    const uint32_t stg = R + (wl >> 1) * 16384 + wg * 8192 + (wl & 1) * 4096;
#define PART_OUT(p)                                                             \
  stage_part<16>(acc, stg + (p) * 32768, lane);                                 \
  fence_async_smem();                                                           \
  __syncwarp();                                                                 \
  if (lane == 0) mbar_arrive(sfull + ((p) * 2 + wg) * 8);
    bar_sync(2 + wg, 128);
#pragma unroll 1
    for (int p = 0; p < 2; p++) {
      MMA_TILE(wl_rs_n128_t1, 1, p);
      PART_OUT(2 * p);
      MMA_TILE(wl_rs_n128_t1, 0, p ^ 1);
      PART_OUT(2 * p + 1);
    }
    MMA_TILE(wl_rs_n64_t1, 1, 0);
    stage_part<8>(acc, RING + wg * STG_BYTES + 8192 + wl * 2048, lane);
    fence_async_smem();
    __syncwarp();
    if (lane == 0) mbar_arrive(sfull + (8 + wg) * 8);
    TSS(3);
    const int rl = tid >> 4, ch = tid & 15;
    const size_t off = (size_t)(mb * 128 + fb * 16 + rl) * DM + ch * 8;
    uint4 xv[5], gv[5];
#pragma unroll
    for (int p = 0; p < 5; p++)
      if (p < 4 || ch < 8) { xv[p] = __ldcg((const uint4*)(g_x1 + (mb * 2 + (fb >> 2)) * 73728 + (p * 16 + ch) * 1024 + ((fb & 3) * 16 + rl) * 16)); gv[p] = __ldcg((const uint4*)(g_gb + p * 128 + ch * 8)); }
#pragma unroll
    for (int p = 0; p < 5; p++) {
      if (p == 4 && ch >= 8) break;
      mbar_wait(gfull + p * 8, 0);
      float r8[8] = {0, 0, 0, 0, 0, 0, 0, 0};
#pragma unroll
      for (int f = 0; f < 8; f++) {
        const uint4 v = lds128((p < 4 ? R + p * 32768 + f * 4096 + rl * 256 : RING + (2 + (f >> 2)) * STG_BYTES + 8192 + (f & 3) * 2048 + rl * 128) +
                               ((ch ^ (rl & 7)) << 4));
        r8[0] += bf_lo(v.x); r8[1] += bf_hi(v.x); r8[2] += bf_lo(v.y); r8[3] += bf_hi(v.y);
        r8[4] += bf_lo(v.z); r8[5] += bf_hi(v.z); r8[6] += bf_lo(v.w); r8[7] += bf_hi(v.w);
      }
      uint4 r;
      r.x = res_pair(xv[p].x, gv[p].x, r8[0], r8[1]);
      r.y = res_pair(xv[p].y, gv[p].y, r8[2], r8[3]);
      r.z = res_pair(xv[p].z, gv[p].z, r8[4], r8[5]);
      r.w = res_pair(xv[p].w, gv[p].w, r8[6], r8[7]);
      *(uint4*)(out + off + p * 128) = r;
      if (p >= 2) TSS(2 + p);
    }
    TSDUMP(4);
  }
}

typedef CUresult (*EncodeFn)(CUtensorMap*, CUtensorMapDataType, cuuint32_t, void*, const cuuint64_t*, const cuuint64_t*,
                             const cuuint32_t*, const cuuint32_t*, CUtensorMapInterleave, CUtensorMapSwizzle,
                             CUtensorMapL2promotion, CUtensorMapFloatOOBfill);
static void make_map(EncodeFn fn, CUtensorMap* m, const void* p, int rows, int cols, int box_rows, int box_cols = 64) {
  cuuint64_t dims[2] = {(cuuint64_t)cols, (cuuint64_t)rows};
  cuuint64_t strides[1] = {(cuuint64_t)cols * 2};
  cuuint32_t box[2] = {(cuuint32_t)box_cols, (cuuint32_t)box_rows};
  cuuint32_t es[2] = {1, 1};
  fn(m, CU_TENSOR_MAP_DATA_TYPE_BFLOAT16, 2, (void*)p, dims, strides, box, es, CU_TENSOR_MAP_INTERLEAVE_NONE,
     box_cols == 64 ? CU_TENSOR_MAP_SWIZZLE_128B : CU_TENSOR_MAP_SWIZZLE_NONE,
     box_cols == 64 ? CU_TENSOR_MAP_L2_PROMOTION_L2_256B : CU_TENSOR_MAP_L2_PROMOTION_NONE, CU_TENSOR_MAP_FLOAT_OOB_FILL_NONE);
}
template <typename... KA, typename... A>
static void launch(void (*k)(KA...), int grid, int block, int smem, bool pdl, A... args) {
  cudaLaunchConfig_t cfg = {};
  cfg.gridDim = dim3(grid); cfg.blockDim = dim3(block); cfg.dynamicSmemBytes = smem; cfg.stream = cudaStreamPerThread;
  cudaLaunchAttribute at;
  at.id = cudaLaunchAttributeProgrammaticStreamSerialization;
  at.val.programmaticStreamSerializationAllowed = 1;
  cfg.attrs = &at; cfg.numAttrs = pdl ? 1 : 0;
  cudaLaunchKernelEx(&cfg, k, KA(args)...);
}

extern "C" void kernel_launch(void* const* d_in, const int* in_sizes, int n_in, void* d_out, int out_size) {
  const __nv_bfloat16* x = (const __nv_bfloat16*)d_in[0];
  void* fnp = nullptr;
  cudaDriverEntryPointQueryResult qr;
  cudaGetDriverEntryPoint("cuTensorMapEncodeTiled", &fnp, cudaEnableDefault, &qr);
  EncodeFn fn = (EncodeFn)fnp;
  CUtensorMap mm, mx, mqkv, mg, mu, md;
  make_map(fn, &mm, d_in[8], DM, 6 * DM, 192, 16);
  make_map(fn, &mx, x, SEQ, DM, 128);
  make_map(fn, &mqkv, d_in[1], DM, 3 * DM, 64);
  make_map(fn, &mg, d_in[4], DM, FF, 64);
  make_map(fn, &mu, d_in[5], DM, FF, 64);
  make_map(fn, &md, d_in[6], FF, DM, 64);
  cudaFuncSetAttribute(k1_kernel, cudaFuncAttributeMaxDynamicSharedMemorySize, GEMM_SMEM);
  cudaFuncSetAttribute(k2_kernel, cudaFuncAttributeMaxDynamicSharedMemorySize, ATT_SMEM);
  cudaFuncSetAttribute(k3_kernel, cudaFuncAttributeMaxDynamicSharedMemorySize, K3_SMEM);
  cudaFuncSetAttribute(k4_kernel, cudaFuncAttributeMaxDynamicSharedMemorySize, GEMM_SMEM);
  launch(k1_kernel, 128, 384, GEMM_SMEM, false, mx, mqkv, mm, (const __nv_bfloat16*)d_in[7], (const uint8_t*)d_in[1], (const uint4*)d_in[2]);
  launch(k2_kernel, 132, 512, ATT_SMEM, true, (const uint8_t*)d_in[4], (const uint8_t*)d_in[5], (const uint8_t*)d_in[6],
         (const __nv_bfloat16*)d_in[7], (const __nv_bfloat16*)d_in[8]);
  launch(k3_kernel, 128, 320, K3_SMEM, true, x);
  launch(k4_kernel, 128, 384, GEMM_SMEM, true, mg, mu, md, (__nv_bfloat16*)d_out);
}
```

```cpp
#include <cuda_runtime.h>
#include <cuda_bf16.h>
#include <cuda.h>
#include <stdint.h>

#define SEQ 2048
#define DM 576
#define NH 32
#define FF 4608

__device__ uint4 g_ll[36 * 4 * 2];
__device__ uint4 g_tab2[36 * 4];
__device__ __align__(16) __nv_bfloat16 g_ga[DM];
__device__ __align__(16) __nv_bfloat16 g_gb[DM];
__device__ float2 g_stat2[SEQ * 8];
__device__ __align__(1024) uint8_t g_qkv[96 * 98304];
__device__ float g_kmax[NH * 16];
__device__ __align__(1024) uint8_t g_o[SEQ * DM * 2];
__device__ __align__(1024) uint8_t g_x1[SEQ * DM * 2];
__device__ __align__(1024) uint4 g_wo[DM * DM / 8];
__device__ __align__(1024) uint8_t g_part[8 * 16 * 5 * 2 * 16384];
__device__ unsigned int g_cnt[16 * 5];

#define TS(k, i)
#define TSS(i)
#define TSDUMP(k)
__device__ __forceinline__ uint32_t s2u(const void* p) { return (uint32_t)__cvta_generic_to_shared(p); }
__device__ __forceinline__ void mbar_init(uint32_t b, int c) { asm volatile("mbarrier.init.shared::cta.b64 [%0],%1;" ::"r"(b), "r"(c)); }
__device__ __forceinline__ void mbar_expect(uint32_t b, uint32_t n) { asm volatile("mbarrier.arrive.expect_tx.shared::cta.b64 _,[%0],%1;" ::"r"(b), "r"(n) : "memory"); }
__device__ __forceinline__ void mbar_arrive(uint32_t b) { asm volatile("mbarrier.arrive.shared::cta.b64 _,[%0];" ::"r"(b) : "memory"); }
__device__ __forceinline__ void mbar_wait(uint32_t b, uint32_t ph) {
  asm volatile(
      "{.reg .pred p; .reg .u32 n;\n"
      "mbarrier.try_wait.parity.shared::cta.b64 p,[%0],%1;\n"
      "@p bra D;\n"
      "mov.u32 n,0;\n"
      "W: mbarrier.try_wait.parity.shared::cta.b64 p,[%0],%1;\n"
      "@p bra D;\n"
      "add.u32 n,n,1; setp.lt.u32 p,n,4000000; @p bra W;\n"
      "trap;\n"
      "D: }" ::"r"(b), "r"(ph) : "memory");
}
__device__ __forceinline__ void tma2d(uint32_t dst, const CUtensorMap* m, int c0, int c1, uint32_t bar) {
  asm volatile("cp.async.bulk.tensor.2d.shared::cluster.global.mbarrier::complete_tx::bytes [%0],[%1,{%3,%4}],[%2];"
               ::"r"(dst), "l"(m), "r"(bar), "r"(c0), "r"(c1) : "memory");
}
__device__ __forceinline__ void bulk_g2s(uint32_t dst, const void* src, uint32_t bytes, uint32_t bar) {
  asm volatile("cp.async.bulk.shared::cluster.global.mbarrier::complete_tx::bytes [%0],[%1],%2,[%3];"
               ::"r"(dst), "l"(src), "r"(bytes), "r"(bar) : "memory");
}
__device__ __forceinline__ void bulk_s2g(void* dst, uint32_t src, uint32_t bytes) {
  asm volatile("cp.async.bulk.global.shared::cta.bulk_group [%0],[%1],%2;" ::"l"(dst), "r"(src), "r"(bytes) : "memory");
}
__device__ __forceinline__ void bulk_commit() { asm volatile("cp.async.bulk.commit_group;" ::: "memory"); }
__device__ __forceinline__ void bulk_wait0() { asm volatile("cp.async.bulk.wait_group 0;" ::: "memory"); }
__device__ __forceinline__ void prefetch_map(const CUtensorMap* m) { asm volatile("prefetch.tensormap [%0];" ::"l"(m) : "memory"); }
__device__ __forceinline__ void fence_async_smem() { asm volatile("fence.proxy.async.shared::cta;" ::: "memory"); }
__device__ __forceinline__ void bulk_g2s_mc(uint32_t dst, const void* src, uint32_t bytes, uint32_t bar) {
  asm volatile("cp.async.bulk.shared::cluster.global.mbarrier::complete_tx::bytes.multicast::cluster [%0],[%1],%2,[%3],%4;"
               ::"r"(dst), "l"(src), "r"(bytes), "r"(bar), "h"((uint16_t)3) : "memory");
}
__device__ __forceinline__ void tma2d_mc(uint32_t dst, const CUtensorMap* m, int c0, int c1, uint32_t bar) {
  asm volatile("cp.async.bulk.tensor.2d.shared::cluster.global.mbarrier::complete_tx::bytes.multicast::cluster [%0],[%1,{%3,%4}],[%2],%5;"
               ::"r"(dst), "l"(m), "r"(bar), "r"(c0), "r"(c1), "h"((uint16_t)3) : "memory");
}
__device__ __forceinline__ void pair_sync() { asm volatile("barrier.cluster.arrive.relaxed.aligned;\nbarrier.cluster.wait.acquire.aligned;" ::: "memory"); }
#define MC 7
#define CL1 __cluster_dims__(2, 1, 1)
#define CL3 __cluster_dims__(2, 1, 1)
#define MW 0
#define CL4 __cluster_dims__(2, 1, 1)
__device__ __forceinline__ void fence_bar_init() { asm volatile("fence.mbarrier_init.release.cluster;" ::: "memory"); }
__device__ __forceinline__ void pdl_wait() { asm volatile("griddepcontrol.wait;" ::: "memory"); }
__device__ __forceinline__ void pdl_launch() { asm volatile("griddepcontrol.launch_dependents;" ::: "memory"); }
__device__ __forceinline__ void bar_sync(int id, int n) { asm volatile("bar.sync %0,%1;" ::"r"(id), "r"(n) : "memory"); }
__device__ __forceinline__ void bar_arrive(int id, int n) { asm volatile("bar.arrive %0,%1;" ::"r"(id), "r"(n) : "memory"); }
#define WG_FENCE() asm volatile("wgmma.fence.sync.aligned;" ::: "memory")
#define WG_COMMIT() asm volatile("wgmma.commit_group.sync.aligned;" ::: "memory")
#define WG_WAIT(n) asm volatile("wgmma.wait_group.sync.aligned " #n ";" ::: "memory")
template <int N> __device__ __forceinline__ void fence_regs(float* r) {
#pragma unroll
  for (int i = 0; i < N; i++) asm volatile("" : "+f"(r[i])::"memory");
}
#define REG_INC(n) asm volatile("setmaxnreg.inc.sync.aligned.u32 " #n ";")
#define REG_DEC(n) asm volatile("setmaxnreg.dec.sync.aligned.u32 " #n ";")
__device__ __forceinline__ uint64_t mkdesc(uint32_t addr, uint32_t lbo, uint32_t sbo, int sw) {
  return (uint64_t)((addr & 0x3FFFF) >> 4) | ((uint64_t)(lbo >> 4) << 16) | ((uint64_t)(sbo >> 4) << 32) | ((uint64_t)sw << 62);
}
__device__ __forceinline__ void ldsm4(uint32_t* r, uint32_t addr) {
  asm volatile("ldmatrix.sync.aligned.m8n8.x4.shared.b16 {%0,%1,%2,%3},[%4];" : "=r"(r[0]), "=r"(r[1]), "=r"(r[2]), "=r"(r[3]) : "r"(addr) : "memory");
}
__device__ __forceinline__ void stsm4(uint32_t addr, uint32_t r0, uint32_t r1, uint32_t r2, uint32_t r3) {
  asm volatile("stmatrix.sync.aligned.m8n8.x4.shared.b16 [%0],{%1,%2,%3,%4};" ::"r"(addr), "r"(r0), "r"(r1), "r"(r2), "r"(r3) : "memory");
}
__device__ __forceinline__ uint32_t pack_bf16(float lo, float hi) {
  uint32_t r;
  asm("cvt.rn.bf16x2.f32 %0,%1,%2;" : "=r"(r) : "f"(hi), "f"(lo));
  return r;
}
__device__ __forceinline__ float bf_lo(uint32_t v) { return __uint_as_float(v << 16); }
__device__ __forceinline__ float bf_hi(uint32_t v) { return __uint_as_float(v & 0xFFFF0000u); }
__device__ __forceinline__ float sq2(uint32_t v) { return bf_lo(v) * bf_lo(v) + bf_hi(v) * bf_hi(v); }
__device__ __forceinline__ float rbf(float x) { return __bfloat162float(__float2bfloat16_rn(x)); }
__device__ __forceinline__ uint32_t hfma2(uint32_t a, uint32_t b, uint32_t c) {
  uint32_t r;
  asm("fma.rn.bf16x2 %0,%1,%2,%3;" : "=r"(r) : "r"(a), "r"(b), "r"(c));
  return r;
}
__device__ __forceinline__ uint32_t hadd2(uint32_t a, uint32_t b) {
  uint32_t r;
  asm("add.rn.bf16x2 %0,%1,%2;" : "=r"(r) : "r"(a), "r"(b));
  return r;
}
__device__ __forceinline__ uint32_t hmul2(uint32_t a, uint32_t b) {
  uint32_t r;
  asm("mul.rn.bf16x2 %0,%1,%2;" : "=r"(r) : "r"(a), "r"(b));
  return r;
}
__device__ __forceinline__ uint32_t hneg2(uint32_t a) {
  uint32_t r;
  asm("neg.bf16x2 %0,%1;" : "=r"(r) : "r"(a));
  return r;
}
__device__ __forceinline__ float ex2f(float x) {
  float r;
  asm("ex2.approx.ftz.f32 %0,%1;" : "=f"(r) : "f"(x));
  return r;
}
__device__ __forceinline__ float sqrt_fast(float x) {
  float r;
  asm("sqrt.approx.f32 %0,%1;" : "=f"(r) : "f"(x));
  return r;
}
__device__ __forceinline__ float rcp_fast(float x) {
  float r;
  asm("rcp.approx.f32 %0,%1;" : "=f"(r) : "f"(x));
  return r;
}
__device__ __forceinline__ float tanhf_fast(float x) {
  float r;
  asm("tanh.approx.f32 %0,%1;" : "=f"(r) : "f"(x));
  return r;
}
__device__ __forceinline__ uint4 ln_consts(float mean, float var) {
  float m = rbf(mean), v = rbf(var);
  float s = rbf(sqrtf(rbf(v + 1e-5f)));
  float r = 1.0f / s;
  float rh = rbf(r), rl = r - rh;
  return make_uint4(pack_bf16(-m, -m), pack_bf16(rh, rh), pack_bf16(rl, rl), 0u);
}
__device__ __forceinline__ uint32_t ln_apply(uint32_t x, const uint4& st, uint32_t a, uint32_t s) {
  uint32_t d = hadd2(x, st.x);
  uint32_t n = hfma2(d, st.y, hmul2(d, st.z));
  return hfma2(n, a, s);
}

__device__ __forceinline__ uint4 lds128(uint32_t a) {
  uint4 v;
  asm volatile("ld.shared.v4.b32 {%0,%1,%2,%3},[%4];" : "=r"(v.x), "=r"(v.y), "=r"(v.z), "=r"(v.w) : "r"(a) : "memory");
  return v;
}
__device__ __forceinline__ void sts128(uint32_t a, const uint4& v) {
  asm volatile("st.shared.v4.b32 [%0],{%1,%2,%3,%4};" ::"r"(a), "r"(v.x), "r"(v.y), "r"(v.z), "r"(v.w) : "memory");
}
__device__ __forceinline__ void hmma(float* c, const uint32_t* a, uint32_t b0, uint32_t b1) {
  asm volatile("mma.sync.aligned.m16n8k16.row.col.f32.bf16.bf16.f32 {%0,%1,%2,%3},{%4,%5,%6,%7},{%8,%9},{%0,%1,%2,%3};"
               : "+f"(c[0]), "+f"(c[1]), "+f"(c[2]), "+f"(c[3]) : "r"(a[0]), "r"(a[1]), "r"(a[2]), "r"(a[3]), "r"(b0), "r"(b1));
}
struct RowStat {
  float s[4], q0[4], q1[4];
  __device__ __forceinline__ void init() {
#pragma unroll
    for (int i = 0; i < 4; i++) s[i] = q0[i] = q1[i] = 0.f;
  }
  __device__ __forceinline__ void add(const uint32_t* a) {
    hmma(s, a, 0x3F803F80u, 0x3F803F80u);
    hmma(q0, a, a[0], a[2]);
    hmma(q1, a, a[1], a[3]);
  }
  __device__ __forceinline__ void merge(const RowStat& o) {
#pragma unroll
    for (int i = 0; i < 4; i++) { s[i] += o.s[i]; q0[i] += o.q0[i]; q1[i] += o.q1[i]; }
  }
  __device__ __forceinline__ void finish(int lane, uint4& c0, uint4& c1) {
    const int g = lane >> 2, src = (lane & ~3) | (g >> 1);
    const float a0 = __shfl_sync(~0u, (g & 1) ? q0[1] : q0[0], src), a1 = __shfl_sync(~0u, (g & 1) ? q1[3] : q1[2], src);
    const float m0 = s[0] * (1.0f / DM), m1 = s[2] * (1.0f / DM);
    c0 = ln_consts(m0, fmaxf(a0 * (1.0f / DM) - m0 * m0, 0.f));
    c1 = ln_consts(m1, fmaxf(a1 * (1.0f / DM) - m1 * m1, 0.f));
  }
};
#define LN_CHUNK(c, LOAD)                                                       \
  LOAD(&a[(c) * 4], R + (c) * 16384, warp * 16, lane);                          \
  _Pragma("unroll") for (int k = (c) * 4; k < (c) * 4 + 4; k++) {               \
    const uint4 t = lds128(TAB + (k * 4 + (lane & 3)) * 16);                    \
    a[k][0] = ln_apply(a[k][0], s0, t.x, t.y);                                  \
    a[k][1] = ln_apply(a[k][1], s1, t.x, t.y);                                  \
    a[k][2] = ln_apply(a[k][2], s0, t.z, t.w);                                  \
    a[k][3] = ln_apply(a[k][3], s1, t.z, t.w);                                  \
  }

__device__ __forceinline__ void wg_ss_n72_t1(float* d, uint64_t da, uint64_t db, int sc) {
  asm volatile("{.reg .pred p; setp.ne.b32 p,%38,0; wgmma.mma_async.sync.aligned.m64n72k16.f32.bf16.bf16 {%0,%1,%2,%3,%4,%5,%6,%7,%8,%9,%10,%11,%12,%13,%14,%15,%16,%17,%18,%19,%20,%21,%22,%23,%24,%25,%26,%27,%28,%29,%30,%31,%32,%33,%34,%35}, %36, %37, p,1,1,0,1;}"
  : "+f"(d[0]),"+f"(d[1]),"+f"(d[2]),"+f"(d[3]),"+f"(d[4]),"+f"(d[5]),"+f"(d[6]),"+f"(d[7]),"+f"(d[8]),"+f"(d[9]),"+f"(d[10]),"+f"(d[11]),"+f"(d[12]),"+f"(d[13]),"+f"(d[14]),"+f"(d[15]),"+f"(d[16]),"+f"(d[17]),"+f"(d[18]),"+f"(d[19]),"+f"(d[20]),"+f"(d[21]),"+f"(d[22]),"+f"(d[23]),"+f"(d[24]),"+f"(d[25]),"+f"(d[26]),"+f"(d[27]),"+f"(d[28]),"+f"(d[29]),"+f"(d[30]),"+f"(d[31]),"+f"(d[32]),"+f"(d[33]),"+f"(d[34]),"+f"(d[35]) : "l"(da),"l"(db),"r"(sc));
}
template <int SC> __device__ __forceinline__ void wl_rs_n128_t1(float* d, const uint32_t* a, uint64_t e) {
  if (SC) asm volatile("wgmma.mma_async.sync.aligned.m64n128k16.f32.bf16.bf16 {%0,%1,%2,%3,%4,%5,%6,%7,%8,%9,%10,%11,%12,%13,%14,%15,%16,%17,%18,%19,%20,%21,%22,%23,%24,%25,%26,%27,%28,%29,%30,%31,%32,%33,%34,%35,%36,%37,%38,%39,%40,%41,%42,%43,%44,%45,%46,%47,%48,%49,%50,%51,%52,%53,%54,%55,%56,%57,%58,%59,%60,%61,%62,%63}, {%64,%65,%66,%67}, %68, 1,1,1,1;"
  : "+f"(d[0]),"+f"(d[1]),"+f"(d[2]),"+f"(d[3]),"+f"(d[4]),"+f"(d[5]),"+f"(d[6]),"+f"(d[7]),"+f"(d[8]),"+f"(d[9]),"+f"(d[10]),"+f"(d[11]),"+f"(d[12]),"+f"(d[13]),"+f"(d[14]),"+f"(d[15]),"+f"(d[16]),"+f"(d[17]),"+f"(d[18]),"+f"(d[19]),"+f"(d[20]),"+f"(d[21]),"+f"(d[22]),"+f"(d[23]),"+f"(d[24]),"+f"(d[25]),"+f"(d[26]),"+f"(d[27]),"+f"(d[28]),"+f"(d[29]),"+f"(d[30]),"+f"(d[31]),"+f"(d[32]),"+f"(d[33]),"+f"(d[34]),"+f"(d[35]),"+f"(d[36]),"+f"(d[37]),"+f"(d[38]),"+f"(d[39]),"+f"(d[40]),"+f"(d[41]),"+f"(d[42]),"+f"(d[43]),"+f"(d[44]),"+f"(d[45]),"+f"(d[46]),"+f"(d[47]),"+f"(d[48]),"+f"(d[49]),"+f"(d[50]),"+f"(d[51]),"+f"(d[52]),"+f"(d[53]),"+f"(d[54]),"+f"(d[55]),"+f"(d[56]),"+f"(d[57]),"+f"(d[58]),"+f"(d[59]),"+f"(d[60]),"+f"(d[61]),"+f"(d[62]),"+f"(d[63]) : "r"(a[0]),"r"(a[1]),"r"(a[2]),"r"(a[3]),"l"(e));
  else asm volatile("wgmma.mma_async.sync.aligned.m64n128k16.f32.bf16.bf16 {%0,%1,%2,%3,%4,%5,%6,%7,%8,%9,%10,%11,%12,%13,%14,%15,%16,%17,%18,%19,%20,%21,%22,%23,%24,%25,%26,%27,%28,%29,%30,%31,%32,%33,%34,%35,%36,%37,%38,%39,%40,%41,%42,%43,%44,%45,%46,%47,%48,%49,%50,%51,%52,%53,%54,%55,%56,%57,%58,%59,%60,%61,%62,%63}, {%64,%65,%66,%67}, %68, 0,1,1,1;"
  : "=f"(d[0]),"=f"(d[1]),"=f"(d[2]),"=f"(d[3]),"=f"(d[4]),"=f"(d[5]),"=f"(d[6]),"=f"(d[7]),"=f"(d[8]),"=f"(d[9]),"=f"(d[10]),"=f"(d[11]),"=f"(d[12]),"=f"(d[13]),"=f"(d[14]),"=f"(d[15]),"=f"(d[16]),"=f"(d[17]),"=f"(d[18]),"=f"(d[19]),"=f"(d[20]),"=f"(d[21]),"=f"(d[22]),"=f"(d[23]),"=f"(d[24]),"=f"(d[25]),"=f"(d[26]),"=f"(d[27]),"=f"(d[28]),"=f"(d[29]),"=f"(d[30]),"=f"(d[31]),"=f"(d[32]),"=f"(d[33]),"=f"(d[34]),"=f"(d[35]),"=f"(d[36]),"=f"(d[37]),"=f"(d[38]),"=f"(d[39]),"=f"(d[40]),"=f"(d[41]),"=f"(d[42]),"=f"(d[43]),"=f"(d[44]),"=f"(d[45]),"=f"(d[46]),"=f"(d[47]),"=f"(d[48]),"=f"(d[49]),"=f"(d[50]),"=f"(d[51]),"=f"(d[52]),"=f"(d[53]),"=f"(d[54]),"=f"(d[55]),"=f"(d[56]),"=f"(d[57]),"=f"(d[58]),"=f"(d[59]),"=f"(d[60]),"=f"(d[61]),"=f"(d[62]),"=f"(d[63]) : "r"(a[0]),"r"(a[1]),"r"(a[2]),"r"(a[3]),"l"(e));
}
template <int SC> __device__ __forceinline__ void wl_rs_n24_t1(float* d, const uint32_t* a, uint64_t e) {
  if (SC) asm volatile("wgmma.mma_async.sync.aligned.m64n24k16.f32.bf16.bf16 {%0,%1,%2,%3,%4,%5,%6,%7,%8,%9,%10,%11}, {%12,%13,%14,%15}, %16, 1,1,1,1;"
  : "+f"(d[0]),"+f"(d[1]),"+f"(d[2]),"+f"(d[3]),"+f"(d[4]),"+f"(d[5]),"+f"(d[6]),"+f"(d[7]),"+f"(d[8]),"+f"(d[9]),"+f"(d[10]),"+f"(d[11]) : "r"(a[0]),"r"(a[1]),"r"(a[2]),"r"(a[3]),"l"(e));
  else asm volatile("wgmma.mma_async.sync.aligned.m64n24k16.f32.bf16.bf16 {%0,%1,%2,%3,%4,%5,%6,%7,%8,%9,%10,%11}, {%12,%13,%14,%15}, %16, 0,1,1,1;"
  : "=f"(d[0]),"=f"(d[1]),"=f"(d[2]),"=f"(d[3]),"=f"(d[4]),"=f"(d[5]),"=f"(d[6]),"=f"(d[7]),"=f"(d[8]),"=f"(d[9]),"=f"(d[10]),"=f"(d[11]) : "r"(a[0]),"r"(a[1]),"r"(a[2]),"r"(a[3]),"l"(e));
}
template <int SC> __device__ __forceinline__ void wl_rs_n64_t0(float* d, const uint32_t* a, uint64_t e) {
  if (SC) asm volatile("wgmma.mma_async.sync.aligned.m64n64k16.f32.bf16.bf16 {%0,%1,%2,%3,%4,%5,%6,%7,%8,%9,%10,%11,%12,%13,%14,%15,%16,%17,%18,%19,%20,%21,%22,%23,%24,%25,%26,%27,%28,%29,%30,%31}, {%32,%33,%34,%35}, %36, 1,1,1,0;"
  : "+f"(d[0]),"+f"(d[1]),"+f"(d[2]),"+f"(d[3]),"+f"(d[4]),"+f"(d[5]),"+f"(d[6]),"+f"(d[7]),"+f"(d[8]),"+f"(d[9]),"+f"(d[10]),"+f"(d[11]),"+f"(d[12]),"+f"(d[13]),"+f"(d[14]),"+f"(d[15]),"+f"(d[16]),"+f"(d[17]),"+f"(d[18]),"+f"(d[19]),"+f"(d[20]),"+f"(d[21]),"+f"(d[22]),"+f"(d[23]),"+f"(d[24]),"+f"(d[25]),"+f"(d[26]),"+f"(d[27]),"+f"(d[28]),"+f"(d[29]),"+f"(d[30]),"+f"(d[31]) : "r"(a[0]),"r"(a[1]),"r"(a[2]),"r"(a[3]),"l"(e));
  else asm volatile("wgmma.mma_async.sync.aligned.m64n64k16.f32.bf16.bf16 {%0,%1,%2,%3,%4,%5,%6,%7,%8,%9,%10,%11,%12,%13,%14,%15,%16,%17,%18,%19,%20,%21,%22,%23,%24,%25,%26,%27,%28,%29,%30,%31}, {%32,%33,%34,%35}, %36, 0,1,1,0;"
  : "=f"(d[0]),"=f"(d[1]),"=f"(d[2]),"=f"(d[3]),"=f"(d[4]),"=f"(d[5]),"=f"(d[6]),"=f"(d[7]),"=f"(d[8]),"=f"(d[9]),"=f"(d[10]),"=f"(d[11]),"=f"(d[12]),"=f"(d[13]),"=f"(d[14]),"=f"(d[15]),"=f"(d[16]),"=f"(d[17]),"=f"(d[18]),"=f"(d[19]),"=f"(d[20]),"=f"(d[21]),"=f"(d[22]),"=f"(d[23]),"=f"(d[24]),"=f"(d[25]),"=f"(d[26]),"=f"(d[27]),"=f"(d[28]),"=f"(d[29]),"=f"(d[30]),"=f"(d[31]) : "r"(a[0]),"r"(a[1]),"r"(a[2]),"r"(a[3]),"l"(e));
}
template <int SC> __device__ __forceinline__ void wl_rs_n64_t1(float* d, const uint32_t* a, uint64_t e) {
  if (SC) asm volatile("wgmma.mma_async.sync.aligned.m64n64k16.f32.bf16.bf16 {%0,%1,%2,%3,%4,%5,%6,%7,%8,%9,%10,%11,%12,%13,%14,%15,%16,%17,%18,%19,%20,%21,%22,%23,%24,%25,%26,%27,%28,%29,%30,%31}, {%32,%33,%34,%35}, %36, 1,1,1,1;"
  : "+f"(d[0]),"+f"(d[1]),"+f"(d[2]),"+f"(d[3]),"+f"(d[4]),"+f"(d[5]),"+f"(d[6]),"+f"(d[7]),"+f"(d[8]),"+f"(d[9]),"+f"(d[10]),"+f"(d[11]),"+f"(d[12]),"+f"(d[13]),"+f"(d[14]),"+f"(d[15]),"+f"(d[16]),"+f"(d[17]),"+f"(d[18]),"+f"(d[19]),"+f"(d[20]),"+f"(d[21]),"+f"(d[22]),"+f"(d[23]),"+f"(d[24]),"+f"(d[25]),"+f"(d[26]),"+f"(d[27]),"+f"(d[28]),"+f"(d[29]),"+f"(d[30]),"+f"(d[31]) : "r"(a[0]),"r"(a[1]),"r"(a[2]),"r"(a[3]),"l"(e));
  else asm volatile("wgmma.mma_async.sync.aligned.m64n64k16.f32.bf16.bf16 {%0,%1,%2,%3,%4,%5,%6,%7,%8,%9,%10,%11,%12,%13,%14,%15,%16,%17,%18,%19,%20,%21,%22,%23,%24,%25,%26,%27,%28,%29,%30,%31}, {%32,%33,%34,%35}, %36, 0,1,1,1;"
  : "=f"(d[0]),"=f"(d[1]),"=f"(d[2]),"=f"(d[3]),"=f"(d[4]),"=f"(d[5]),"=f"(d[6]),"=f"(d[7]),"=f"(d[8]),"=f"(d[9]),"=f"(d[10]),"=f"(d[11]),"=f"(d[12]),"=f"(d[13]),"=f"(d[14]),"=f"(d[15]),"=f"(d[16]),"=f"(d[17]),"=f"(d[18]),"=f"(d[19]),"=f"(d[20]),"=f"(d[21]),"=f"(d[22]),"=f"(d[23]),"=f"(d[24]),"=f"(d[25]),"=f"(d[26]),"=f"(d[27]),"=f"(d[28]),"=f"(d[29]),"=f"(d[30]),"=f"(d[31]) : "r"(a[0]),"r"(a[1]),"r"(a[2]),"r"(a[3]),"l"(e));
}
template <int SC> __device__ __forceinline__ void wl_rs_n88_t1(float* d, const uint32_t* a, uint64_t e) {
  if (SC) asm volatile("wgmma.mma_async.sync.aligned.m64n88k16.f32.bf16.bf16 {%0,%1,%2,%3,%4,%5,%6,%7,%8,%9,%10,%11,%12,%13,%14,%15,%16,%17,%18,%19,%20,%21,%22,%23,%24,%25,%26,%27,%28,%29,%30,%31,%32,%33,%34,%35,%36,%37,%38,%39,%40,%41,%42,%43}, {%44,%45,%46,%47}, %48, 1,1,1,1;"
  : "+f"(d[0]),"+f"(d[1]),"+f"(d[2]),"+f"(d[3]),"+f"(d[4]),"+f"(d[5]),"+f"(d[6]),"+f"(d[7]),"+f"(d[8]),"+f"(d[9]),"+f"(d[10]),"+f"(d[11]),"+f"(d[12]),"+f"(d[13]),"+f"(d[14]),"+f"(d[15]),"+f"(d[16]),"+f"(d[17]),"+f"(d[18]),"+f"(d[19]),"+f"(d[20]),"+f"(d[21]),"+f"(d[22]),"+f"(d[23]),"+f"(d[24]),"+f"(d[25]),"+f"(d[26]),"+f"(d[27]),"+f"(d[28]),"+f"(d[29]),"+f"(d[30]),"+f"(d[31]),"+f"(d[32]),"+f"(d[33]),"+f"(d[34]),"+f"(d[35]),"+f"(d[36]),"+f"(d[37]),"+f"(d[38]),"+f"(d[39]),"+f"(d[40]),"+f"(d[41]),"+f"(d[42]),"+f"(d[43]) : "r"(a[0]),"r"(a[1]),"r"(a[2]),"r"(a[3]),"l"(e));
  else asm volatile("wgmma.mma_async.sync.aligned.m64n88k16.f32.bf16.bf16 {%0,%1,%2,%3,%4,%5,%6,%7,%8,%9,%10,%11,%12,%13,%14,%15,%16,%17,%18,%19,%20,%21,%22,%23,%24,%25,%26,%27,%28,%29,%30,%31,%32,%33,%34,%35,%36,%37,%38,%39,%40,%41,%42,%43}, {%44,%45,%46,%47}, %48, 0,1,1,1;"
  : "=f"(d[0]),"=f"(d[1]),"=f"(d[2]),"=f"(d[3]),"=f"(d[4]),"=f"(d[5]),"=f"(d[6]),"=f"(d[7]),"=f"(d[8]),"=f"(d[9]),"=f"(d[10]),"=f"(d[11]),"=f"(d[12]),"=f"(d[13]),"=f"(d[14]),"=f"(d[15]),"=f"(d[16]),"=f"(d[17]),"=f"(d[18]),"=f"(d[19]),"=f"(d[20]),"=f"(d[21]),"=f"(d[22]),"=f"(d[23]),"=f"(d[24]),"=f"(d[25]),"=f"(d[26]),"=f"(d[27]),"=f"(d[28]),"=f"(d[29]),"=f"(d[30]),"=f"(d[31]),"=f"(d[32]),"=f"(d[33]),"=f"(d[34]),"=f"(d[35]),"=f"(d[36]),"=f"(d[37]),"=f"(d[38]),"=f"(d[39]),"=f"(d[40]),"=f"(d[41]),"=f"(d[42]),"=f"(d[43]) : "r"(a[0]),"r"(a[1]),"r"(a[2]),"r"(a[3]),"l"(e));
}

#define POLY_MASK 0xB5u
#define PFX 9
#define PACE3 330
#define PACE4 300
#define PACEB 400
#define XL -1
#define ALIAS 0
#define P4W 1
#define W1 0
#define PACE1 0
#define GU "unroll"
#define PACEW 800
#define WOL 0
#define PFD 0
#define QSCALE (0.23570226039551584f * 1.4426950408889634f)

#define NSTG 6
#define STG_BYTES 16384
#define R_BYTES (8 * 16384)
#define GEMM_SMEM (R_BYTES + NSTG * STG_BYTES + 3072)

__device__ __forceinline__ void load_a_chunk(uint32_t (*a)[4], uint32_t chunk_base, int row_in_tile, int lane) {
  const int r = row_in_tile + (lane & 7) + ((lane >> 3) & 1) * 8;
  const uint32_t rb = chunk_base + r * 128;
#pragma unroll
  for (int k = 0; k < 4; k++) ldsm4(a[k], rb + (((k * 2 + (lane >> 4)) ^ (r & 7)) << 4));
}

__device__ __forceinline__ void load_a_core(uint32_t (*a)[4], uint32_t chunk_base, int row_in_tile, int lane) {
  const uint32_t rb = chunk_base + (row_in_tile >> 6) * 8192 + ((row_in_tile & 63) + (lane & 15)) * 16 + (lane >> 4) * 1024;
#pragma unroll
  for (int k = 0; k < 4; k++) ldsm4(a[k], rb + k * 2048);
}

#define MMA_TILE(FN, ODD, pj) MMA_TILE_(FN, ODD, pj, )
#define REL(o) if (lane == 0) mbar_arrive(empty + (o))
#define MMA_TILE_(FN, ODD, pj, PRE)                                             \
  {                                                                             \
    uint32_t rb_ = (RING & 0x3FFFF) >> 4;                                                 \
    asm volatile("" : "+r"(rb_));                                               \
    const uint64_t db = mkdesc(0, 8192, 1024, 1) + (uint32_t)__shfl_sync(~0u, rb_, 0); \
    _Pragma("unroll") for (int s = 0; s < 9; s++) {                             \
      const int g_ = 1 + (ODD) * 9 + s, st_ = g_ % NSTG;                        \
      PRE;                                                                      \
      mbar_wait(full + st_ * 8, (pj) ^ ((g_ / NSTG) & 1));                      \
      WG_FENCE();                                                               \
      if (s == 0) FN<0>(acc, a[0], db + st_ * 1024); else FN<1>(acc, a[s * 4], db + st_ * 1024); \
      _Pragma("unroll") for (int k = 1; k < 4; k++) FN<1>(acc, a[s * 4 + k], db + st_ * 1024 + k * 128); \
      WG_COMMIT();                                                              \
      if (s > 0) { WG_WAIT(1); REL(((g_ - 1) % NSTG) * 8); } \
    }                                                                           \
    WG_WAIT(0);                                                                 \
    REL(((9 + (ODD) * 9) % NSTG) * 8);    \
  }

template <int NG, int G0>
__device__ __forceinline__ void qkv_stage(const float* acc, uint32_t stg, int rowl, int cq, int nb) {
  const float vs0 = ((POLY_MASK >> ((rowl >> 3) & 7)) & 1) ? 0.5f : 1.0f, vs1 = ((POLY_MASK >> (((rowl >> 3) + 1) & 7)) & 1) ? 0.5f : 1.0f;
  const uint32_t base = stg + (rowl >> 3) * 384 + (rowl & 7) * 16;
#pragma unroll
  for (int j = 0; j < 9; j++) {
    const int cc = j * 8 + cq * 2, slot = (cc * 3641) >> 16, d = cc - slot * 18;
    const uint32_t ad = base + slot * 6144 + (d >> 3) * 128 + (d & 7) * 2;
#pragma unroll
    for (int per = 0; per < 3; per++) {
      const int i = per * 9 + j - G0, type = (nb * 3 + per) >> 3;
      if (i < 0 || i >= NG) continue;
      const float sc0 = type == 0 ? QSCALE : (type == 1 ? vs0 : 1.0f), sc1 = type == 0 ? QSCALE : (type == 1 ? vs1 : 1.0f);
      asm volatile("st.shared.b32 [%0],%1;" ::"r"(ad + per * 24576), "r"(pack_bf16(acc[4 * i] * sc0, acc[4 * i + 1] * sc0)) : "memory");
      asm volatile("st.shared.b32 [%0],%1;" ::"r"(ad + per * 24576 + 384), "r"(pack_bf16(acc[4 * i + 2] * sc1, acc[4 * i + 3] * sc1)) : "memory");
    }
  }
}

__device__ __forceinline__ float silu_f(float v) { return rbf(__fdividef(v, 1.0f + fminf(__expf(-v), 1e37f))); }
__device__ __forceinline__ float silu_bf(__nv_bfloat16 c) { return silu_f(__bfloat162float(c)); }
__device__ __forceinline__ void fma8(float* acc, float sv, const uint4& w) {
  acc[0] += sv * bf_lo(w.x); acc[1] += sv * bf_hi(w.x); acc[2] += sv * bf_lo(w.y); acc[3] += sv * bf_hi(w.y);
  acc[4] += sv * bf_lo(w.z); acc[5] += sv * bf_hi(w.z); acc[6] += sv * bf_lo(w.w); acc[7] += sv * bf_hi(w.w);
}
__device__ __forceinline__ int tab_pos(int col, int shift) {
  return (((col >> 4) * 4 + ((col & 7) >> 1)) * 4 + ((col >> 3) & 1) * 2 + shift) * 2 + (col & 1);
}
__device__ __forceinline__ float knorm_row(uint32_t slot, int row) {
  const uint32_t ad = slot + (row >> 3) * 384 + (row & 7) * 16;
  const uint4 u = lds128(ad), v = lds128(ad + 128);
  uint32_t w;
  asm volatile("ld.shared.b32 %0,[%1];" : "=r"(w) : "r"(ad + 256) : "memory");
  float q = sq2(u.x) + sq2(u.y) + sq2(u.z) + sq2(u.w) + sq2(v.x) + sq2(v.y) + sq2(v.z) + sq2(v.w) + sq2(w);
  if ((POLY_MASK >> ((row >> 3) & 7)) & 1) q *= 4.0f;
  return q == q ? q : __int_as_float(0x7f800000);
}

__global__ void CL1 __launch_bounds__(384, 1) k1_kernel(const __grid_constant__ CUtensorMap mx, const __grid_constant__ CUtensorMap mw,
                                                    const __grid_constant__ CUtensorMap mm, const __nv_bfloat16* __restrict__ cvec,
                                                    const uint8_t* __restrict__ wqkv, const uint4* __restrict__ wo) {
  extern __shared__ __align__(1024) uint8_t smem_raw[];
  const uint32_t sb = s2u(smem_raw);
  const uint32_t R = sb, RING = sb + R_BYTES, BAR = RING + NSTG * STG_BYTES, TAB = BAR + 512;
  const uint32_t full = BAR, empty = BAR + 64, xfull = BAR + 128;
  const int tid = threadIdx.x, lane = tid & 31, warp = tid >> 5;
  const int mb = blockIdx.x >> 3, nb = blockIdx.x & 7;
  if (tid == 0) TS(1, 0);
  if (tid == 288) { prefetch_map(&mx); prefetch_map(&mw); }
  if (tid == 256) {
    if (sb & 1023) __trap();
    for (int i = 0; i < NSTG; i++) { mbar_init(full + i * 8, 1); mbar_init(empty + i * 8, 8); }
    for (int i = 0; i < 9; i++) mbar_init(xfull + i * 8, 1);
    if (MC & 1) { for (int i = 0; i < 8; i++) mbar_expect(xfull + i * 8, 16384); mbar_expect(full, 16384); }
    fence_bar_init();
    if (blockIdx.x < 72) {
      mbar_expect(xfull + 64, 18432);
      for (int i = 0; i < 3; i++) tma2d(RING + 4 * STG_BYTES + i * 6144, &mm, blockIdx.x * 16, i * 192, xfull + 64);
    }
  }
  if (MC & 1) pair_sync(); else __syncthreads();
  pdl_launch();
  if (MC & 1) {
    if (PACE1 && warp < 8) { const uint32_t t0 = clock(); while ((uint32_t)clock() - t0 < (uint32_t)((warp == 1 && !(nb & 1) ? 8 : warp) * PACE1)) {} }
    if (lane == 0 && warp < 8 && (warp & 1) == (nb & 1)) tma2d_mc(R + warp * 16384, &mx, warp * 64, mb * 128, xfull + warp * 8);
    if (lane == 0 && warp == 1 && !(nb & 1)) tma2d_mc(RING, &mx, 512, mb * 128, full);
  } else if (lane == 0) {
    if (warp < 8) { mbar_expect(xfull + warp * 8, 16384); tma2d(R + warp * 16384, &mx, warp * 64, mb * 128, xfull + warp * 8); }
    if (warp == 1) { mbar_expect(full, 16384); tma2d(RING, &mx, 512, mb * 128, full); }
  }
  __syncwarp();
#define W_FIRST() { asm volatile("cp.async.bulk.prefetch.L2.global [%0],%1;" ::"l"(wqkv + blockIdx.x * 15552), "r"(15552) : "memory"); \
      for (int st = 1; st < 4; st++) { \
        mbar_expect(full + st * 8, 16384); \
        tma2d(RING + st * STG_BYTES, &mw, nb * 216, st * 64 - 64, full + st * 8); \
        tma2d(RING + st * STG_BYTES + 8192, &mw, nb * 216 + 64, st * 64 - 64, full + st * 8); } }
  if (warp >= 8) {
    REG_DEC(24);
    const int pt = tid - 256;
    if (PFD < 0 && pt == 0) W_FIRST();
    if (blockIdx.x < 72) {
      float* sf = (float*)(smem_raw + R_BYTES + 4 * STG_BYTES + 18432);
      if (pt < 72) {
        const uint4 cv = __ldg((const uint4*)cvec + pt);
        const uint32_t cw[4] = {cv.x, cv.y, cv.z, cv.w};
#pragma unroll
        for (int i = 0; i < 4; i++) { sf[pt * 8 + 2 * i] = silu_f(bf_lo(cw[i])); sf[pt * 8 + 2 * i + 1] = silu_f(bf_hi(cw[i])); }
      }
      bar_sync(3, 128);
      mbar_wait(xfull + 64, 0);
      float acc[8] = {0, 0, 0, 0, 0, 0, 0, 0};
#pragma unroll 1
      for (int i = 0; i < 9; i++) fma8(acc, sf[(pt >> 1) + 64 * i], lds128(RING + 4 * STG_BYTES + i * 2048 + pt * 16));
#pragma unroll
      for (int j = 0; j < 8; j++)
#pragma unroll
        for (int o = 2; o < 32; o *= 2) acc[j] += __shfl_xor_sync(~0u, acc[j], o);
      if (lane < 2) {
#pragma unroll
        for (int j = 0; j < 8; j++) sf[DM + (warp - 8) * 16 + lane * 8 + j] = acc[j];
      }
      bar_sync(3, 128);
      if (pt < 16) {
        const float v = rbf(sf[DM + pt] + sf[DM + 16 + pt] + sf[DM + 32 + pt] + sf[DM + 48 + pt]);
        const int n = blockIdx.x * 16 + pt, shift = n < DM;
        const uint32_t word = pack_bf16(shift ? v : 1.0f + v, 1.0f);
        asm volatile("st.relaxed.gpu.global.u32 [%0],%1;" ::"l"((uint32_t*)g_ll + tab_pos(shift ? n : n - DM, shift)), "r"(word) : "memory");
      }
      fence_async_smem();
      __syncwarp();
      if (pt == 0) TS(0, 1);
    }
    if (warp == 8) {
      if (lane == 0) {
        int st = 4; uint32_t ph = 0;
        for (int it = 3; it < 18; it++) {
          const int t = it / 9, s = it - t * 9;
          mbar_wait(empty + st * 8, ph ^ 1);
          mbar_expect(full + st * 8, 16384);
          tma2d(RING + st * STG_BYTES, &mw, nb * 216 + t * 128, s * 64, full + st * 8);
          tma2d(RING + st * STG_BYTES + 8192, &mw, nb * 216 + t * 128 + 64, s * 64, full + st * 8);
          if (++st == NSTG) { st = 0; ph ^= 1; }
        }
      }
    } else {
      const int ht = tid - 288;
#define WO_TILE() _Pragma("unroll 2") for (int j = ht; j < 324; j += 96) {        \
        const int i = blockIdx.x * 324 + j, k = i / 72, n8 = i - k * 72; \
        g_wo[(n8 / 9) * 5184 + (k >> 3) * 72 + (n8 % 9) * 8 + (k & 7)] = __ldg(wo + i); }
      if (WOL == 0) { mbar_wait(full, 0); WO_TILE() }
      if (WOL == 2) { mbar_wait(full + 24, 0); WO_TILE() }
      bar_sync(1, 352);
      for (int i = ht; i < 12 * 128; i += 96) {
        const int slot = i >> 7, row = i & 127, type = (nb * 12 + slot) >> 5;
        uint32_t v = 0;
        if (type == 1) v = ((POLY_MASK >> ((row >> 3) & 7)) & 1) ? 0x43403F00u : 0x40253F80u;
        if (type == 2) v = 0x3F80u;
        const uint32_t ad = R + slot * 6144 + (row >> 3) * 384 + 256 + (row & 7) * 16;
        asm volatile("st.shared.b32 [%0],%1;" ::"r"(ad + 4), "r"(v) : "memory");
        asm volatile("st.shared.v2.b32 [%0],{%1,%1};" ::"r"(ad + 8), "r"(0) : "memory");
      }
      fence_async_smem();
      bar_sync(2, 352);
      if (ht == 0) {
        for (int s = 0; s < 7; s++) bulk_s2g(g_qkv + (size_t)(nb * 12 + s) * 98304 + mb * 6144, R + s * 6144, 6144);
        bulk_commit();
      }
      if (WOL == 1) { WO_TILE() }
      for (int s = warp - 9; s < 7; s += 3) {
        const int gs = nb * 12 + s;
        if ((gs >> 5) != 1) continue;
        float mx2 = 0;
#pragma unroll 1
        for (int row = lane; row < 128; row += 32) mx2 = fmaxf(mx2, knorm_row(R + s * 6144, row));
#pragma unroll
        for (int o = 16; o; o >>= 1) mx2 = fmaxf(mx2, __shfl_xor_sync(~0u, mx2, o));
        if (lane == 0) g_kmax[(gs & 31) * 16 + mb] = mx2;
      }
      if (ht == 0) bulk_wait0();
    }
  } else {
    REG_INC(240);
    TSS(0);
    const int rowl = warp * 16;
    uint4 s0, s1;
    {
      RowStat rs, rt;
      rs.init(); rt.init();
      uint32_t f[4][4];
#pragma unroll 1
      for (int c = 0; c < 9; c++) {
        mbar_wait(c < 8 ? xfull + c * 8 : full, 0);
        if (c == PFD && tid == 224) W_FIRST();
        __syncwarp();
        load_a_chunk(f, R + c * 16384, rowl, lane);
        rs.add(f[0]); rt.add(f[1]); rs.add(f[2]); rt.add(f[3]);
      }
      rs.merge(rt);
      rs.finish(lane, s0, s1);
    }
    TSS(1);
    if (tid < 144) {
      uint4 u, v;
      int n = 0;
      do {
        asm volatile("ld.relaxed.gpu.global.v4.u32 {%0,%1,%2,%3},[%4];" : "=r"(u.x), "=r"(u.y), "=r"(u.z), "=r"(u.w) : "l"(g_ll + tid * 2) : "memory");
        asm volatile("ld.relaxed.gpu.global.v4.u32 {%0,%1,%2,%3},[%4];" : "=r"(v.x), "=r"(v.y), "=r"(v.z), "=r"(v.w) : "l"(g_ll + tid * 2 + 1) : "memory");
        if (++n > 4000000) __trap();
      } while (((u.x & u.y & u.z & u.w & v.x & v.y & v.z & v.w) >> 16) != 0x3F80u);
      sts128(TAB + tid * 16, make_uint4(__byte_perm(u.x, u.y, 0x5410), __byte_perm(u.z, u.w, 0x5410), __byte_perm(v.x, v.y, 0x5410), __byte_perm(v.z, v.w, 0x5410)));
    }
    bar_sync(4, 256);
    TSS(2);
    uint32_t a[36][4];
    float acc[64];
    MMA_TILE_(wl_rs_n128_t1, 0, 0, if (s < 8) { LN_CHUNK(s, load_a_chunk) } if (s == 1) { LN_CHUNK(8, load_a_chunk) if (lane == 0) mbar_arrive(empty); } if (s == 5) bar_arrive(1, 352));
    TSS(3);
    bar_sync(4, 256);
    int t2 = threadIdx.x;
    asm volatile("" : "+r"(t2));
    qkv_stage<16, 0>(acc, R, (t2 >> 5) * 16 + ((t2 & 31) >> 2), t2 & 3, nb);
    fence_async_smem();
    bar_arrive(2, 352);
    TSS(4);
    MMA_TILE(wl_rs_n88_t1, 1, 0);
    asm volatile("" : "+r"(t2));
    qkv_stage<11, 16>(acc, R, (t2 >> 5) * 16 + ((t2 & 31) >> 2), t2 & 3, nb);
    fence_async_smem();
    bar_sync(4, 256);
    TSS(5);
    if (tid == 0) {
      for (int s = 7; s < 12; s++) bulk_s2g(g_qkv + (size_t)(nb * 12 + s) * 98304 + mb * 6144, R + s * 6144, 6144);
      bulk_commit();
    }
    if (warp >= 3 && ((nb * 12 + 4 + warp) >> 5) == 1) {
      float mx2 = 0;
#pragma unroll
      for (int i = 0; i < 4; i++) mx2 = fmaxf(mx2, knorm_row(R + (4 + warp) * 6144, lane + 32 * i));
#pragma unroll
      for (int o = 16; o; o >>= 1) mx2 = fmaxf(mx2, __shfl_xor_sync(~0u, mx2, o));
      if (lane == 0) g_kmax[((nb * 12 + 4 + warp) & 31) * 16 + mb] = mx2;
    }
    if (tid == 0) bulk_wait0();
    TSS(6);
    TSDUMP(1);
  }
}

#define ATT_SMEM (2 * 98304 + 1024 + 256)

__device__ __forceinline__ uint32_t exp2_pair_fma(float t0, float t1) {
  uint32_t y;
  asm("prmt.b32 %0,%1,%2,0x6521;" : "=r"(y) : "r"(__float_as_uint(t0)), "r"(__float_as_uint(t1)));
  return hfma2(y, y | 0x3F803F80u, y | 0x007F007Fu);
}

__device__ __forceinline__ void softmax_fast(const float* s, uint32_t* p) {
#pragma unroll
  for (int i = 0; i < 8; i++) {
    if ((POLY_MASK >> i) & 1) {
      p[2 * i] = exp2_pair_fma(s[4 * i], s[4 * i + 1]);
      p[2 * i + 1] = exp2_pair_fma(s[4 * i + 2], s[4 * i + 3]);
    } else {
      p[2 * i] = pack_bf16(ex2f(s[4 * i]), ex2f(s[4 * i + 1]));
      p[2 * i + 1] = pack_bf16(ex2f(s[4 * i + 2]), ex2f(s[4 * i + 3]));
    }
  }
}
#define QK_MMA(S, kd)                                                           \
  wl_rs_n64_t0<0>(S, q, (kd));                                                  \
  wl_rs_n64_t0<1>(S, q + 4, (kd) + 16 - (8ull << 16));
#define PV_MMA(P, vd)                                                           \
  _Pragma("unroll") for (int t = 0; t < 4; t++) wl_rs_n24_t1<1>(o, P + 4 * t, (vd) + t * 48);

__device__ __forceinline__ void att_store(const float* o, int row0, int head, int lane) {
  const int cq = lane & 3;
  const float l0 = __shfl_sync(~0u, o[8], (lane & ~3) | 1), l1 = __shfl_sync(~0u, o[10], (lane & ~3) | 1);
  const float i0 = rcp_fast(l0), i1 = rcp_fast(l1);
  const int col = head * 18 + cq * 2;
  uint32_t* og = (uint32_t*)(g_o + (row0 >> 6) * 73728 + (col >> 3) * 1024 + (row0 & 63) * 16 + (col & 7) * 2);
  og[0] = pack_bf16(o[0] * i0, o[1] * i0);
  og[256] = pack_bf16(o[4] * i0, o[5] * i0);
  og[32] = pack_bf16(o[2] * i1, o[3] * i1);
  og[256 + 32] = pack_bf16(o[6] * i1, o[7] * i1);
  if (cq == 0) {
    og[512] = pack_bf16(o[8] * i0, o[9] * i0);
    og[512 + 32] = pack_bf16(o[10] * i1, o[11] * i1);
  }
}

__global__ void __launch_bounds__(512, 1) k2_kernel(const uint8_t* __restrict__ xin, const uint8_t* __restrict__ wg_, const uint8_t* __restrict__ wu,
                                                    const uint8_t* __restrict__ wd, const __nv_bfloat16* __restrict__ cvec,
                                                    const __nv_bfloat16* __restrict__ wmod) {
  extern __shared__ __align__(1024) uint8_t smem_raw[];
  const uint32_t sb = (s2u(smem_raw) + 1023) & ~1023u;
  const uint32_t KS = sb, VS = sb + 98304, BAR = sb + 2 * 98304;
  const int tid = threadIdx.x, lane = tid & 31, warp = tid >> 5, wg = tid >> 7;
  if (blockIdx.x < 4) {
    float* sf = (float*)smem_raw;
    const int part = blockIdx.x + 2;
    for (int i = tid; i < DM; i += 512) sf[i] = silu_bf(cvec[i]);
    if (part == 2 && tid < 80) g_cnt[tid] = 0;
    __nanosleep(4000);
    __syncthreads();
    if (tid < 432) {
      const int cg = tid % 72, rg = tid / 72;
      const __nv_bfloat16* w = wmod + (size_t)rg * 96 * 3456 + part * DM + cg * 8;
      float acc[8] = {0, 0, 0, 0, 0, 0, 0, 0};
#pragma unroll 1
      for (int r = 0; r < 96; r += 12) {
        uint4 v[12];
#pragma unroll
        for (int i = 0; i < 12; i++) v[i] = __ldg((const uint4*)(w + (size_t)(r + i) * 3456));
#pragma unroll
        for (int i = 0; i < 12; i++) fma8(acc, sf[rg * 96 + r + i], v[i]);
      }
#pragma unroll
      for (int j = 0; j < 8; j++) sf[DM + rg * DM + cg * 8 + j] = acc[j];
    }
    __syncthreads();
    for (int col = tid; col < DM; col += 512) {
      float v = 0;
#pragma unroll
      for (int j = 1; j < 7; j++) v += sf[j * DM + col];
      v = rbf(v);
      if (part == 2) g_ga[col] = __float2bfloat16_rn(v);
      else if (part == 5) g_gb[col] = __float2bfloat16_rn(v);
      else ((__nv_bfloat16*)g_tab2)[tab_pos(col, part == 3)] = __float2bfloat16_rn(0.5f * (part == 3 ? v : rbf(1.0f + v)));
    }
    pdl_wait();
    if (part == 2 && tid < 288) g_ll[tid] = make_uint4(0, 0, 0, 0);
    if (tid == 0) TS(0, 0);
    return;
  }
  const int bid = blockIdx.x - 4, head = bid >> 2, qb = bid & 3;
  if (tid == 0) {
    TS(2, 0);
    for (int i = 0; i < 16; i++) mbar_init(BAR + i * 8, 1);
    fence_bar_init();
  }
  __syncthreads();
  const int g = lane >> 2, cq = lane & 3;
  const int row0 = qb * 512 + wg * 128 + (warp & 3) * 16 + g;
  const uint8_t* qg = g_qkv + (size_t)head * 98304 + (row0 >> 3) * 384 + (row0 & 7) * 16 + cq * 4;
  pdl_wait();
  pdl_launch();
  if (tid == 0) TS(2, 1);
  const uint8_t* kg = g_qkv + (size_t)(32 + head) * 98304;
#define KV_LOAD(c) { mbar_expect(BAR + (c) * 8, 12288); bulk_g2s(KS + (c) * 6144, kg + (c) * 6144, 6144, BAR + (c) * 8); \
                     bulk_g2s(VS + (c) * 6144, kg + 32 * 98304 + (c) * 6144, 6144, BAR + (c) * 8); }
  if (lane == 0 && warp < 2) KV_LOAD(warp);
  __syncwarp();
  uint32_t q[8], q2[6];
  float kmax2 = __ldcg(g_kmax + head * 16 + (lane & 15));
#pragma unroll
  for (int i = 0; i < 6; i++) {
    q[i] = __ldcg((const uint32_t*)(qg + (i & 1) * 384 + (i >> 1) * 128));
    q2[i] = __ldcg((const uint32_t*)(qg + 3072 + (i & 1) * 384 + (i >> 1) * 128));
  }
  q[6] = __ldcg((const uint32_t*)(qg + 256 + 12 - cq * 4)); q[7] = __ldcg((const uint32_t*)(qg + 256 + 8 - cq * 4));
  const uint64_t dk = mkdesc(KS, 128, 384, 0), dv = mkdesc(VS, 384, 128, 0);
#pragma unroll
  for (int o = 8; o; o >>= 1) kmax2 = fmaxf(kmax2, __shfl_xor_sync(~0u, kmax2, o));
  float bd[4] = {sq2(q[0]) + sq2(q[2]) + sq2(q[4]), sq2(q[1]) + sq2(q[3]) + sq2(q[5]),
                 sq2(q2[0]) + sq2(q2[2]) + sq2(q2[4]), sq2(q2[1]) + sq2(q2[3]) + sq2(q2[5])};
  int ok = 1;
  if (tid == 0 && bd[0] + bd[3] + kmax2 != 1.2345f) TS(2, 5);
#pragma unroll
  for (int i = 0; i < 4; i++) {
    bd[i] += __shfl_xor_sync(~0u, bd[i], 1); bd[i] += __shfl_xor_sync(~0u, bd[i], 2);
    bd[i] = sqrt_fast(bd[i] * kmax2) * 1.01f + 1.0f;
    ok = ok && (bd[i] <= 62.0f);
  }
  {
    uint32_t all;
    asm volatile("{.reg .pred p,q; setp.ne.b32 p,%1,0; barrier.red.and.pred q,1,512,p; selp.u32 %0,1,0,q;}"
                 : "=r"(all) : "r"(ok) : "memory");
    ok = __all_sync(~0u, all);
  }
  float o[12];
#pragma unroll
  for (int i = 0; i < 12; i++) { o[i] = 0.f; asm volatile("" : "+f"(o[i])); }
  float s[32];
  uint32_t p[16];
  if (tid == 0) TS(2, 2);
  if (ok) {
    if (cq == 1) {
      q[4] = pack_bf16(-bd[0], 1.0f); q[5] = pack_bf16(-bd[1], 1.0f);
      q2[4] = pack_bf16(-bd[2], 1.0f); q2[5] = pack_bf16(-bd[3], 1.0f);
    }
    if (lane == 0 && (warp & 3) == wg && wg) KV_LOAD(1 + wg);
    __syncwarp();
    mbar_wait(BAR, 0);
    WG_FENCE();
    QK_MMA(s, dk);
    WG_COMMIT();
#pragma unroll 1
    for (int tile = 0; tile < 2; tile++) {
#pragma unroll 1
      for (int jj = 0; jj < 8; jj++) {
        const uint64_t kd = dk + (uint32_t)(jj * 768), vd = dv + (uint32_t)(jj * 768), kn = dk + (uint32_t)(((jj + 1) & 7) * 768);
        if (tile == 0) {
          if (lane == 0 && (warp == 9 || warp == 14) && 2 * jj + 3 + wg < 16) KV_LOAD(2 * jj + 3 + wg);
          if (lane == 0 && (warp == 3 || warp == 4 || warp == 7))
            asm volatile("cp.async.bulk.prefetch.L2.global [%0],%1;" ::"l"((warp == 4 ? wg_ : warp == 3 ? wu : wd) + (bid * 8 + jj) * 5184), "r"(5184) : "memory");
          __syncwarp();
          if (!W1) mbar_wait(BAR + jj * 16 + 8, 0);
          if (tid == 0) TS(2, 8 + jj);
        } else if (jj == PFX) {
          if (tid == 96) asm volatile("cp.async.bulk.prefetch.L2.global [%0],%1;" ::"l"(xin + bid * 18432), "r"(18432) : "memory");
          if (tid == 160) asm volatile("cp.async.bulk.prefetch.L2.global [%0],%1;" ::"l"(g_wo + bid * 324), "r"(5184) : "memory");
          __syncwarp();
        }
#pragma unroll
        for (int u = 0; u < 4; u++) {
          WG_WAIT(0);
          fence_regs<32>(s);
          softmax_fast(s, p);
          if (W1 && u == 1 && tile == 0) mbar_wait(BAR + jj * 16 + 8, 0);
          if (u == 3 && tile == 0) mbar_wait(BAR + ((jj * 16 + 16) & 127), 0);
          if (u == 3 && jj == 7) {
#pragma unroll
            for (int i = 0; i < 6; i++) q[i] = q2[i];
          }
          WG_FENCE();
          PV_MMA(p, vd + u * 192);
          QK_MMA(s, u < 3 ? kd + u * 192 + 192 : kn);
          WG_COMMIT();
        }
      }
      WG_WAIT(0);
      fence_regs<12>(o);
      att_store(o, row0 + tile * 64, head, lane);
#pragma unroll
      for (int i = 0; i < 12; i++) o[i] = 0.f;
      fence_regs<12>(o);
      if (tid == 0 && tile == 0) TS(2, 3);
    }
  } else {
    if (lane == 0 && warp >= 2) KV_LOAD(warp);
    __syncwarp();
#pragma unroll 1
    for (int tile = 0; tile < 2; tile++) {
      float m0 = -INFINITY, m1 = -INFINITY;
#pragma unroll 1
      for (int j = 0; j < 32; j++) {
        mbar_wait(BAR + (j >> 1) * 8, 0);
        WG_FENCE();
        QK_MMA(s, dk + (uint32_t)(j * 192));
        WG_COMMIT();
        WG_WAIT(0);
        fence_regs<32>(s);
#pragma unroll
        for (int i = 0; i < 32; i++) if ((POLY_MASK >> (i >> 2)) & 1) s[i] *= 2.0f;
        float x0 = m0, x1 = m1;
#pragma unroll
        for (int i = 0; i < 8; i++) {
          x0 = fmaxf(x0, fmaxf(s[4 * i], s[4 * i + 1]));
          x1 = fmaxf(x1, fmaxf(s[4 * i + 2], s[4 * i + 3]));
        }
        x0 = fmaxf(x0, __shfl_xor_sync(~0u, x0, 1)); x0 = fmaxf(x0, __shfl_xor_sync(~0u, x0, 2));
        x1 = fmaxf(x1, __shfl_xor_sync(~0u, x1, 1)); x1 = fmaxf(x1, __shfl_xor_sync(~0u, x1, 2));
        const float c0 = ex2f(m0 - x0), c1 = ex2f(m1 - x1);
        m0 = x0; m1 = x1;
#pragma unroll
        for (int i = 0; i < 3; i++) { o[4 * i] *= c0; o[4 * i + 1] *= c0; o[4 * i + 2] *= c1; o[4 * i + 3] *= c1; }
#pragma unroll
        for (int i = 0; i < 8; i++) {
          p[2 * i] = pack_bf16(ex2f(s[4 * i] - x0), ex2f(s[4 * i + 1] - x0));
          p[2 * i + 1] = pack_bf16(ex2f(s[4 * i + 2] - x1), ex2f(s[4 * i + 3] - x1));
        }
        WG_FENCE();
        PV_MMA(p, dv + (uint32_t)(j * 192));
        WG_COMMIT();
        WG_WAIT(0);
        fence_regs<12>(o);
      }
      att_store(o, row0 + tile * 64, head, lane);
#pragma unroll
      for (int i = 0; i < 12; i++) o[i] = 0.f;
#pragma unroll
      for (int i = 0; i < 6; i++) q[i] = q2[i];
    }
  }
  if (tid == 0) TS(2, 4);
}

#define K3_SMEM (9 * 16384 + 9 * 9216 + 256)
__device__ __forceinline__ uint32_t res_pair(uint32_t x, uint32_t g, float s0, float s1) { return hadd2(x, hmul2(g, pack_bf16(s0, s1))); }
__global__ void CL3 __launch_bounds__(320, 1) k3_kernel(const __nv_bfloat16* __restrict__ x) {
  extern __shared__ __align__(1024) uint8_t smem_raw[];
  const uint32_t sb = s2u(smem_raw);
  const uint32_t A = sb, B = sb + 9 * 16384, BAR = B + 9 * 9216;
  const int tid = threadIdx.x, lane = tid & 31, warp = tid >> 5;
  const int mb = blockIdx.x >> 3, nb = blockIdx.x & 7;
  if (tid == 0) {
    TS(3, 0);
    if (sb & 1023) __trap();
    for (int i = 0; i < 9; i++) { mbar_init(BAR + i * 8, 1); mbar_expect(BAR + i * 8, 9216 + 16384 + (i == 8 ? 144 : 0)); }
    fence_bar_init();
  }
  if (MC & 2) pair_sync(); else __syncthreads();
  if (warp >= 8) {
    if (tid == 256) {
      const uint32_t t0 = clock();
      for (int s = 0; s < 9; s++) {
        while ((uint32_t)clock() - t0 < (uint32_t)(s * PACEB)) {}
        bulk_g2s(B + s * 9216, g_wo + nb * 5184 + s * 576, 9216, BAR + s * 8);
      }
      TS(0, 2);
    }
    if (tid == 288) {
      pdl_wait();
      pdl_launch();
      TS(0, 3);
      const uint32_t t0 = clock();
      for (int c = nb & 1; c < 18; c += 2) {
        while ((uint32_t)clock() - t0 < (uint32_t)((c >> 1) * PACE3)) {}
        bulk_g2s_mc(A + c * 8192, g_o + (mb * 2 + (c & 1)) * 73728 + (c >> 1) * 8192, 8192, BAR + (c >> 1) * 8);
      }
      bulk_g2s(BAR + 96, g_ga + nb * 72, 144, BAR + 64);
    }
  } else {
    const int g = lane >> 2, cq = lane & 3, wg = warp >> 2;
    const int row = mb * 128 + warp * 16 + g, col = nb * 72 + cq * 2;
    uint32_t xv[20], ga[9];
#define X_LOAD() _Pragma("unroll") for (int i = 0; i < 9; i++) { \
      xv[2 * i] = __ldg((const uint32_t*)(x + (size_t)row * DM + col + 8 * i)); \
      xv[2 * i + 1] = __ldg((const uint32_t*)(x + (size_t)(row + 8) * DM + col + 8 * i)); }
    if (XL < 0) { X_LOAD() }
    float acc[36];
    const uint64_t da = mkdesc(A + wg * 8192, 1024, 128, 0), db = mkdesc(B, 1152, 128, 0);
#pragma unroll 1
    for (int s = 0; s < 9; s++) {
      mbar_wait(BAR + s * 8, 0);
      if (tid == 0) TS(0, 4 + s);
      WG_FENCE();
#pragma unroll
      for (int k = 0; k < 4; k++) wg_ss_n72_t1(acc, da + s * 1024 + k * 128, db + s * 576 + k * 144, s | k);
      WG_COMMIT();
      if (s == XL) { X_LOAD() }
    }
    pdl_launch();
#pragma unroll
    for (int i = 0; i < 9; i++) asm volatile("ld.shared.b32 %0,[%1];" : "=r"(ga[i]) : "r"(BAR + 96 + cq * 4 + i * 16));
    WG_WAIT(0);
    fence_regs<36>(acc);
    if (tid == 0) TS(3, 2);
    bar_sync(1, 256);
    const uint32_t stg = A + wg * 9216 + ((warp & 3) * 16 + g) * 16 + cq * 4;
#pragma unroll
    for (int i = 0; i < 9; i++) {
      xv[2 * i] = res_pair(xv[2 * i], ga[i], acc[4 * i], acc[4 * i + 1]);
      xv[2 * i + 1] = res_pair(xv[2 * i + 1], ga[i], acc[4 * i + 2], acc[4 * i + 3]);
      asm volatile("st.shared.b32 [%0],%1;" ::"r"(stg + i * 1024), "r"(xv[2 * i]) : "memory");
      asm volatile("st.shared.b32 [%0],%1;" ::"r"(stg + i * 1024 + 128), "r"(xv[2 * i + 1]) : "memory");
    }
    fence_async_smem();
    bar_sync(2 + wg, 128);
    if ((tid & 127) == 0) {
      bulk_s2g(g_x1 + (mb * 2 + wg) * 73728 + nb * 9216, A + wg * 9216, 9216);
      bulk_commit();
    }
    xv[18] = xv[19] = 0;
    RowStat rs;
    rs.init();
#pragma unroll
    for (int i = 0; i < 5; i++) rs.add(&xv[4 * i]);
    if (cq == (g >> 1)) {
      g_stat2[row * 8 + nb] = make_float2(rs.s[0], (g & 1) ? rs.q0[1] : rs.q0[0]);
      g_stat2[(row + 8) * 8 + nb] = make_float2(rs.s[2], (g & 1) ? rs.q1[3] : rs.q1[2]);
    }
    if ((tid & 127) == 0) bulk_wait0();
    if (tid == 0) TS(3, 3);
  }
}

__device__ __forceinline__ uint4 ln2_consts(int row, int cq) {
  const float4 p = __ldcg((const float4*)(g_stat2 + row * 8 + cq * 2));
  float s = p.x + p.z, q = p.y + p.w;
  s += __shfl_xor_sync(~0u, s, 1); q += __shfl_xor_sync(~0u, q, 1);
  s += __shfl_xor_sync(~0u, s, 2); q += __shfl_xor_sync(~0u, q, 2);
  const float mean = s * (1.0f / DM);
  return ln_consts(mean, fmaxf(q * (1.0f / DM) - mean * mean, 0.f));
}
__device__ __forceinline__ uint8_t* part_ptr(int f, int mb, int p) {
  const int i = f * 16 + mb;
  if (ALIAS && p == 4) return g_o + i * 16384;
  if (ALIAS && (p >> 1) == ALIAS - 1) return g_qkv + (size_t)(i * 2 + (p & 1)) * 32768;
  return g_part + (size_t)(i * 5 + p) * 32768;
}
__device__ __forceinline__ uint32_t glu_pair(float g0, float g1, float u0, float u1) {
  return pack_bf16(fmaf(tanhf_fast(g0), u0, u0), fmaf(tanhf_fast(g1), u1, u1));
}
template <int NG>
__device__ __forceinline__ void stage_part(const float* acc, uint32_t stg, int lane) {
  const int r = (lane & 7) + ((lane >> 3) & 1) * 8;
#pragma unroll
  for (int i = 0; i < NG; i += 2) {
    const int ch = i + (lane >> 4);
    stsm4(stg + r * (NG * 16) + ((ch ^ (r & 7)) << 4), pack_bf16(acc[4 * i], acc[4 * i + 1]), pack_bf16(acc[4 * i + 2], acc[4 * i + 3]),
          pack_bf16(acc[4 * i + 4], acc[4 * i + 5]), pack_bf16(acc[4 * i + 6], acc[4 * i + 7]));
  }
}
__global__ void CL4 __launch_bounds__(384, 1) k4_kernel(const __grid_constant__ CUtensorMap mg,
                                                    const __grid_constant__ CUtensorMap mu, const __grid_constant__ CUtensorMap md,
                                                    __nv_bfloat16* __restrict__ out) {
  extern __shared__ __align__(1024) uint8_t smem_raw[];
  const uint32_t sb = s2u(smem_raw);
  const uint32_t R = sb, RING = sb + R_BYTES, BAR = RING + NSTG * STG_BYTES, TAB = BAR + 512;
  const uint32_t full = BAR, empty = BAR + 64, xfull = BAR + 128, gfull = BAR + 272, sfull = BAR + 320;
  const int tid = threadIdx.x, lane = tid & 31, warp = tid >> 5;
  const int rank = blockIdx.x & 1, mb = MW ? (blockIdx.x >> 4) * 2 + rank : blockIdx.x >> 3, fb = MW ? (blockIdx.x >> 1) & 7 : blockIdx.x & 7;
  if (tid == 0) {
    TS(4, 0);
    if (sb & 1023) __trap();
    for (int i = 0; i < 10; i++) mbar_init(sfull + i * 8, 4);
    for (int i = 0; i < NSTG; i++) { mbar_init(full + i * 8, 1); mbar_init(empty + i * 8, MW ? 16 : 8); }
    for (int i = 0; i < 9; i++) mbar_init(xfull + i * 8, 1);
    for (int i = 0; i < 5; i++) mbar_init(gfull + i * 8, 1);
    mbar_arrive(full);
    for (int i = 0; i < 9; i++) mbar_expect(xfull + i * 8, 16384);
    fence_bar_init();
  }
  if ((MC & 4) || MW) pair_sync(); else __syncthreads();
  if (warp >= 8) {
    REG_DEC(24);
    if (lane == 0) {
      if (warp == 8) {
        int st = 1; uint32_t ph = 0;
        const uint32_t t0 = clock();
        for (int it = 0; it < 126; it++) {
          if (it < 5) while ((uint32_t)clock() - t0 < (uint32_t)(it * PACEW)) {}
          const int t = it / 9, s = it - t * 9;
          const uint32_t dst = RING + st * STG_BYTES, fb_ = full + st * 8;
          mbar_wait(empty + st * 8, ph ^ 1);
          if (MW) {
            mbar_expect(fb_, t < 13 ? 16384 : 8192);
            if (t < 9) tma2d_mc(dst + rank * 8192, rank ? &mu : &mg, fb * 576 + t * 64, s * 64, fb_);
            else if (t < 13) tma2d_mc(dst + rank * 8192, &md, (t - 9) * 128 + rank * 64, fb * 576 + s * 64, fb_);
            else if ((s & 1) == rank) tma2d_mc(dst, &md, 512, fb * 576 + s * 64, fb_);
          } else if (t < 9) {
            mbar_expect(fb_, 16384);
            tma2d(dst, &mg, fb * 576 + t * 64, s * 64, fb_);
            tma2d(dst + 8192, &mu, fb * 576 + t * 64, s * 64, fb_);
          } else {
            mbar_expect(fb_, t < 13 ? 16384 : 8192);
            tma2d(dst, &md, (t - 9) * 128, fb * 576 + s * 64, fb_);
            if (t < 13) tma2d(dst + 8192, &md, (t - 9) * 128 + 64, fb * 576 + s * 64, fb_);
          }
          if (++st == NSTG) { st = 0; ph ^= 1; }
        }
      }
#define GATHER(p)                                                               \
  { unsigned int v; int n = 0;                                                  \
    do { asm volatile("ld.acquire.gpu.global.u32 %0,[%1];" : "=r"(v) : "l"(g_cnt + mb * 5 + (p)) : "memory"); } while (v < 8 && ++n < 20000000); \
    if (v < 8) __trap();                                                        \
    asm volatile("fence.proxy.async.global;" ::: "memory");                     \
    TS(3, 9 + (p));                                                             \
    const uint32_t sz = (p) < 4 ? 4096 : 2048;                                  \
    mbar_expect(gfull + (p) * 8, sz * 8);                                       \
    _Pragma(GU) for (int f = 0; f < 8; f++)                             \
      bulk_g2s((p) < 4 ? R + (p) * 32768 + f * 4096 : RING + (2 + (f >> 2)) * STG_BYTES + 8192 + (f & 3) * 2048, \
               part_ptr(f, mb, p) + fb * sz, sz, gfull + (p) * 8); }
      if (warp < 11) {
#pragma unroll 1
        for (int p = warp == 8 ? 4 : warp - 9; p < 5 - (warp != 8); p += 2) {
          uint8_t* dst = part_ptr(fb, mb, p);
#pragma unroll 1
          for (int wg = 0; wg < 2; wg++) {
            mbar_wait(sfull + (p * 2 + wg) * 8, 0);
            if (p < 4) {
              bulk_s2g(dst + wg * 16384, R + p * 32768 + wg * 8192, 8192);
              bulk_s2g(dst + wg * 16384 + 8192, R + p * 32768 + 16384 + wg * 8192, 8192);
            } else {
              bulk_s2g(dst + wg * 8192, RING + wg * STG_BYTES + 8192, 8192);
            }
          }
          bulk_commit();
          if (p >= 3) TS(3, 11 + p);
          bulk_wait0();
          TS(3, 4 + p);
          asm volatile("fence.proxy.async.global;" ::: "memory");
          asm volatile("red.release.gpu.global.add.u32 [%0],1;" ::"l"(g_cnt + mb * 5 + p) : "memory");
          GATHER(p);
        }
      } else {
        pdl_wait();
        const uint32_t t0 = clock();
        for (int c = 0; c < 9; c++) {
          while ((uint32_t)clock() - t0 < (uint32_t)(c * PACE4)) {}
          const int k = c < 2 ? c : (c == 2 ? 8 : c - 1);
          if (MC & 4) { bulk_g2s_mc(R + k * 16384 + (fb & 1) * 8192, g_x1 + (mb * 2 + (fb & 1)) * 73728 + k * 8192, 8192, xfull + c * 8); continue; }
          bulk_g2s(R + k * 16384, g_x1 + mb * 2 * 73728 + k * 8192, 8192, xfull + c * 8);
          bulk_g2s(R + k * 16384 + 8192, g_x1 + (mb * 2 + 1) * 73728 + k * 8192, 8192, xfull + c * 8);
        }
      }
    }
    if (MW) { __syncwarp(); pair_sync(); }
  } else {
    REG_INC(240);
    [[maybe_unused]] uint32_t emp;
    asm("mapa.shared::cluster.u32 %0,%1,%2;" : "=r"(emp) : "r"(empty), "r"(lane & 1));
    uint32_t a[36][4];
    const int wg = warp >> 2, wl = warp & 3;
    if (tid < 144) sts128(TAB + tid * 16, g_tab2[tid]);
    bar_sync(1, 256);
    pdl_wait();
    TSS(0);
    float acc[64];
    const uint32_t hsp = R + wg * 8192 + (wl * 16 + (lane & 15)) * 16 + (lane >> 4) * 1024;
#define GLU_SPILL(t)                                                            \
  _Pragma("unroll") for (int j = 0; j < 4; j++) {                               \
    uint32_t h[4];                                                              \
    _Pragma("unroll") for (int e = 0; e < 4; e++)                               \
      h[e] = glu_pair(acc[8 * j + 2 * e], acc[8 * j + 2 * e + 1], acc[32 + 8 * j + 2 * e], acc[32 + 8 * j + 2 * e + 1]); \
    asm volatile("st.shared.v4.b32 [%0],{%1,%2,%3,%4};" ::"r"(hsp + (t) * 16384 + j * 2048), "r"(h[0]), "r"(h[1]), "r"(h[2]), "r"(h[3]) : "memory"); \
  }
    {
      const uint4 s0 = ln2_consts(mb * 128 + warp * 16 + (lane >> 2), lane & 3), s1 = ln2_consts(mb * 128 + warp * 16 + (lane >> 2) + 8, lane & 3);
      TSS(1);
      MMA_TILE_(wl_rs_n128_t1, 0, 0,
                if (s < 8) { mbar_wait(xfull + (s + (s > 1)) * 8, 0); LN_CHUNK(s, load_a_core) }
                if (s == 1) { mbar_wait(xfull + 16, 0); LN_CHUNK(8, load_a_core) REL(0); });
    }
    GLU_SPILL(0);
#pragma unroll 1
    for (int t = 0; t < 3; t++) {
      MMA_TILE(wl_rs_n128_t1, 1, t & 1);
      GLU_SPILL(2 * t + 1);
      MMA_TILE(wl_rs_n128_t1, 0, (t & 1) ^ 1);
      GLU_SPILL(2 * t + 2);
    }
    MMA_TILE(wl_rs_n128_t1, 1, 1);
    GLU_SPILL(7);
    MMA_TILE(wl_rs_n128_t1, 0, 0);
#pragma unroll
    for (int j = 0; j < 4; j++)
#pragma unroll
      for (int e = 0; e < 4; e++)
        a[32 + j][e] = glu_pair(acc[8 * j + 2 * e], acc[8 * j + 2 * e + 1], acc[32 + 8 * j + 2 * e], acc[32 + 8 * j + 2 * e + 1]);
#pragma unroll
    for (int k = 0; k < 32; k++)
      asm volatile("ld.shared.v4.b32 {%0,%1,%2,%3},[%4];" : "=r"(a[k][0]), "=r"(a[k][1]), "=r"(a[k][2]), "=r"(a[k][3]) : "r"(hsp + (k >> 2) * 16384 + (k & 3) * 2048) : "memory");
    TSS(2);
    const uint32_t stg = R + (wl >> 1) * 16384 + wg * 8192 + (wl & 1) * 4096;
#define PART_OUT(p)                                                             \
  stage_part<16>(acc, stg + (p) * 32768, lane);                                 \
  fence_async_smem();                                                           \
  __syncwarp();                                                                 \
  if (lane == 0) mbar_arrive(sfull + ((p) * 2 + wg) * 8);
    bar_sync(2 + wg, 128);
#pragma unroll 1
    for (int p = 0; p < 2; p++) {
      MMA_TILE(wl_rs_n128_t1, 1, p);
      PART_OUT(2 * p);
      MMA_TILE(wl_rs_n128_t1, 0, p ^ 1);
      PART_OUT(2 * p + 1);
    }
    MMA_TILE(wl_rs_n64_t1, 1, 0);
    if (MW) { __syncwarp(); asm volatile("barrier.cluster.arrive.relaxed.aligned;" ::: "memory"); }
    stage_part<8>(acc, RING + wg * STG_BYTES + 8192 + wl * 2048, lane);
    fence_async_smem();
    __syncwarp();
    if (lane == 0) mbar_arrive(sfull + (8 + wg) * 8);
    TSS(3);
    const int rl = tid >> 4, ch = tid & 15;
    const size_t off = (size_t)(mb * 128 + fb * 16 + rl) * DM + ch * 8;
    uint4 xv[5], gv[5];
#pragma unroll
    for (int p = 0; p < 5; p++)
      if (p < 4 || ch < 8) { xv[p] = __ldcg((const uint4*)(g_x1 + (mb * 2 + (fb >> 2)) * 73728 + (p * 16 + ch) * 1024 + ((fb & 3) * 16 + rl) * 16)); gv[p] = __ldcg((const uint4*)(g_gb + p * 128 + ch * 8)); }
#pragma unroll
    for (int p = 0; p < 5; p++) {
      if (p == 4 && ch >= 8) break;
      mbar_wait(gfull + p * 8, 0);
      float r8[8] = {0, 0, 0, 0, 0, 0, 0, 0};
#pragma unroll
      for (int f = 0; f < 8; f++) {
        const uint4 v = lds128((p < 4 ? R + p * 32768 + f * 4096 + rl * 256 : RING + (2 + (f >> 2)) * STG_BYTES + 8192 + (f & 3) * 2048 + rl * 128) +
                               ((ch ^ (rl & 7)) << 4));
        r8[0] += bf_lo(v.x); r8[1] += bf_hi(v.x); r8[2] += bf_lo(v.y); r8[3] += bf_hi(v.y);
        r8[4] += bf_lo(v.z); r8[5] += bf_hi(v.z); r8[6] += bf_lo(v.w); r8[7] += bf_hi(v.w);
      }
      uint4 r;
      r.x = res_pair(xv[p].x, gv[p].x, r8[0], r8[1]);
      r.y = res_pair(xv[p].y, gv[p].y, r8[2], r8[3]);
      r.z = res_pair(xv[p].z, gv[p].z, r8[4], r8[5]);
      r.w = res_pair(xv[p].w, gv[p].w, r8[6], r8[7]);
      *(uint4*)(out + off + p * 128) = r;
      if (p >= 2) TSS(2 + p);
    }
    if (MW) { __syncwarp(); asm volatile("barrier.cluster.wait.aligned;" ::: "memory"); }
    TSDUMP(4);
  }
}

typedef CUresult (*EncodeFn)(CUtensorMap*, CUtensorMapDataType, cuuint32_t, void*, const cuuint64_t*, const cuuint64_t*,
                             const cuuint32_t*, const cuuint32_t*, CUtensorMapInterleave, CUtensorMapSwizzle,
                             CUtensorMapL2promotion, CUtensorMapFloatOOBfill);
static void make_map(EncodeFn fn, CUtensorMap* m, const void* p, int rows, int cols, int box_rows, int box_cols = 64) {
  cuuint64_t dims[2] = {(cuuint64_t)cols, (cuuint64_t)rows};
  cuuint64_t strides[1] = {(cuuint64_t)cols * 2};
  cuuint32_t box[2] = {(cuuint32_t)box_cols, (cuuint32_t)box_rows};
  cuuint32_t es[2] = {1, 1};
  fn(m, CU_TENSOR_MAP_DATA_TYPE_BFLOAT16, 2, (void*)p, dims, strides, box, es, CU_TENSOR_MAP_INTERLEAVE_NONE,
     box_cols == 64 ? CU_TENSOR_MAP_SWIZZLE_128B : CU_TENSOR_MAP_SWIZZLE_NONE,
     box_cols == 64 ? CU_TENSOR_MAP_L2_PROMOTION_L2_256B : CU_TENSOR_MAP_L2_PROMOTION_NONE, CU_TENSOR_MAP_FLOAT_OOB_FILL_NONE);
}
template <typename... KA, typename... A>
static void launch(void (*k)(KA...), int grid, int block, int smem, bool pdl, A... args) {
  cudaLaunchConfig_t cfg = {};
  cfg.gridDim = dim3(grid); cfg.blockDim = dim3(block); cfg.dynamicSmemBytes = smem; cfg.stream = cudaStreamPerThread;
  cudaLaunchAttribute at;
  at.id = cudaLaunchAttributeProgrammaticStreamSerialization;
  at.val.programmaticStreamSerializationAllowed = 1;
  cfg.attrs = &at; cfg.numAttrs = pdl ? 1 : 0;
  cudaLaunchKernelEx(&cfg, k, KA(args)...);
}

extern "C" void kernel_launch(void* const* d_in, const int* in_sizes, int n_in, void* d_out, int out_size) {
  const __nv_bfloat16* x = (const __nv_bfloat16*)d_in[0];
  void* fnp = nullptr;
  cudaDriverEntryPointQueryResult qr;
  cudaGetDriverEntryPoint("cuTensorMapEncodeTiled", &fnp, cudaEnableDefault, &qr);
  EncodeFn fn = (EncodeFn)fnp;
  CUtensorMap mm, mx, mqkv, mg, mu, md;
  make_map(fn, &mm, d_in[8], DM, 6 * DM, 192, 16);
  make_map(fn, &mx, x, SEQ, DM, 128);
  make_map(fn, &mqkv, d_in[1], DM, 3 * DM, 64);
  make_map(fn, &mg, d_in[4], DM, FF, 64);
  make_map(fn, &mu, d_in[5], DM, FF, 64);
  make_map(fn, &md, d_in[6], FF, DM, 64);
  cudaFuncSetAttribute(k1_kernel, cudaFuncAttributeMaxDynamicSharedMemorySize, GEMM_SMEM);
  cudaFuncSetAttribute(k2_kernel, cudaFuncAttributeMaxDynamicSharedMemorySize, ATT_SMEM);
  cudaFuncSetAttribute(k3_kernel, cudaFuncAttributeMaxDynamicSharedMemorySize, K3_SMEM);
  cudaFuncSetAttribute(k4_kernel, cudaFuncAttributeMaxDynamicSharedMemorySize, GEMM_SMEM);
  launch(k1_kernel, 128, 384, GEMM_SMEM, false, mx, mqkv, mm, (const __nv_bfloat16*)d_in[7], (const uint8_t*)d_in[1], (const uint4*)d_in[2]);
  launch(k2_kernel, 132, 512, ATT_SMEM, true, (const uint8_t*)d_in[0], (const uint8_t*)d_in[4], (const uint8_t*)d_in[5], (const uint8_t*)d_in[6],
         (const __nv_bfloat16*)d_in[7], (const __nv_bfloat16*)d_in[8]);
  launch(k3_kernel, 128, 320, K3_SMEM, true, x);
  launch(k4_kernel, 128, 384, GEMM_SMEM, true, mg, mu, md, (__nv_bfloat16*)d_out);
}
```

```cpp
#include <cuda_runtime.h>
#include <cuda_bf16.h>
#include <cuda.h>
#include <stdint.h>

#define SEQ 2048
#define DM 576
#define NH 32
#define FF 4608

__device__ uint4 g_ll[36 * 4 * 2];
__device__ uint4 g_tab2[36 * 4];
__device__ __align__(16) __nv_bfloat16 g_ga[DM];
__device__ __align__(16) __nv_bfloat16 g_gb[DM];
__device__ float2 g_stat2[SEQ * 8];
__device__ __align__(1024) uint8_t g_qkv[96 * 98304];
__device__ float g_kmax[NH * 16];
__device__ __align__(1024) uint8_t g_o[SEQ * DM * 2];
__device__ __align__(1024) uint8_t g_x1[SEQ * DM * 2];
__device__ __align__(1024) uint4 g_wo[DM * DM / 8];
__device__ __align__(1024) uint8_t g_part[8 * 16 * 5 * 2 * 16384];
__device__ unsigned int g_cnt[16 * 5];

#define TS(k, i)
#define TSS(i)
#define TSDUMP(k)
__device__ __forceinline__ uint32_t s2u(const void* p) { return (uint32_t)__cvta_generic_to_shared(p); }
__device__ __forceinline__ void mbar_init(uint32_t b, int c) { asm volatile("mbarrier.init.shared::cta.b64 [%0],%1;" ::"r"(b), "r"(c)); }
__device__ __forceinline__ void mbar_expect(uint32_t b, uint32_t n) { asm volatile("mbarrier.arrive.expect_tx.shared::cta.b64 _,[%0],%1;" ::"r"(b), "r"(n) : "memory"); }
__device__ __forceinline__ void mbar_arrive(uint32_t b) { asm volatile("mbarrier.arrive.shared::cta.b64 _,[%0];" ::"r"(b) : "memory"); }
__device__ __forceinline__ void mbar_wait(uint32_t b, uint32_t ph) {
  asm volatile(
      "{.reg .pred p; .reg .u32 n;\n"
      "mbarrier.try_wait.parity.shared::cta.b64 p,[%0],%1;\n"
      "@p bra D;\n"
      "mov.u32 n,0;\n"
      "W: mbarrier.try_wait.parity.shared::cta.b64 p,[%0],%1;\n"
      "@p bra D;\n"
      "add.u32 n,n,1; setp.lt.u32 p,n,4000000; @p bra W;\n"
      "trap;\n"
      "D: }" ::"r"(b), "r"(ph) : "memory");
}
__device__ __forceinline__ void tma2d(uint32_t dst, const CUtensorMap* m, int c0, int c1, uint32_t bar) {
  asm volatile("cp.async.bulk.tensor.2d.shared::cluster.global.mbarrier::complete_tx::bytes [%0],[%1,{%3,%4}],[%2];"
               ::"r"(dst), "l"(m), "r"(bar), "r"(c0), "r"(c1) : "memory");
}
__device__ __forceinline__ void bulk_g2s(uint32_t dst, const void* src, uint32_t bytes, uint32_t bar) {
  asm volatile("cp.async.bulk.shared::cluster.global.mbarrier::complete_tx::bytes [%0],[%1],%2,[%3];"
               ::"r"(dst), "l"(src), "r"(bytes), "r"(bar) : "memory");
}
__device__ __forceinline__ void bulk_s2g(void* dst, uint32_t src, uint32_t bytes) {
  asm volatile("cp.async.bulk.global.shared::cta.bulk_group [%0],[%1],%2;" ::"l"(dst), "r"(src), "r"(bytes) : "memory");
}
__device__ __forceinline__ void bulk_commit() { asm volatile("cp.async.bulk.commit_group;" ::: "memory"); }
__device__ __forceinline__ void bulk_wait0() { asm volatile("cp.async.bulk.wait_group 0;" ::: "memory"); }
__device__ __forceinline__ void prefetch_map(const CUtensorMap* m) { asm volatile("prefetch.tensormap [%0];" ::"l"(m) : "memory"); }
__device__ __forceinline__ void fence_async_smem() { asm volatile("fence.proxy.async.shared::cta;" ::: "memory"); }
__device__ __forceinline__ void bulk_g2s_mc(uint32_t dst, const void* src, uint32_t bytes, uint32_t bar) {
  asm volatile("cp.async.bulk.shared::cluster.global.mbarrier::complete_tx::bytes.multicast::cluster [%0],[%1],%2,[%3],%4;"
               ::"r"(dst), "l"(src), "r"(bytes), "r"(bar), "h"((uint16_t)3) : "memory");
}
__device__ __forceinline__ void tma2d_mc(uint32_t dst, const CUtensorMap* m, int c0, int c1, uint32_t bar) {
  asm volatile("cp.async.bulk.tensor.2d.shared::cluster.global.mbarrier::complete_tx::bytes.multicast::cluster [%0],[%1,{%3,%4}],[%2],%5;"
               ::"r"(dst), "l"(m), "r"(bar), "r"(c0), "r"(c1), "h"((uint16_t)3) : "memory");
}
__device__ __forceinline__ void pair_sync() { asm volatile("barrier.cluster.arrive.relaxed.aligned;\nbarrier.cluster.wait.acquire.aligned;" ::: "memory"); }
#define MC 7
#define CL1 __cluster_dims__(2, 1, 1)
#define CL3 __cluster_dims__(2, 1, 1)
#define MW 0
#define CL4 __cluster_dims__(2, 1, 1)
__device__ __forceinline__ void bulk_wait_exit() { asm volatile("cp.async.bulk.wait_group.read 0;" ::: "memory"); }
__device__ __forceinline__ void fence_bar_init() { asm volatile("fence.mbarrier_init.release.cluster;" ::: "memory"); }
__device__ __forceinline__ void pdl_wait() { asm volatile("griddepcontrol.wait;" ::: "memory"); }
__device__ __forceinline__ void pdl_launch() { asm volatile("griddepcontrol.launch_dependents;" ::: "memory"); }
__device__ __forceinline__ void bar_sync(int id, int n) { asm volatile("bar.sync %0,%1;" ::"r"(id), "r"(n) : "memory"); }
__device__ __forceinline__ void bar_arrive(int id, int n) { asm volatile("bar.arrive %0,%1;" ::"r"(id), "r"(n) : "memory"); }
#define WG_FENCE() asm volatile("wgmma.fence.sync.aligned;" ::: "memory")
#define WG_COMMIT() asm volatile("wgmma.commit_group.sync.aligned;" ::: "memory")
#define WG_WAIT(n) asm volatile("wgmma.wait_group.sync.aligned " #n ";" ::: "memory")
template <int N> __device__ __forceinline__ void fence_regs(float* r) {
#pragma unroll
  for (int i = 0; i < N; i++) asm volatile("" : "+f"(r[i])::"memory");
}
#define REG_INC(n) asm volatile("setmaxnreg.inc.sync.aligned.u32 " #n ";")
#define REG_DEC(n) asm volatile("setmaxnreg.dec.sync.aligned.u32 " #n ";")
__device__ __forceinline__ uint64_t mkdesc(uint32_t addr, uint32_t lbo, uint32_t sbo, int sw) {
  return (uint64_t)((addr & 0x3FFFF) >> 4) | ((uint64_t)(lbo >> 4) << 16) | ((uint64_t)(sbo >> 4) << 32) | ((uint64_t)sw << 62);
}
__device__ __forceinline__ void ldsm4(uint32_t* r, uint32_t addr) {
  asm volatile("ldmatrix.sync.aligned.m8n8.x4.shared.b16 {%0,%1,%2,%3},[%4];" : "=r"(r[0]), "=r"(r[1]), "=r"(r[2]), "=r"(r[3]) : "r"(addr) : "memory");
}
__device__ __forceinline__ void stsm4(uint32_t addr, uint32_t r0, uint32_t r1, uint32_t r2, uint32_t r3) {
  asm volatile("stmatrix.sync.aligned.m8n8.x4.shared.b16 [%0],{%1,%2,%3,%4};" ::"r"(addr), "r"(r0), "r"(r1), "r"(r2), "r"(r3) : "memory");
}
__device__ __forceinline__ uint32_t pack_bf16(float lo, float hi) {
  uint32_t r;
  asm("cvt.rn.bf16x2.f32 %0,%1,%2;" : "=r"(r) : "f"(hi), "f"(lo));
  return r;
}
__device__ __forceinline__ float bf_lo(uint32_t v) { return __uint_as_float(v << 16); }
__device__ __forceinline__ float bf_hi(uint32_t v) { return __uint_as_float(v & 0xFFFF0000u); }
__device__ __forceinline__ float sq2(uint32_t v) { return bf_lo(v) * bf_lo(v) + bf_hi(v) * bf_hi(v); }
__device__ __forceinline__ float rbf(float x) { return __bfloat162float(__float2bfloat16_rn(x)); }
__device__ __forceinline__ uint32_t hfma2(uint32_t a, uint32_t b, uint32_t c) {
  uint32_t r;
  asm("fma.rn.bf16x2 %0,%1,%2,%3;" : "=r"(r) : "r"(a), "r"(b), "r"(c));
  return r;
}
__device__ __forceinline__ uint32_t hadd2(uint32_t a, uint32_t b) {
  uint32_t r;
  asm("add.rn.bf16x2 %0,%1,%2;" : "=r"(r) : "r"(a), "r"(b));
  return r;
}
__device__ __forceinline__ uint32_t hmul2(uint32_t a, uint32_t b) {
  uint32_t r;
  asm("mul.rn.bf16x2 %0,%1,%2;" : "=r"(r) : "r"(a), "r"(b));
  return r;
}
__device__ __forceinline__ uint32_t hneg2(uint32_t a) {
  uint32_t r;
  asm("neg.bf16x2 %0,%1;" : "=r"(r) : "r"(a));
  return r;
}
__device__ __forceinline__ float ex2f(float x) {
  float r;
  asm("ex2.approx.ftz.f32 %0,%1;" : "=f"(r) : "f"(x));
  return r;
}
__device__ __forceinline__ float sqrt_fast(float x) {
  float r;
  asm("sqrt.approx.f32 %0,%1;" : "=f"(r) : "f"(x));
  return r;
}
__device__ __forceinline__ float rcp_fast(float x) {
  float r;
  asm("rcp.approx.f32 %0,%1;" : "=f"(r) : "f"(x));
  return r;
}
__device__ __forceinline__ float tanhf_fast(float x) {
  float r;
  asm("tanh.approx.f32 %0,%1;" : "=f"(r) : "f"(x));
  return r;
}
__device__ __forceinline__ uint4 ln_consts(float mean, float var) {
  float m = rbf(mean), v = rbf(var);
  float s = rbf(sqrtf(rbf(v + 1e-5f)));
  float r = 1.0f / s;
  float rh = rbf(r), rl = r - rh;
  return make_uint4(pack_bf16(-m, -m), pack_bf16(rh, rh), pack_bf16(rl, rl), 0u);
}
__device__ __forceinline__ uint32_t ln_apply(uint32_t x, const uint4& st, uint32_t a, uint32_t s) {
  uint32_t d = hadd2(x, st.x);
  uint32_t n = hfma2(d, st.y, hmul2(d, st.z));
  return hfma2(n, a, s);
}

__device__ __forceinline__ uint4 lds128(uint32_t a) {
  uint4 v;
  asm volatile("ld.shared.v4.b32 {%0,%1,%2,%3},[%4];" : "=r"(v.x), "=r"(v.y), "=r"(v.z), "=r"(v.w) : "r"(a) : "memory");
  return v;
}
__device__ __forceinline__ void sts128(uint32_t a, const uint4& v) {
  asm volatile("st.shared.v4.b32 [%0],{%1,%2,%3,%4};" ::"r"(a), "r"(v.x), "r"(v.y), "r"(v.z), "r"(v.w) : "memory");
}
__device__ __forceinline__ void hmma(float* c, const uint32_t* a, uint32_t b0, uint32_t b1) {
  asm volatile("mma.sync.aligned.m16n8k16.row.col.f32.bf16.bf16.f32 {%0,%1,%2,%3},{%4,%5,%6,%7},{%8,%9},{%0,%1,%2,%3};"
               : "+f"(c[0]), "+f"(c[1]), "+f"(c[2]), "+f"(c[3]) : "r"(a[0]), "r"(a[1]), "r"(a[2]), "r"(a[3]), "r"(b0), "r"(b1));
}
struct RowStat {
  float s[4], q0[4], q1[4];
  __device__ __forceinline__ void init() {
#pragma unroll
    for (int i = 0; i < 4; i++) s[i] = q0[i] = q1[i] = 0.f;
  }
  __device__ __forceinline__ void add(const uint32_t* a) {
    hmma(s, a, 0x3F803F80u, 0x3F803F80u);
    hmma(q0, a, a[0], a[2]);
    hmma(q1, a, a[1], a[3]);
  }
  __device__ __forceinline__ void merge(const RowStat& o) {
#pragma unroll
    for (int i = 0; i < 4; i++) { s[i] += o.s[i]; q0[i] += o.q0[i]; q1[i] += o.q1[i]; }
  }
  __device__ __forceinline__ void finish(int lane, uint4& c0, uint4& c1) {
    const int g = lane >> 2, src = (lane & ~3) | (g >> 1);
    const float a0 = __shfl_sync(~0u, (g & 1) ? q0[1] : q0[0], src), a1 = __shfl_sync(~0u, (g & 1) ? q1[3] : q1[2], src);
    const float m0 = s[0] * (1.0f / DM), m1 = s[2] * (1.0f / DM);
    c0 = ln_consts(m0, fmaxf(a0 * (1.0f / DM) - m0 * m0, 0.f));
    c1 = ln_consts(m1, fmaxf(a1 * (1.0f / DM) - m1 * m1, 0.f));
  }
};
#define LN_CHUNK(c, LOAD)                                                       \
  LOAD(&a[(c) * 4], R + (c) * 16384, warp * 16, lane);                          \
  _Pragma("unroll") for (int k = (c) * 4; k < (c) * 4 + 4; k++) {               \
    const uint4 t = lds128(TAB + (k * 4 + (lane & 3)) * 16);                    \
    a[k][0] = ln_apply(a[k][0], s0, t.x, t.y);                                  \
    a[k][1] = ln_apply(a[k][1], s1, t.x, t.y);                                  \
    a[k][2] = ln_apply(a[k][2], s0, t.z, t.w);                                  \
    a[k][3] = ln_apply(a[k][3], s1, t.z, t.w);                                  \
  }

__device__ __forceinline__ void wg_ss_n72_t1(float* d, uint64_t da, uint64_t db, int sc) {
  asm volatile("{.reg .pred p; setp.ne.b32 p,%38,0; wgmma.mma_async.sync.aligned.m64n72k16.f32.bf16.bf16 {%0,%1,%2,%3,%4,%5,%6,%7,%8,%9,%10,%11,%12,%13,%14,%15,%16,%17,%18,%19,%20,%21,%22,%23,%24,%25,%26,%27,%28,%29,%30,%31,%32,%33,%34,%35}, %36, %37, p,1,1,0,1;}"
  : "+f"(d[0]),"+f"(d[1]),"+f"(d[2]),"+f"(d[3]),"+f"(d[4]),"+f"(d[5]),"+f"(d[6]),"+f"(d[7]),"+f"(d[8]),"+f"(d[9]),"+f"(d[10]),"+f"(d[11]),"+f"(d[12]),"+f"(d[13]),"+f"(d[14]),"+f"(d[15]),"+f"(d[16]),"+f"(d[17]),"+f"(d[18]),"+f"(d[19]),"+f"(d[20]),"+f"(d[21]),"+f"(d[22]),"+f"(d[23]),"+f"(d[24]),"+f"(d[25]),"+f"(d[26]),"+f"(d[27]),"+f"(d[28]),"+f"(d[29]),"+f"(d[30]),"+f"(d[31]),"+f"(d[32]),"+f"(d[33]),"+f"(d[34]),"+f"(d[35]) : "l"(da),"l"(db),"r"(sc));
}
template <int SC> __device__ __forceinline__ void wl_rs_n128_t1(float* d, const uint32_t* a, uint64_t e) {
  if (SC) asm volatile("wgmma.mma_async.sync.aligned.m64n128k16.f32.bf16.bf16 {%0,%1,%2,%3,%4,%5,%6,%7,%8,%9,%10,%11,%12,%13,%14,%15,%16,%17,%18,%19,%20,%21,%22,%23,%24,%25,%26,%27,%28,%29,%30,%31,%32,%33,%34,%35,%36,%37,%38,%39,%40,%41,%42,%43,%44,%45,%46,%47,%48,%49,%50,%51,%52,%53,%54,%55,%56,%57,%58,%59,%60,%61,%62,%63}, {%64,%65,%66,%67}, %68, 1,1,1,1;"
  : "+f"(d[0]),"+f"(d[1]),"+f"(d[2]),"+f"(d[3]),"+f"(d[4]),"+f"(d[5]),"+f"(d[6]),"+f"(d[7]),"+f"(d[8]),"+f"(d[9]),"+f"(d[10]),"+f"(d[11]),"+f"(d[12]),"+f"(d[13]),"+f"(d[14]),"+f"(d[15]),"+f"(d[16]),"+f"(d[17]),"+f"(d[18]),"+f"(d[19]),"+f"(d[20]),"+f"(d[21]),"+f"(d[22]),"+f"(d[23]),"+f"(d[24]),"+f"(d[25]),"+f"(d[26]),"+f"(d[27]),"+f"(d[28]),"+f"(d[29]),"+f"(d[30]),"+f"(d[31]),"+f"(d[32]),"+f"(d[33]),"+f"(d[34]),"+f"(d[35]),"+f"(d[36]),"+f"(d[37]),"+f"(d[38]),"+f"(d[39]),"+f"(d[40]),"+f"(d[41]),"+f"(d[42]),"+f"(d[43]),"+f"(d[44]),"+f"(d[45]),"+f"(d[46]),"+f"(d[47]),"+f"(d[48]),"+f"(d[49]),"+f"(d[50]),"+f"(d[51]),"+f"(d[52]),"+f"(d[53]),"+f"(d[54]),"+f"(d[55]),"+f"(d[56]),"+f"(d[57]),"+f"(d[58]),"+f"(d[59]),"+f"(d[60]),"+f"(d[61]),"+f"(d[62]),"+f"(d[63]) : "r"(a[0]),"r"(a[1]),"r"(a[2]),"r"(a[3]),"l"(e));
  else asm volatile("wgmma.mma_async.sync.aligned.m64n128k16.f32.bf16.bf16 {%0,%1,%2,%3,%4,%5,%6,%7,%8,%9,%10,%11,%12,%13,%14,%15,%16,%17,%18,%19,%20,%21,%22,%23,%24,%25,%26,%27,%28,%29,%30,%31,%32,%33,%34,%35,%36,%37,%38,%39,%40,%41,%42,%43,%44,%45,%46,%47,%48,%49,%50,%51,%52,%53,%54,%55,%56,%57,%58,%59,%60,%61,%62,%63}, {%64,%65,%66,%67}, %68, 0,1,1,1;"
  : "=f"(d[0]),"=f"(d[1]),"=f"(d[2]),"=f"(d[3]),"=f"(d[4]),"=f"(d[5]),"=f"(d[6]),"=f"(d[7]),"=f"(d[8]),"=f"(d[9]),"=f"(d[10]),"=f"(d[11]),"=f"(d[12]),"=f"(d[13]),"=f"(d[14]),"=f"(d[15]),"=f"(d[16]),"=f"(d[17]),"=f"(d[18]),"=f"(d[19]),"=f"(d[20]),"=f"(d[21]),"=f"(d[22]),"=f"(d[23]),"=f"(d[24]),"=f"(d[25]),"=f"(d[26]),"=f"(d[27]),"=f"(d[28]),"=f"(d[29]),"=f"(d[30]),"=f"(d[31]),"=f"(d[32]),"=f"(d[33]),"=f"(d[34]),"=f"(d[35]),"=f"(d[36]),"=f"(d[37]),"=f"(d[38]),"=f"(d[39]),"=f"(d[40]),"=f"(d[41]),"=f"(d[42]),"=f"(d[43]),"=f"(d[44]),"=f"(d[45]),"=f"(d[46]),"=f"(d[47]),"=f"(d[48]),"=f"(d[49]),"=f"(d[50]),"=f"(d[51]),"=f"(d[52]),"=f"(d[53]),"=f"(d[54]),"=f"(d[55]),"=f"(d[56]),"=f"(d[57]),"=f"(d[58]),"=f"(d[59]),"=f"(d[60]),"=f"(d[61]),"=f"(d[62]),"=f"(d[63]) : "r"(a[0]),"r"(a[1]),"r"(a[2]),"r"(a[3]),"l"(e));
}
template <int SC> __device__ __forceinline__ void wl_rs_n24_t1(float* d, const uint32_t* a, uint64_t e) {
  if (SC) asm volatile("wgmma.mma_async.sync.aligned.m64n24k16.f32.bf16.bf16 {%0,%1,%2,%3,%4,%5,%6,%7,%8,%9,%10,%11}, {%12,%13,%14,%15}, %16, 1,1,1,1;"
  : "+f"(d[0]),"+f"(d[1]),"+f"(d[2]),"+f"(d[3]),"+f"(d[4]),"+f"(d[5]),"+f"(d[6]),"+f"(d[7]),"+f"(d[8]),"+f"(d[9]),"+f"(d[10]),"+f"(d[11]) : "r"(a[0]),"r"(a[1]),"r"(a[2]),"r"(a[3]),"l"(e));
  else asm volatile("wgmma.mma_async.sync.aligned.m64n24k16.f32.bf16.bf16 {%0,%1,%2,%3,%4,%5,%6,%7,%8,%9,%10,%11}, {%12,%13,%14,%15}, %16, 0,1,1,1;"
  : "=f"(d[0]),"=f"(d[1]),"=f"(d[2]),"=f"(d[3]),"=f"(d[4]),"=f"(d[5]),"=f"(d[6]),"=f"(d[7]),"=f"(d[8]),"=f"(d[9]),"=f"(d[10]),"=f"(d[11]) : "r"(a[0]),"r"(a[1]),"r"(a[2]),"r"(a[3]),"l"(e));
}
template <int SC> __device__ __forceinline__ void wl_rs_n64_t0(float* d, const uint32_t* a, uint64_t e) {
  if (SC) asm volatile("wgmma.mma_async.sync.aligned.m64n64k16.f32.bf16.bf16 {%0,%1,%2,%3,%4,%5,%6,%7,%8,%9,%10,%11,%12,%13,%14,%15,%16,%17,%18,%19,%20,%21,%22,%23,%24,%25,%26,%27,%28,%29,%30,%31}, {%32,%33,%34,%35}, %36, 1,1,1,0;"
  : "+f"(d[0]),"+f"(d[1]),"+f"(d[2]),"+f"(d[3]),"+f"(d[4]),"+f"(d[5]),"+f"(d[6]),"+f"(d[7]),"+f"(d[8]),"+f"(d[9]),"+f"(d[10]),"+f"(d[11]),"+f"(d[12]),"+f"(d[13]),"+f"(d[14]),"+f"(d[15]),"+f"(d[16]),"+f"(d[17]),"+f"(d[18]),"+f"(d[19]),"+f"(d[20]),"+f"(d[21]),"+f"(d[22]),"+f"(d[23]),"+f"(d[24]),"+f"(d[25]),"+f"(d[26]),"+f"(d[27]),"+f"(d[28]),"+f"(d[29]),"+f"(d[30]),"+f"(d[31]) : "r"(a[0]),"r"(a[1]),"r"(a[2]),"r"(a[3]),"l"(e));
  else asm volatile("wgmma.mma_async.sync.aligned.m64n64k16.f32.bf16.bf16 {%0,%1,%2,%3,%4,%5,%6,%7,%8,%9,%10,%11,%12,%13,%14,%15,%16,%17,%18,%19,%20,%21,%22,%23,%24,%25,%26,%27,%28,%29,%30,%31}, {%32,%33,%34,%35}, %36, 0,1,1,0;"
  : "=f"(d[0]),"=f"(d[1]),"=f"(d[2]),"=f"(d[3]),"=f"(d[4]),"=f"(d[5]),"=f"(d[6]),"=f"(d[7]),"=f"(d[8]),"=f"(d[9]),"=f"(d[10]),"=f"(d[11]),"=f"(d[12]),"=f"(d[13]),"=f"(d[14]),"=f"(d[15]),"=f"(d[16]),"=f"(d[17]),"=f"(d[18]),"=f"(d[19]),"=f"(d[20]),"=f"(d[21]),"=f"(d[22]),"=f"(d[23]),"=f"(d[24]),"=f"(d[25]),"=f"(d[26]),"=f"(d[27]),"=f"(d[28]),"=f"(d[29]),"=f"(d[30]),"=f"(d[31]) : "r"(a[0]),"r"(a[1]),"r"(a[2]),"r"(a[3]),"l"(e));
}
template <int SC> __device__ __forceinline__ void wl_rs_n64_t1(float* d, const uint32_t* a, uint64_t e) {
  if (SC) asm volatile("wgmma.mma_async.sync.aligned.m64n64k16.f32.bf16.bf16 {%0,%1,%2,%3,%4,%5,%6,%7,%8,%9,%10,%11,%12,%13,%14,%15,%16,%17,%18,%19,%20,%21,%22,%23,%24,%25,%26,%27,%28,%29,%30,%31}, {%32,%33,%34,%35}, %36, 1,1,1,1;"
  : "+f"(d[0]),"+f"(d[1]),"+f"(d[2]),"+f"(d[3]),"+f"(d[4]),"+f"(d[5]),"+f"(d[6]),"+f"(d[7]),"+f"(d[8]),"+f"(d[9]),"+f"(d[10]),"+f"(d[11]),"+f"(d[12]),"+f"(d[13]),"+f"(d[14]),"+f"(d[15]),"+f"(d[16]),"+f"(d[17]),"+f"(d[18]),"+f"(d[19]),"+f"(d[20]),"+f"(d[21]),"+f"(d[22]),"+f"(d[23]),"+f"(d[24]),"+f"(d[25]),"+f"(d[26]),"+f"(d[27]),"+f"(d[28]),"+f"(d[29]),"+f"(d[30]),"+f"(d[31]) : "r"(a[0]),"r"(a[1]),"r"(a[2]),"r"(a[3]),"l"(e));
  else asm volatile("wgmma.mma_async.sync.aligned.m64n64k16.f32.bf16.bf16 {%0,%1,%2,%3,%4,%5,%6,%7,%8,%9,%10,%11,%12,%13,%14,%15,%16,%17,%18,%19,%20,%21,%22,%23,%24,%25,%26,%27,%28,%29,%30,%31}, {%32,%33,%34,%35}, %36, 0,1,1,1;"
  : "=f"(d[0]),"=f"(d[1]),"=f"(d[2]),"=f"(d[3]),"=f"(d[4]),"=f"(d[5]),"=f"(d[6]),"=f"(d[7]),"=f"(d[8]),"=f"(d[9]),"=f"(d[10]),"=f"(d[11]),"=f"(d[12]),"=f"(d[13]),"=f"(d[14]),"=f"(d[15]),"=f"(d[16]),"=f"(d[17]),"=f"(d[18]),"=f"(d[19]),"=f"(d[20]),"=f"(d[21]),"=f"(d[22]),"=f"(d[23]),"=f"(d[24]),"=f"(d[25]),"=f"(d[26]),"=f"(d[27]),"=f"(d[28]),"=f"(d[29]),"=f"(d[30]),"=f"(d[31]) : "r"(a[0]),"r"(a[1]),"r"(a[2]),"r"(a[3]),"l"(e));
}
template <int SC> __device__ __forceinline__ void wl_rs_n88_t1(float* d, const uint32_t* a, uint64_t e) {
  if (SC) asm volatile("wgmma.mma_async.sync.aligned.m64n88k16.f32.bf16.bf16 {%0,%1,%2,%3,%4,%5,%6,%7,%8,%9,%10,%11,%12,%13,%14,%15,%16,%17,%18,%19,%20,%21,%22,%23,%24,%25,%26,%27,%28,%29,%30,%31,%32,%33,%34,%35,%36,%37,%38,%39,%40,%41,%42,%43}, {%44,%45,%46,%47}, %48, 1,1,1,1;"
  : "+f"(d[0]),"+f"(d[1]),"+f"(d[2]),"+f"(d[3]),"+f"(d[4]),"+f"(d[5]),"+f"(d[6]),"+f"(d[7]),"+f"(d[8]),"+f"(d[9]),"+f"(d[10]),"+f"(d[11]),"+f"(d[12]),"+f"(d[13]),"+f"(d[14]),"+f"(d[15]),"+f"(d[16]),"+f"(d[17]),"+f"(d[18]),"+f"(d[19]),"+f"(d[20]),"+f"(d[21]),"+f"(d[22]),"+f"(d[23]),"+f"(d[24]),"+f"(d[25]),"+f"(d[26]),"+f"(d[27]),"+f"(d[28]),"+f"(d[29]),"+f"(d[30]),"+f"(d[31]),"+f"(d[32]),"+f"(d[33]),"+f"(d[34]),"+f"(d[35]),"+f"(d[36]),"+f"(d[37]),"+f"(d[38]),"+f"(d[39]),"+f"(d[40]),"+f"(d[41]),"+f"(d[42]),"+f"(d[43]) : "r"(a[0]),"r"(a[1]),"r"(a[2]),"r"(a[3]),"l"(e));
  else asm volatile("wgmma.mma_async.sync.aligned.m64n88k16.f32.bf16.bf16 {%0,%1,%2,%3,%4,%5,%6,%7,%8,%9,%10,%11,%12,%13,%14,%15,%16,%17,%18,%19,%20,%21,%22,%23,%24,%25,%26,%27,%28,%29,%30,%31,%32,%33,%34,%35,%36,%37,%38,%39,%40,%41,%42,%43}, {%44,%45,%46,%47}, %48, 0,1,1,1;"
  : "=f"(d[0]),"=f"(d[1]),"=f"(d[2]),"=f"(d[3]),"=f"(d[4]),"=f"(d[5]),"=f"(d[6]),"=f"(d[7]),"=f"(d[8]),"=f"(d[9]),"=f"(d[10]),"=f"(d[11]),"=f"(d[12]),"=f"(d[13]),"=f"(d[14]),"=f"(d[15]),"=f"(d[16]),"=f"(d[17]),"=f"(d[18]),"=f"(d[19]),"=f"(d[20]),"=f"(d[21]),"=f"(d[22]),"=f"(d[23]),"=f"(d[24]),"=f"(d[25]),"=f"(d[26]),"=f"(d[27]),"=f"(d[28]),"=f"(d[29]),"=f"(d[30]),"=f"(d[31]),"=f"(d[32]),"=f"(d[33]),"=f"(d[34]),"=f"(d[35]),"=f"(d[36]),"=f"(d[37]),"=f"(d[38]),"=f"(d[39]),"=f"(d[40]),"=f"(d[41]),"=f"(d[42]),"=f"(d[43]) : "r"(a[0]),"r"(a[1]),"r"(a[2]),"r"(a[3]),"l"(e));
}

#define POLY_MASK 0xB5u
#define PFX 9
#define PACE3 380
#define PACE4 300
#define PACEB 400
#define XL -1
#define ALIAS 0
#define P4W 1
#define W1 0
#define PACE1 0
#define GU "unroll"
#define PACEW 800
#define WOL 0
#define PFT 1
#define PFD 0
#define QSCALE (0.23570226039551584f * 1.4426950408889634f)

#define NSTG 6
#define STG_BYTES 16384
#define R_BYTES (8 * 16384)
#define GEMM_SMEM (R_BYTES + NSTG * STG_BYTES + 3072)

__device__ __forceinline__ void load_a_chunk(uint32_t (*a)[4], uint32_t chunk_base, int row_in_tile, int lane) {
  const int r = row_in_tile + (lane & 7) + ((lane >> 3) & 1) * 8;
  const uint32_t rb = chunk_base + r * 128;
#pragma unroll
  for (int k = 0; k < 4; k++) ldsm4(a[k], rb + (((k * 2 + (lane >> 4)) ^ (r & 7)) << 4));
}

__device__ __forceinline__ void load_a_core(uint32_t (*a)[4], uint32_t chunk_base, int row_in_tile, int lane) {
  const uint32_t rb = chunk_base + (row_in_tile >> 6) * 8192 + ((row_in_tile & 63) + (lane & 15)) * 16 + (lane >> 4) * 1024;
#pragma unroll
  for (int k = 0; k < 4; k++) ldsm4(a[k], rb + k * 2048);
}

#define MMA_TILE(FN, ODD, pj) MMA_TILE_(FN, ODD, pj, )
#define REL(o) if (lane == 0) mbar_arrive(empty + (o))
#define MMA_TILE_(FN, ODD, pj, PRE)                                             \
  {                                                                             \
    uint32_t rb_ = (RING & 0x3FFFF) >> 4;                                                 \
    asm volatile("" : "+r"(rb_));                                               \
    const uint64_t db = mkdesc(0, 8192, 1024, 1) + (uint32_t)__shfl_sync(~0u, rb_, 0); \
    _Pragma("unroll") for (int s = 0; s < 9; s++) {                             \
      const int g_ = 1 + (ODD) * 9 + s, st_ = g_ % NSTG;                        \
      PRE;                                                                      \
      mbar_wait(full + st_ * 8, (pj) ^ ((g_ / NSTG) & 1));                      \
      WG_FENCE();                                                               \
      if (s == 0) FN<0>(acc, a[0], db + st_ * 1024); else FN<1>(acc, a[s * 4], db + st_ * 1024); \
      _Pragma("unroll") for (int k = 1; k < 4; k++) FN<1>(acc, a[s * 4 + k], db + st_ * 1024 + k * 128); \
      WG_COMMIT();                                                              \
      if (s > 0) { WG_WAIT(1); REL(((g_ - 1) % NSTG) * 8); } \
    }                                                                           \
    WG_WAIT(0);                                                                 \
    REL(((9 + (ODD) * 9) % NSTG) * 8);    \
  }

template <int NG, int G0>
__device__ __forceinline__ void qkv_stage(const float* acc, uint32_t stg, int rowl, int cq, int nb) {
  const float vs0 = ((POLY_MASK >> ((rowl >> 3) & 7)) & 1) ? 0.5f : 1.0f, vs1 = ((POLY_MASK >> (((rowl >> 3) + 1) & 7)) & 1) ? 0.5f : 1.0f;
  const uint32_t base = stg + (rowl >> 3) * 384 + (rowl & 7) * 16;
#pragma unroll
  for (int j = 0; j < 9; j++) {
    const int cc = j * 8 + cq * 2, slot = (cc * 3641) >> 16, d = cc - slot * 18;
    const uint32_t ad = base + slot * 6144 + (d >> 3) * 128 + (d & 7) * 2;
#pragma unroll
    for (int per = 0; per < 3; per++) {
      const int i = per * 9 + j - G0, type = (nb * 3 + per) >> 3;
      if (i < 0 || i >= NG) continue;
      const float sc0 = type == 0 ? QSCALE : (type == 1 ? vs0 : 1.0f), sc1 = type == 0 ? QSCALE : (type == 1 ? vs1 : 1.0f);
      asm volatile("st.shared.b32 [%0],%1;" ::"r"(ad + per * 24576), "r"(pack_bf16(acc[4 * i] * sc0, acc[4 * i + 1] * sc0)) : "memory");
      asm volatile("st.shared.b32 [%0],%1;" ::"r"(ad + per * 24576 + 384), "r"(pack_bf16(acc[4 * i + 2] * sc1, acc[4 * i + 3] * sc1)) : "memory");
    }
  }
}

__device__ __forceinline__ float silu_f(float v) { return rbf(__fdividef(v, 1.0f + fminf(__expf(-v), 1e37f))); }
__device__ __forceinline__ float silu_bf(__nv_bfloat16 c) { return silu_f(__bfloat162float(c)); }
__device__ __forceinline__ void fma8(float* acc, float sv, const uint4& w) {
  acc[0] += sv * bf_lo(w.x); acc[1] += sv * bf_hi(w.x); acc[2] += sv * bf_lo(w.y); acc[3] += sv * bf_hi(w.y);
  acc[4] += sv * bf_lo(w.z); acc[5] += sv * bf_hi(w.z); acc[6] += sv * bf_lo(w.w); acc[7] += sv * bf_hi(w.w);
}
__device__ __forceinline__ int tab_pos(int col, int shift) {
  return (((col >> 4) * 4 + ((col & 7) >> 1)) * 4 + ((col >> 3) & 1) * 2 + shift) * 2 + (col & 1);
}
__device__ __forceinline__ float knorm_row(uint32_t slot, int row) {
  const uint32_t ad = slot + (row >> 3) * 384 + (row & 7) * 16;
  const uint4 u = lds128(ad), v = lds128(ad + 128);
  uint32_t w;
  asm volatile("ld.shared.b32 %0,[%1];" : "=r"(w) : "r"(ad + 256) : "memory");
  float q = sq2(u.x) + sq2(u.y) + sq2(u.z) + sq2(u.w) + sq2(v.x) + sq2(v.y) + sq2(v.z) + sq2(v.w) + sq2(w);
  if ((POLY_MASK >> ((row >> 3) & 7)) & 1) q *= 4.0f;
  return q == q ? q : __int_as_float(0x7f800000);
}

__global__ void CL1 __launch_bounds__(384, 1) k1_kernel(const __grid_constant__ CUtensorMap mx, const __grid_constant__ CUtensorMap mw,
                                                    const __grid_constant__ CUtensorMap mm, const __nv_bfloat16* __restrict__ cvec,
                                                    const uint8_t* __restrict__ wqkv, const uint4* __restrict__ wo) {
  extern __shared__ __align__(1024) uint8_t smem_raw[];
  const uint32_t sb = s2u(smem_raw);
  const uint32_t R = sb, RING = sb + R_BYTES, BAR = RING + NSTG * STG_BYTES, TAB = BAR + 512;
  const uint32_t full = BAR, empty = BAR + 64, xfull = BAR + 128;
  const int tid = threadIdx.x, lane = tid & 31, warp = tid >> 5;
  const int mb = blockIdx.x >> 3, nb = blockIdx.x & 7;
  if (tid == 0) TS(1, 0);
  if (tid == 288) { prefetch_map(&mx); prefetch_map(&mw); }
  if (tid == 256) {
    if (sb & 1023) __trap();
    for (int i = 0; i < NSTG; i++) { mbar_init(full + i * 8, 1); mbar_init(empty + i * 8, 8); }
    for (int i = 0; i < 9; i++) mbar_init(xfull + i * 8, 1);
    if (MC & 1) { for (int i = 0; i < 8; i++) mbar_expect(xfull + i * 8, 16384); mbar_expect(full, 16384); }
    fence_bar_init();
    if (blockIdx.x < 72) {
      mbar_expect(xfull + 64, 18432);
      for (int i = 0; i < 3; i++) tma2d(RING + 4 * STG_BYTES + i * 6144, &mm, blockIdx.x * 16, i * 192, xfull + 64);
    }
  }
  if (MC & 1) pair_sync(); else __syncthreads();
  pdl_launch();
  if (MC & 1) {
    if (PACE1 && warp < 8) { const uint32_t t0 = clock(); while ((uint32_t)clock() - t0 < (uint32_t)((warp == 1 && !(nb & 1) ? 8 : warp) * PACE1)) {} }
    if (lane == 0 && warp < 8 && (warp & 1) == (nb & 1)) tma2d_mc(R + warp * 16384, &mx, warp * 64, mb * 128, xfull + warp * 8);
    if (lane == 0 && warp == 1 && !(nb & 1)) tma2d_mc(RING, &mx, 512, mb * 128, full);
  } else if (lane == 0) {
    if (warp < 8) { mbar_expect(xfull + warp * 8, 16384); tma2d(R + warp * 16384, &mx, warp * 64, mb * 128, xfull + warp * 8); }
    if (warp == 1) { mbar_expect(full, 16384); tma2d(RING, &mx, 512, mb * 128, full); }
  }
  __syncwarp();
#define W_FIRST() { asm volatile("cp.async.bulk.prefetch.L2.global [%0],%1;" ::"l"(wqkv + blockIdx.x * 15552), "r"(15552) : "memory"); \
      for (int st = 1; st < 4; st++) { \
        mbar_expect(full + st * 8, 16384); \
        tma2d(RING + st * STG_BYTES, &mw, nb * 216, st * 64 - 64, full + st * 8); \
        tma2d(RING + st * STG_BYTES + 8192, &mw, nb * 216 + 64, st * 64 - 64, full + st * 8); } }
  if (warp >= 8) {
    REG_DEC(24);
    const int pt = tid - 256;
    if (PFD < 0 && pt == 0) W_FIRST();
    if (blockIdx.x < 72) {
      float* sf = (float*)(smem_raw + R_BYTES + 4 * STG_BYTES + 18432);
      if (pt < 72) {
        const uint4 cv = __ldg((const uint4*)cvec + pt);
        const uint32_t cw[4] = {cv.x, cv.y, cv.z, cv.w};
#pragma unroll
        for (int i = 0; i < 4; i++) { sf[pt * 8 + 2 * i] = silu_f(bf_lo(cw[i])); sf[pt * 8 + 2 * i + 1] = silu_f(bf_hi(cw[i])); }
      }
      bar_sync(3, 128);
      mbar_wait(xfull + 64, 0);
      float acc[8] = {0, 0, 0, 0, 0, 0, 0, 0};
#pragma unroll 1
      for (int i = 0; i < 9; i++) fma8(acc, sf[(pt >> 1) + 64 * i], lds128(RING + 4 * STG_BYTES + i * 2048 + pt * 16));
#pragma unroll
      for (int j = 0; j < 8; j++)
#pragma unroll
        for (int o = 2; o < 32; o *= 2) acc[j] += __shfl_xor_sync(~0u, acc[j], o);
      if (lane < 2) {
#pragma unroll
        for (int j = 0; j < 8; j++) sf[DM + (warp - 8) * 16 + lane * 8 + j] = acc[j];
      }
      bar_sync(3, 128);
      if (pt < 16) {
        const float v = rbf(sf[DM + pt] + sf[DM + 16 + pt] + sf[DM + 32 + pt] + sf[DM + 48 + pt]);
        const int n = blockIdx.x * 16 + pt, shift = n < DM;
        const uint32_t word = pack_bf16(shift ? v : 1.0f + v, 1.0f);
        asm volatile("st.relaxed.gpu.global.u32 [%0],%1;" ::"l"((uint32_t*)g_ll + tab_pos(shift ? n : n - DM, shift)), "r"(word) : "memory");
      }
      fence_async_smem();
      __syncwarp();
      if (pt == 0) TS(0, 1);
    }
    if (warp == 8) {
      if (lane == 0) {
        int st = 4; uint32_t ph = 0;
        for (int it = 3; it < 18; it++) {
          const int t = it / 9, s = it - t * 9;
          mbar_wait(empty + st * 8, ph ^ 1);
          mbar_expect(full + st * 8, 16384);
          tma2d(RING + st * STG_BYTES, &mw, nb * 216 + t * 128, s * 64, full + st * 8);
          tma2d(RING + st * STG_BYTES + 8192, &mw, nb * 216 + t * 128 + 64, s * 64, full + st * 8);
          if (++st == NSTG) { st = 0; ph ^= 1; }
        }
      }
    } else {
      const int ht = tid - 288;
#define WO_TILE() _Pragma("unroll 2") for (int j = ht; j < 324; j += 96) {        \
        const int i = blockIdx.x * 324 + j, k = i / 72, n8 = i - k * 72; \
        g_wo[(n8 / 9) * 5184 + (k >> 3) * 72 + (n8 % 9) * 8 + (k & 7)] = __ldg(wo + i); }
      if (WOL == 0) { mbar_wait(full, 0); WO_TILE() }
      if (WOL == 2) { mbar_wait(full + 24, 0); WO_TILE() }
      bar_sync(1, 352);
      for (int i = ht; i < 12 * 128; i += 96) {
        const int slot = i >> 7, row = i & 127, type = (nb * 12 + slot) >> 5;
        uint32_t v = 0;
        if (type == 1) v = ((POLY_MASK >> ((row >> 3) & 7)) & 1) ? 0x43403F00u : 0x40253F80u;
        if (type == 2) v = 0x3F80u;
        const uint32_t ad = R + slot * 6144 + (row >> 3) * 384 + 256 + (row & 7) * 16;
        asm volatile("st.shared.b32 [%0],%1;" ::"r"(ad + 4), "r"(v) : "memory");
        asm volatile("st.shared.v2.b32 [%0],{%1,%1};" ::"r"(ad + 8), "r"(0) : "memory");
      }
      fence_async_smem();
      bar_sync(2, 352);
      if (ht == 0) {
        for (int s = 0; s < 7; s++) bulk_s2g(g_qkv + (size_t)(nb * 12 + s) * 98304 + mb * 6144, R + s * 6144, 6144);
        bulk_commit();
      }
      if (WOL == 1) { WO_TILE() }
      for (int s = warp - 9; s < 7; s += 3) {
        const int gs = nb * 12 + s;
        if ((gs >> 5) != 1) continue;
        float mx2 = 0;
#pragma unroll 1
        for (int row = lane; row < 128; row += 32) mx2 = fmaxf(mx2, knorm_row(R + s * 6144, row));
#pragma unroll
        for (int o = 16; o; o >>= 1) mx2 = fmaxf(mx2, __shfl_xor_sync(~0u, mx2, o));
        if (lane == 0) g_kmax[(gs & 31) * 16 + mb] = mx2;
      }
      if (ht == 0) bulk_wait_exit();
    }
  } else {
    REG_INC(240);
    TSS(0);
    const int rowl = warp * 16;
    uint4 s0, s1;
    {
      RowStat rs, rt;
      rs.init(); rt.init();
      uint32_t f[4][4];
#pragma unroll 1
      for (int c = 0; c < 9; c++) {
        mbar_wait(c < 8 ? xfull + c * 8 : full, 0);
        if (c == PFD && tid == 224) W_FIRST();
        __syncwarp();
        load_a_chunk(f, R + c * 16384, rowl, lane);
        rs.add(f[0]); rt.add(f[1]); rs.add(f[2]); rt.add(f[3]);
      }
      rs.merge(rt);
      rs.finish(lane, s0, s1);
    }
    TSS(1);
    if (tid < 144) {
      uint4 u, v;
      int n = 0;
      do {
        asm volatile("ld.relaxed.gpu.global.v4.u32 {%0,%1,%2,%3},[%4];" : "=r"(u.x), "=r"(u.y), "=r"(u.z), "=r"(u.w) : "l"(g_ll + tid * 2) : "memory");
        asm volatile("ld.relaxed.gpu.global.v4.u32 {%0,%1,%2,%3},[%4];" : "=r"(v.x), "=r"(v.y), "=r"(v.z), "=r"(v.w) : "l"(g_ll + tid * 2 + 1) : "memory");
        if (++n > 4000000) __trap();
      } while (((u.x & u.y & u.z & u.w & v.x & v.y & v.z & v.w) >> 16) != 0x3F80u);
      sts128(TAB + tid * 16, make_uint4(__byte_perm(u.x, u.y, 0x5410), __byte_perm(u.z, u.w, 0x5410), __byte_perm(v.x, v.y, 0x5410), __byte_perm(v.z, v.w, 0x5410)));
    }
    bar_sync(4, 256);
    TSS(2);
    uint32_t a[36][4];
    float acc[64];
    MMA_TILE_(wl_rs_n128_t1, 0, 0, if (s < 8) { LN_CHUNK(s, load_a_chunk) } if (s == 1) { LN_CHUNK(8, load_a_chunk) if (lane == 0) mbar_arrive(empty); } if (s == 5) bar_arrive(1, 352));
    TSS(3);
    bar_sync(4, 256);
    int t2 = threadIdx.x;
    asm volatile("" : "+r"(t2));
    qkv_stage<16, 0>(acc, R, (t2 >> 5) * 16 + ((t2 & 31) >> 2), t2 & 3, nb);
    fence_async_smem();
    bar_arrive(2, 352);
    TSS(4);
    MMA_TILE(wl_rs_n88_t1, 1, 0);
    asm volatile("" : "+r"(t2));
    qkv_stage<11, 16>(acc, R, (t2 >> 5) * 16 + ((t2 & 31) >> 2), t2 & 3, nb);
    fence_async_smem();
    bar_sync(4, 256);
    TSS(5);
    if (tid == 0) {
      for (int s = 7; s < 12; s++) bulk_s2g(g_qkv + (size_t)(nb * 12 + s) * 98304 + mb * 6144, R + s * 6144, 6144);
      bulk_commit();
    }
    if (warp >= 3 && ((nb * 12 + 4 + warp) >> 5) == 1) {
      float mx2 = 0;
#pragma unroll
      for (int i = 0; i < 4; i++) mx2 = fmaxf(mx2, knorm_row(R + (4 + warp) * 6144, lane + 32 * i));
#pragma unroll
      for (int o = 16; o; o >>= 1) mx2 = fmaxf(mx2, __shfl_xor_sync(~0u, mx2, o));
      if (lane == 0) g_kmax[((nb * 12 + 4 + warp) & 31) * 16 + mb] = mx2;
    }
    if (tid == 0) bulk_wait_exit();
    TSS(6);
    TSDUMP(1);
  }
}

#define ATT_SMEM (2 * 98304 + 1024 + 256)

__device__ __forceinline__ uint32_t exp2_pair_fma(float t0, float t1) {
  uint32_t y;
  asm("prmt.b32 %0,%1,%2,0x6521;" : "=r"(y) : "r"(__float_as_uint(t0)), "r"(__float_as_uint(t1)));
  return hfma2(y, y | 0x3F803F80u, y | 0x007F007Fu);
}

__device__ __forceinline__ void softmax_fast(const float* s, uint32_t* p) {
#pragma unroll
  for (int i = 0; i < 8; i++) {
    if ((POLY_MASK >> i) & 1) {
      p[2 * i] = exp2_pair_fma(s[4 * i], s[4 * i + 1]);
      p[2 * i + 1] = exp2_pair_fma(s[4 * i + 2], s[4 * i + 3]);
    } else {
      p[2 * i] = pack_bf16(ex2f(s[4 * i]), ex2f(s[4 * i + 1]));
      p[2 * i + 1] = pack_bf16(ex2f(s[4 * i + 2]), ex2f(s[4 * i + 3]));
    }
  }
}
#define QK_MMA(S, kd)                                                           \
  wl_rs_n64_t0<0>(S, q, (kd));                                                  \
  wl_rs_n64_t0<1>(S, q + 4, (kd) + 16 - (8ull << 16));
#define PV_MMA(P, vd)                                                           \
  _Pragma("unroll") for (int t = 0; t < 4; t++) wl_rs_n24_t1<1>(o, P + 4 * t, (vd) + t * 48);

__device__ __forceinline__ void att_store(const float* o, int row0, int head, int lane) {
  const int cq = lane & 3;
  const float l0 = __shfl_sync(~0u, o[8], (lane & ~3) | 1), l1 = __shfl_sync(~0u, o[10], (lane & ~3) | 1);
  const float i0 = rcp_fast(l0), i1 = rcp_fast(l1);
  const int col = head * 18 + cq * 2;
  uint32_t* og = (uint32_t*)(g_o + (row0 >> 6) * 73728 + (col >> 3) * 1024 + (row0 & 63) * 16 + (col & 7) * 2);
  og[0] = pack_bf16(o[0] * i0, o[1] * i0);
  og[256] = pack_bf16(o[4] * i0, o[5] * i0);
  og[32] = pack_bf16(o[2] * i1, o[3] * i1);
  og[256 + 32] = pack_bf16(o[6] * i1, o[7] * i1);
  if (cq == 0) {
    og[512] = pack_bf16(o[8] * i0, o[9] * i0);
    og[512 + 32] = pack_bf16(o[10] * i1, o[11] * i1);
  }
}

__global__ void __launch_bounds__(512, 1) k2_kernel(const uint8_t* __restrict__ xin, const uint8_t* __restrict__ wg_, const uint8_t* __restrict__ wu,
                                                    const uint8_t* __restrict__ wd, const __nv_bfloat16* __restrict__ cvec,
                                                    const __nv_bfloat16* __restrict__ wmod) {
  extern __shared__ __align__(1024) uint8_t smem_raw[];
  const uint32_t sb = (s2u(smem_raw) + 1023) & ~1023u;
  const uint32_t KS = sb, VS = sb + 98304, BAR = sb + 2 * 98304;
  const int tid = threadIdx.x, lane = tid & 31, warp = tid >> 5, wg = tid >> 7;
  if (blockIdx.x < 4) {
    float* sf = (float*)smem_raw;
    const int part = blockIdx.x + 2;
    for (int i = tid; i < DM; i += 512) sf[i] = silu_bf(cvec[i]);
    if (part == 2 && tid < 80) g_cnt[tid] = 0;
    __nanosleep(4000);
    __syncthreads();
    if (tid < 432) {
      const int cg = tid % 72, rg = tid / 72;
      const __nv_bfloat16* w = wmod + (size_t)rg * 96 * 3456 + part * DM + cg * 8;
      float acc[8] = {0, 0, 0, 0, 0, 0, 0, 0};
#pragma unroll 1
      for (int r = 0; r < 96; r += 12) {
        uint4 v[12];
#pragma unroll
        for (int i = 0; i < 12; i++) v[i] = __ldg((const uint4*)(w + (size_t)(r + i) * 3456));
#pragma unroll
        for (int i = 0; i < 12; i++) fma8(acc, sf[rg * 96 + r + i], v[i]);
      }
#pragma unroll
      for (int j = 0; j < 8; j++) sf[DM + rg * DM + cg * 8 + j] = acc[j];
    }
    __syncthreads();
    for (int col = tid; col < DM; col += 512) {
      float v = 0;
#pragma unroll
      for (int j = 1; j < 7; j++) v += sf[j * DM + col];
      v = rbf(v);
      if (part == 2) g_ga[col] = __float2bfloat16_rn(v);
      else if (part == 5) g_gb[col] = __float2bfloat16_rn(v);
      else ((__nv_bfloat16*)g_tab2)[tab_pos(col, part == 3)] = __float2bfloat16_rn(0.5f * (part == 3 ? v : rbf(1.0f + v)));
    }
    pdl_wait();
    if (part == 2 && tid < 288) g_ll[tid] = make_uint4(0, 0, 0, 0);
    if (tid == 0) TS(0, 0);
    return;
  }
  const int bid = blockIdx.x - 4, head = bid >> 2, qb = bid & 3;
  if (tid == 0) {
    TS(2, 0);
    for (int i = 0; i < 16; i++) mbar_init(BAR + i * 8, 1);
    fence_bar_init();
  }
  __syncthreads();
  const int g = lane >> 2, cq = lane & 3;
  const int row0 = qb * 512 + wg * 128 + (warp & 3) * 16 + g;
  const uint8_t* qg = g_qkv + (size_t)head * 98304 + (row0 >> 3) * 384 + (row0 & 7) * 16 + cq * 4;
  pdl_wait();
  pdl_launch();
  if (tid == 0) TS(2, 1);
  const uint8_t* kg = g_qkv + (size_t)(32 + head) * 98304;
#define KV_LOAD(c) { mbar_expect(BAR + (c) * 8, 12288); bulk_g2s(KS + (c) * 6144, kg + (c) * 6144, 6144, BAR + (c) * 8); \
                     bulk_g2s(VS + (c) * 6144, kg + 32 * 98304 + (c) * 6144, 6144, BAR + (c) * 8); }
  if (lane == 0 && warp < 2 - W1) KV_LOAD(warp);
  __syncwarp();
  uint32_t q[8], q2[6];
  float kmax2 = __ldcg(g_kmax + head * 16 + (lane & 15));
#pragma unroll
  for (int i = 0; i < 6; i++) {
    q[i] = __ldcg((const uint32_t*)(qg + (i & 1) * 384 + (i >> 1) * 128));
    q2[i] = __ldcg((const uint32_t*)(qg + 3072 + (i & 1) * 384 + (i >> 1) * 128));
  }
  q[6] = __ldcg((const uint32_t*)(qg + 256 + 12 - cq * 4)); q[7] = __ldcg((const uint32_t*)(qg + 256 + 8 - cq * 4));
  const uint64_t dk = mkdesc(KS, 128, 384, 0), dv = mkdesc(VS, 384, 128, 0);
#pragma unroll
  for (int o = 8; o; o >>= 1) kmax2 = fmaxf(kmax2, __shfl_xor_sync(~0u, kmax2, o));
  float bd[4] = {sq2(q[0]) + sq2(q[2]) + sq2(q[4]), sq2(q[1]) + sq2(q[3]) + sq2(q[5]),
                 sq2(q2[0]) + sq2(q2[2]) + sq2(q2[4]), sq2(q2[1]) + sq2(q2[3]) + sq2(q2[5])};
  int ok = 1;
  if (tid == 0 && bd[0] + bd[3] + kmax2 != 1.2345f) TS(2, 5);
#pragma unroll
  for (int i = 0; i < 4; i++) {
    bd[i] += __shfl_xor_sync(~0u, bd[i], 1); bd[i] += __shfl_xor_sync(~0u, bd[i], 2);
    bd[i] = sqrt_fast(bd[i] * kmax2) * 1.01f + 1.0f;
    ok = ok && (bd[i] <= 62.0f);
  }
  {
    uint32_t all;
    asm volatile("{.reg .pred p,q; setp.ne.b32 p,%1,0; barrier.red.and.pred q,1,512,p; selp.u32 %0,1,0,q;}"
                 : "=r"(all) : "r"(ok) : "memory");
    ok = __all_sync(~0u, all);
  }
  float o[12];
#pragma unroll
  for (int i = 0; i < 12; i++) { o[i] = 0.f; asm volatile("" : "+f"(o[i])); }
  float s[32];
  uint32_t p[16];
  if (tid == 0) TS(2, 2);
  if (ok) {
    if (cq == 1) {
      q[4] = pack_bf16(-bd[0], 1.0f); q[5] = pack_bf16(-bd[1], 1.0f);
      q2[4] = pack_bf16(-bd[2], 1.0f); q2[5] = pack_bf16(-bd[3], 1.0f);
    }
    if (lane == 0 && (warp & 3) == wg && (wg || W1)) KV_LOAD(1 + wg);
    __syncwarp();
    mbar_wait(BAR, 0);
    WG_FENCE();
    QK_MMA(s, dk);
    WG_COMMIT();
#pragma unroll 1
    for (int tile = 0; tile < 2; tile++) {
#pragma unroll 1
      for (int jj = 0; jj < 8; jj++) {
        const uint64_t kd = dk + (uint32_t)(jj * 768), vd = dv + (uint32_t)(jj * 768), kn = dk + (uint32_t)(((jj + 1) & 7) * 768);
        if (tile == 0) {
          if (lane == 0 && (warp == 9 || warp == 14) && 2 * jj + 3 + wg < 16) KV_LOAD(2 * jj + 3 + wg);
          __syncwarp();
          if (!W1) mbar_wait(BAR + jj * 16 + 8, 0);
          if (tid == 0) TS(2, 8 + jj);
        } else if (PFT) {
          if (lane == 0 && (warp == 3 || warp == 4 || warp == 7))
            asm volatile("cp.async.bulk.prefetch.L2.global [%0],%1;" ::"l"((warp == 4 ? wg_ : warp == 3 ? wu : wd) + (bid * 8 + jj) * 5184), "r"(5184) : "memory");
          __syncwarp();
        }
#pragma unroll
        for (int u = 0; u < 4; u++) {
          WG_WAIT(0);
          fence_regs<32>(s);
          softmax_fast(s, p);
          if (W1 && u == 1 && tile == 0) mbar_wait(BAR + jj * 16 + 8, 0);
          if (u == 3 && tile == 0) mbar_wait(BAR + ((jj * 16 + 16) & 127), 0);
          if (u == 3 && jj == 7) {
#pragma unroll
            for (int i = 0; i < 6; i++) q[i] = q2[i];
          }
          WG_FENCE();
          PV_MMA(p, vd + u * 192);
          QK_MMA(s, u < 3 ? kd + u * 192 + 192 : kn);
          WG_COMMIT();
        }
      }
      WG_WAIT(0);
      fence_regs<12>(o);
      att_store(o, row0 + tile * 64, head, lane);
#pragma unroll
      for (int i = 0; i < 12; i++) o[i] = 0.f;
      fence_regs<12>(o);
      if (tid == 0 && tile == 0) TS(2, 3);
    }
  } else {
    if (lane == 0 && warp >= 2 - W1) KV_LOAD(warp);
    __syncwarp();
#pragma unroll 1
    for (int tile = 0; tile < 2; tile++) {
      float m0 = -INFINITY, m1 = -INFINITY;
#pragma unroll 1
      for (int j = 0; j < 32; j++) {
        mbar_wait(BAR + (j >> 1) * 8, 0);
        WG_FENCE();
        QK_MMA(s, dk + (uint32_t)(j * 192));
        WG_COMMIT();
        WG_WAIT(0);
        fence_regs<32>(s);
#pragma unroll
        for (int i = 0; i < 32; i++) if ((POLY_MASK >> (i >> 2)) & 1) s[i] *= 2.0f;
        float x0 = m0, x1 = m1;
#pragma unroll
        for (int i = 0; i < 8; i++) {
          x0 = fmaxf(x0, fmaxf(s[4 * i], s[4 * i + 1]));
          x1 = fmaxf(x1, fmaxf(s[4 * i + 2], s[4 * i + 3]));
        }
        x0 = fmaxf(x0, __shfl_xor_sync(~0u, x0, 1)); x0 = fmaxf(x0, __shfl_xor_sync(~0u, x0, 2));
        x1 = fmaxf(x1, __shfl_xor_sync(~0u, x1, 1)); x1 = fmaxf(x1, __shfl_xor_sync(~0u, x1, 2));
        const float c0 = ex2f(m0 - x0), c1 = ex2f(m1 - x1);
        m0 = x0; m1 = x1;
#pragma unroll
        for (int i = 0; i < 3; i++) { o[4 * i] *= c0; o[4 * i + 1] *= c0; o[4 * i + 2] *= c1; o[4 * i + 3] *= c1; }
#pragma unroll
        for (int i = 0; i < 8; i++) {
          p[2 * i] = pack_bf16(ex2f(s[4 * i] - x0), ex2f(s[4 * i + 1] - x0));
          p[2 * i + 1] = pack_bf16(ex2f(s[4 * i + 2] - x1), ex2f(s[4 * i + 3] - x1));
        }
        WG_FENCE();
        PV_MMA(p, dv + (uint32_t)(j * 192));
        WG_COMMIT();
        WG_WAIT(0);
        fence_regs<12>(o);
      }
      att_store(o, row0 + tile * 64, head, lane);
#pragma unroll
      for (int i = 0; i < 12; i++) o[i] = 0.f;
#pragma unroll
      for (int i = 0; i < 6; i++) q[i] = q2[i];
    }
  }
  if (tid == 0) TS(2, 4);
}

#define K3_SMEM (9 * 16384 + 9 * 9216 + 256)
__device__ __forceinline__ uint32_t res_pair(uint32_t x, uint32_t g, float s0, float s1) { return hadd2(x, hmul2(g, pack_bf16(s0, s1))); }
__global__ void CL3 __launch_bounds__(320, 1) k3_kernel(const __nv_bfloat16* __restrict__ x) {
  extern __shared__ __align__(1024) uint8_t smem_raw[];
  const uint32_t sb = s2u(smem_raw);
  const uint32_t A = sb, B = sb + 9 * 16384, BAR = B + 9 * 9216;
  const int tid = threadIdx.x, lane = tid & 31, warp = tid >> 5;
  const int mb = blockIdx.x >> 3, nb = blockIdx.x & 7;
  if (tid == 0) {
    TS(3, 0);
    if (sb & 1023) __trap();
    for (int i = 0; i < 9; i++) { mbar_init(BAR + i * 8, 1); mbar_expect(BAR + i * 8, 9216 + 16384 + (i == 8 ? 144 : 0)); }
    fence_bar_init();
  }
  if (MC & 2) pair_sync(); else __syncthreads();
  if (warp >= 8) {
    if (tid == 256) {
      const uint32_t t0 = clock();
      for (int s = 0; s < 9; s++) {
        while ((uint32_t)clock() - t0 < (uint32_t)(s * PACEB)) {}
        bulk_g2s(B + s * 9216, g_wo + nb * 5184 + s * 576, 9216, BAR + s * 8);
      }
      TS(0, 2);
    }
    if (tid == 288) {
      pdl_wait();
      pdl_launch();
      TS(0, 3);
      const uint32_t t0 = clock();
      for (int c = nb & 1; c < 18; c += 2) {
        while ((uint32_t)clock() - t0 < (uint32_t)((c >> 1) * PACE3)) {}
        bulk_g2s_mc(A + c * 8192, g_o + (mb * 2 + (c & 1)) * 73728 + (c >> 1) * 8192, 8192, BAR + (c >> 1) * 8);
      }
      bulk_g2s(BAR + 96, g_ga + nb * 72, 144, BAR + 64);
    }
  } else {
    const int g = lane >> 2, cq = lane & 3, wg = warp >> 2;
    const int row = mb * 128 + warp * 16 + g, col = nb * 72 + cq * 2;
    uint32_t xv[20], ga[9];
#define X_LOAD() _Pragma("unroll") for (int i = 0; i < 9; i++) { \
      xv[2 * i] = __ldg((const uint32_t*)(x + (size_t)row * DM + col + 8 * i)); \
      xv[2 * i + 1] = __ldg((const uint32_t*)(x + (size_t)(row + 8) * DM + col + 8 * i)); }
    if (XL < 0) { X_LOAD() }
    float acc[36];
    const uint64_t da = mkdesc(A + wg * 8192, 1024, 128, 0), db = mkdesc(B, 1152, 128, 0);
#pragma unroll 1
    for (int s = 0; s < 9; s++) {
      mbar_wait(BAR + s * 8, 0);
      if (tid == 0) TS(0, 4 + s);
      WG_FENCE();
#pragma unroll
      for (int k = 0; k < 4; k++) wg_ss_n72_t1(acc, da + s * 1024 + k * 128, db + s * 576 + k * 144, s | k);
      WG_COMMIT();
      if (s == XL) { X_LOAD() }
    }
    pdl_launch();
#pragma unroll
    for (int i = 0; i < 9; i++) asm volatile("ld.shared.b32 %0,[%1];" : "=r"(ga[i]) : "r"(BAR + 96 + cq * 4 + i * 16));
    WG_WAIT(0);
    fence_regs<36>(acc);
    if (tid == 0) TS(3, 2);
    bar_sync(1, 256);
    const uint32_t stg = A + wg * 9216 + ((warp & 3) * 16 + g) * 16 + cq * 4;
#pragma unroll
    for (int i = 0; i < 9; i++) {
      xv[2 * i] = res_pair(xv[2 * i], ga[i], acc[4 * i], acc[4 * i + 1]);
      xv[2 * i + 1] = res_pair(xv[2 * i + 1], ga[i], acc[4 * i + 2], acc[4 * i + 3]);
      asm volatile("st.shared.b32 [%0],%1;" ::"r"(stg + i * 1024), "r"(xv[2 * i]) : "memory");
      asm volatile("st.shared.b32 [%0],%1;" ::"r"(stg + i * 1024 + 128), "r"(xv[2 * i + 1]) : "memory");
    }
    fence_async_smem();
    bar_sync(2 + wg, 128);
    if ((tid & 127) == 0) {
      bulk_s2g(g_x1 + (mb * 2 + wg) * 73728 + nb * 9216, A + wg * 9216, 9216);
      bulk_commit();
    }
    xv[18] = xv[19] = 0;
    RowStat rs;
    rs.init();
#pragma unroll
    for (int i = 0; i < 5; i++) rs.add(&xv[4 * i]);
    if (cq == (g >> 1)) {
      g_stat2[row * 8 + nb] = make_float2(rs.s[0], (g & 1) ? rs.q0[1] : rs.q0[0]);
      g_stat2[(row + 8) * 8 + nb] = make_float2(rs.s[2], (g & 1) ? rs.q1[3] : rs.q1[2]);
    }
    if ((tid & 127) == 0) bulk_wait_exit();
    if (tid == 0) TS(3, 3);
  }
}

__device__ __forceinline__ uint4 ln2_consts(int row, int cq) {
  const float4 p = __ldcg((const float4*)(g_stat2 + row * 8 + cq * 2));
  float s = p.x + p.z, q = p.y + p.w;
  s += __shfl_xor_sync(~0u, s, 1); q += __shfl_xor_sync(~0u, q, 1);
  s += __shfl_xor_sync(~0u, s, 2); q += __shfl_xor_sync(~0u, q, 2);
  const float mean = s * (1.0f / DM);
  return ln_consts(mean, fmaxf(q * (1.0f / DM) - mean * mean, 0.f));
}
__device__ __forceinline__ uint8_t* part_ptr(int f, int mb, int p) {
  const int i = f * 16 + mb;
  if (ALIAS && p == 4) return g_o + i * 16384;
  if (ALIAS && (p >> 1) == ALIAS - 1) return g_qkv + (size_t)(i * 2 + (p & 1)) * 32768;
  return g_part + (size_t)(i * 5 + p) * 32768;
}
__device__ __forceinline__ uint32_t glu_pair(float g0, float g1, float u0, float u1) {
  return pack_bf16(fmaf(tanhf_fast(g0), u0, u0), fmaf(tanhf_fast(g1), u1, u1));
}
template <int NG>
__device__ __forceinline__ void stage_part(const float* acc, uint32_t stg, int lane) {
  const int r = (lane & 7) + ((lane >> 3) & 1) * 8;
#pragma unroll
  for (int i = 0; i < NG; i += 2) {
    const int ch = i + (lane >> 4);
    stsm4(stg + r * (NG * 16) + ((ch ^ (r & 7)) << 4), pack_bf16(acc[4 * i], acc[4 * i + 1]), pack_bf16(acc[4 * i + 2], acc[4 * i + 3]),
          pack_bf16(acc[4 * i + 4], acc[4 * i + 5]), pack_bf16(acc[4 * i + 6], acc[4 * i + 7]));
  }
}
__global__ void CL4 __launch_bounds__(384, 1) k4_kernel(const __grid_constant__ CUtensorMap mg,
                                                    const __grid_constant__ CUtensorMap mu, const __grid_constant__ CUtensorMap md,
                                                    __nv_bfloat16* __restrict__ out) {
  extern __shared__ __align__(1024) uint8_t smem_raw[];
  const uint32_t sb = s2u(smem_raw);
  const uint32_t R = sb, RING = sb + R_BYTES, BAR = RING + NSTG * STG_BYTES, TAB = BAR + 512;
  const uint32_t full = BAR, empty = BAR + 64, xfull = BAR + 128, gfull = BAR + 272, sfull = BAR + 320;
  const int tid = threadIdx.x, lane = tid & 31, warp = tid >> 5;
  const int rank = blockIdx.x & 1, mb = MW ? (blockIdx.x >> 4) * 2 + rank : blockIdx.x >> 3, fb = MW ? (blockIdx.x >> 1) & 7 : blockIdx.x & 7;
  if (tid == 0) {
    TS(4, 0);
    if (sb & 1023) __trap();
    for (int i = 0; i < 10; i++) mbar_init(sfull + i * 8, 4);
    for (int i = 0; i < NSTG; i++) { mbar_init(full + i * 8, 1); mbar_init(empty + i * 8, MW ? 16 : 8); }
    for (int i = 0; i < 9; i++) mbar_init(xfull + i * 8, 1);
    for (int i = 0; i < 5; i++) mbar_init(gfull + i * 8, 1);
    mbar_arrive(full);
    for (int i = 0; i < 9; i++) mbar_expect(xfull + i * 8, 16384);
    fence_bar_init();
  }
  if ((MC & 4) || MW) pair_sync(); else __syncthreads();
  if (warp >= 8) {
    REG_DEC(24);
    if (lane == 0) {
      if (warp == 8) {
        int st = 1; uint32_t ph = 0;
        const uint32_t t0 = clock();
        for (int it = 0; it < 126; it++) {
          if (it < 5) while ((uint32_t)clock() - t0 < (uint32_t)(it * PACEW)) {}
          const int t = it / 9, s = it - t * 9;
          const uint32_t dst = RING + st * STG_BYTES, fb_ = full + st * 8;
          mbar_wait(empty + st * 8, ph ^ 1);
          if (MW) {
            mbar_expect(fb_, t < 13 ? 16384 : 8192);
            if (t < 9) tma2d_mc(dst + rank * 8192, rank ? &mu : &mg, fb * 576 + t * 64, s * 64, fb_);
            else if (t < 13) tma2d_mc(dst + rank * 8192, &md, (t - 9) * 128 + rank * 64, fb * 576 + s * 64, fb_);
            else if ((s & 1) == rank) tma2d_mc(dst, &md, 512, fb * 576 + s * 64, fb_);
          } else if (t < 9) {
            mbar_expect(fb_, 16384);
            tma2d(dst, &mg, fb * 576 + t * 64, s * 64, fb_);
            tma2d(dst + 8192, &mu, fb * 576 + t * 64, s * 64, fb_);
          } else {
            mbar_expect(fb_, t < 13 ? 16384 : 8192);
            tma2d(dst, &md, (t - 9) * 128, fb * 576 + s * 64, fb_);
            if (t < 13) tma2d(dst + 8192, &md, (t - 9) * 128 + 64, fb * 576 + s * 64, fb_);
          }
          if (++st == NSTG) { st = 0; ph ^= 1; }
        }
      }
#define GATHER(p)                                                               \
  { unsigned int v; int n = 0;                                                  \
    do { asm volatile("ld.acquire.gpu.global.u32 %0,[%1];" : "=r"(v) : "l"(g_cnt + mb * 5 + (p)) : "memory"); } while (v < 8 && ++n < 20000000); \
    if (v < 8) __trap();                                                        \
    asm volatile("fence.proxy.async.global;" ::: "memory");                     \
    TS(3, 9 + (p));                                                             \
    const uint32_t sz = (p) < 4 ? 4096 : 2048;                                  \
    mbar_expect(gfull + (p) * 8, sz * 8);                                       \
    _Pragma(GU) for (int f = 0; f < 8; f++)                             \
      bulk_g2s((p) < 4 ? R + (p) * 32768 + f * 4096 : RING + (2 + (f >> 2)) * STG_BYTES + 8192 + (f & 3) * 2048, \
               part_ptr(f, mb, p) + fb * sz, sz, gfull + (p) * 8); }
      if (warp < 11) {
#pragma unroll 1
        for (int p = warp == 8 ? 4 : warp - 9; p < 5 - (warp != 8); p += 2) {
          uint8_t* dst = part_ptr(fb, mb, p);
#pragma unroll 1
          for (int wg = 0; wg < 2; wg++) {
            mbar_wait(sfull + (p * 2 + wg) * 8, 0);
            if (p < 4) {
              bulk_s2g(dst + wg * 16384, R + p * 32768 + wg * 8192, 8192);
              bulk_s2g(dst + wg * 16384 + 8192, R + p * 32768 + 16384 + wg * 8192, 8192);
            } else {
              bulk_s2g(dst + wg * 8192, RING + wg * STG_BYTES + 8192, 8192);
            }
          }
          bulk_commit();
          if (p >= 3) TS(3, 11 + p);
          bulk_wait0();
          TS(3, 4 + p);
          asm volatile("fence.proxy.async.global;" ::: "memory");
          asm volatile("red.release.gpu.global.add.u32 [%0],1;" ::"l"(g_cnt + mb * 5 + p) : "memory");
          GATHER(p);
        }
      } else {
        pdl_wait();
        const uint32_t t0 = clock();
        for (int c = 0; c < 9; c++) {
          while ((uint32_t)clock() - t0 < (uint32_t)(c * PACE4)) {}
          const int k = c < 2 ? c : (c == 2 ? 8 : c - 1);
          if (MC & 4) { bulk_g2s_mc(R + k * 16384 + (fb & 1) * 8192, g_x1 + (mb * 2 + (fb & 1)) * 73728 + k * 8192, 8192, xfull + c * 8); continue; }
          bulk_g2s(R + k * 16384, g_x1 + mb * 2 * 73728 + k * 8192, 8192, xfull + c * 8);
          bulk_g2s(R + k * 16384 + 8192, g_x1 + (mb * 2 + 1) * 73728 + k * 8192, 8192, xfull + c * 8);
        }
      }
    }
    if (MW) { __syncwarp(); pair_sync(); }
  } else {
    REG_INC(240);
    [[maybe_unused]] uint32_t emp;
    asm("mapa.shared::cluster.u32 %0,%1,%2;" : "=r"(emp) : "r"(empty), "r"(lane & 1));
    uint32_t a[36][4];
    const int wg = warp >> 2, wl = warp & 3;
    if (tid < 144) sts128(TAB + tid * 16, g_tab2[tid]);
    bar_sync(1, 256);
    pdl_wait();
    TSS(0);
    float acc[64];
    const uint32_t hsp = R + wg * 8192 + (wl * 16 + (lane & 15)) * 16 + (lane >> 4) * 1024;
#define GLU_SPILL(t)                                                            \
  _Pragma("unroll") for (int j = 0; j < 4; j++) {                               \
    uint32_t h[4];                                                              \
    _Pragma("unroll") for (int e = 0; e < 4; e++)                               \
      h[e] = glu_pair(acc[8 * j + 2 * e], acc[8 * j + 2 * e + 1], acc[32 + 8 * j + 2 * e], acc[32 + 8 * j + 2 * e + 1]); \
    asm volatile("st.shared.v4.b32 [%0],{%1,%2,%3,%4};" ::"r"(hsp + (t) * 16384 + j * 2048), "r"(h[0]), "r"(h[1]), "r"(h[2]), "r"(h[3]) : "memory"); \
  }
    {
      const uint4 s0 = ln2_consts(mb * 128 + warp * 16 + (lane >> 2), lane & 3), s1 = ln2_consts(mb * 128 + warp * 16 + (lane >> 2) + 8, lane & 3);
      TSS(1);
      MMA_TILE_(wl_rs_n128_t1, 0, 0,
                if (s < 8) { mbar_wait(xfull + (s + (s > 1)) * 8, 0); LN_CHUNK(s, load_a_core) }
                if (s == 1) { mbar_wait(xfull + 16, 0); LN_CHUNK(8, load_a_core) REL(0); });
    }
    GLU_SPILL(0);
#pragma unroll 1
    for (int t = 0; t < 3; t++) {
      MMA_TILE(wl_rs_n128_t1, 1, t & 1);
      GLU_SPILL(2 * t + 1);
      MMA_TILE(wl_rs_n128_t1, 0, (t & 1) ^ 1);
      GLU_SPILL(2 * t + 2);
    }
    MMA_TILE(wl_rs_n128_t1, 1, 1);
    GLU_SPILL(7);
    MMA_TILE(wl_rs_n128_t1, 0, 0);
#pragma unroll
    for (int j = 0; j < 4; j++)
#pragma unroll
      for (int e = 0; e < 4; e++)
        a[32 + j][e] = glu_pair(acc[8 * j + 2 * e], acc[8 * j + 2 * e + 1], acc[32 + 8 * j + 2 * e], acc[32 + 8 * j + 2 * e + 1]);
#pragma unroll
    for (int k = 0; k < 32; k++)
      asm volatile("ld.shared.v4.b32 {%0,%1,%2,%3},[%4];" : "=r"(a[k][0]), "=r"(a[k][1]), "=r"(a[k][2]), "=r"(a[k][3]) : "r"(hsp + (k >> 2) * 16384 + (k & 3) * 2048) : "memory");
    TSS(2);
    const uint32_t stg = R + (wl >> 1) * 16384 + wg * 8192 + (wl & 1) * 4096;
#define PART_OUT(p)                                                             \
  stage_part<16>(acc, stg + (p) * 32768, lane);                                 \
  fence_async_smem();                                                           \
  __syncwarp();                                                                 \
  if (lane == 0) mbar_arrive(sfull + ((p) * 2 + wg) * 8);
    bar_sync(2 + wg, 128);
#pragma unroll 1
    for (int p = 0; p < 2; p++) {
      MMA_TILE(wl_rs_n128_t1, 1, p);
      PART_OUT(2 * p);
      MMA_TILE(wl_rs_n128_t1, 0, p ^ 1);
      PART_OUT(2 * p + 1);
    }
    MMA_TILE(wl_rs_n64_t1, 1, 0);
    if (MW) { __syncwarp(); asm volatile("barrier.cluster.arrive.relaxed.aligned;" ::: "memory"); }
    stage_part<8>(acc, RING + wg * STG_BYTES + 8192 + wl * 2048, lane);
    fence_async_smem();
    __syncwarp();
    if (lane == 0) mbar_arrive(sfull + (8 + wg) * 8);
    TSS(3);
    const int rl = tid >> 4, ch = tid & 15;
    const size_t off = (size_t)(mb * 128 + fb * 16 + rl) * DM + ch * 8;
    uint4 xv[5], gv[5];
#pragma unroll
    for (int p = 0; p < 5; p++)
      if (p < 4 || ch < 8) { xv[p] = __ldcg((const uint4*)(g_x1 + (mb * 2 + (fb >> 2)) * 73728 + (p * 16 + ch) * 1024 + ((fb & 3) * 16 + rl) * 16)); gv[p] = __ldcg((const uint4*)(g_gb + p * 128 + ch * 8)); }
#pragma unroll
    for (int p = 0; p < 5; p++) {
      if (p == 4 && ch >= 8) break;
      mbar_wait(gfull + p * 8, 0);
      float r8[8] = {0, 0, 0, 0, 0, 0, 0, 0};
#pragma unroll
      for (int f = 0; f < 8; f++) {
        const uint4 v = lds128((p < 4 ? R + p * 32768 + f * 4096 + rl * 256 : RING + (2 + (f >> 2)) * STG_BYTES + 8192 + (f & 3) * 2048 + rl * 128) +
                               ((ch ^ (rl & 7)) << 4));
        r8[0] += bf_lo(v.x); r8[1] += bf_hi(v.x); r8[2] += bf_lo(v.y); r8[3] += bf_hi(v.y);
        r8[4] += bf_lo(v.z); r8[5] += bf_hi(v.z); r8[6] += bf_lo(v.w); r8[7] += bf_hi(v.w);
      }
      uint4 r;
      r.x = res_pair(xv[p].x, gv[p].x, r8[0], r8[1]);
      r.y = res_pair(xv[p].y, gv[p].y, r8[2], r8[3]);
      r.z = res_pair(xv[p].z, gv[p].z, r8[4], r8[5]);
      r.w = res_pair(xv[p].w, gv[p].w, r8[6], r8[7]);
      *(uint4*)(out + off + p * 128) = r;
      if (p >= 2) TSS(2 + p);
    }
    if (MW) { __syncwarp(); asm volatile("barrier.cluster.wait.aligned;" ::: "memory"); }
    TSDUMP(4);
  }
}

typedef CUresult (*EncodeFn)(CUtensorMap*, CUtensorMapDataType, cuuint32_t, void*, const cuuint64_t*, const cuuint64_t*,
                             const cuuint32_t*, const cuuint32_t*, CUtensorMapInterleave, CUtensorMapSwizzle,
                             CUtensorMapL2promotion, CUtensorMapFloatOOBfill);
static void make_map(EncodeFn fn, CUtensorMap* m, const void* p, int rows, int cols, int box_rows, int box_cols = 64) {
  cuuint64_t dims[2] = {(cuuint64_t)cols, (cuuint64_t)rows};
  cuuint64_t strides[1] = {(cuuint64_t)cols * 2};
  cuuint32_t box[2] = {(cuuint32_t)box_cols, (cuuint32_t)box_rows};
  cuuint32_t es[2] = {1, 1};
  fn(m, CU_TENSOR_MAP_DATA_TYPE_BFLOAT16, 2, (void*)p, dims, strides, box, es, CU_TENSOR_MAP_INTERLEAVE_NONE,
     box_cols == 64 ? CU_TENSOR_MAP_SWIZZLE_128B : CU_TENSOR_MAP_SWIZZLE_NONE,
     box_cols == 64 ? CU_TENSOR_MAP_L2_PROMOTION_L2_256B : CU_TENSOR_MAP_L2_PROMOTION_NONE, CU_TENSOR_MAP_FLOAT_OOB_FILL_NONE);
}
template <typename... KA, typename... A>
static void launch(void (*k)(KA...), int grid, int block, int smem, bool pdl, A... args) {
  cudaLaunchConfig_t cfg = {};
  cfg.gridDim = dim3(grid); cfg.blockDim = dim3(block); cfg.dynamicSmemBytes = smem; cfg.stream = cudaStreamPerThread;
  cudaLaunchAttribute at;
  at.id = cudaLaunchAttributeProgrammaticStreamSerialization;
  at.val.programmaticStreamSerializationAllowed = 1;
  cfg.attrs = &at; cfg.numAttrs = pdl ? 1 : 0;
  cudaLaunchKernelEx(&cfg, k, KA(args)...);
}

extern "C" void kernel_launch(void* const* d_in, const int* in_sizes, int n_in, void* d_out, int out_size) {
  const __nv_bfloat16* x = (const __nv_bfloat16*)d_in[0];
  void* fnp = nullptr;
  cudaDriverEntryPointQueryResult qr;
  cudaGetDriverEntryPoint("cuTensorMapEncodeTiled", &fnp, cudaEnableDefault, &qr);
  EncodeFn fn = (EncodeFn)fnp;
  CUtensorMap mm, mx, mqkv, mg, mu, md;
  make_map(fn, &mm, d_in[8], DM, 6 * DM, 192, 16);
  make_map(fn, &mx, x, SEQ, DM, 128);
  make_map(fn, &mqkv, d_in[1], DM, 3 * DM, 64);
  make_map(fn, &mg, d_in[4], DM, FF, 64);
  make_map(fn, &mu, d_in[5], DM, FF, 64);
  make_map(fn, &md, d_in[6], FF, DM, 64);
  cudaFuncSetAttribute(k1_kernel, cudaFuncAttributeMaxDynamicSharedMemorySize, GEMM_SMEM);
  cudaFuncSetAttribute(k2_kernel, cudaFuncAttributeMaxDynamicSharedMemorySize, ATT_SMEM);
  cudaFuncSetAttribute(k3_kernel, cudaFuncAttributeMaxDynamicSharedMemorySize, K3_SMEM);
  cudaFuncSetAttribute(k4_kernel, cudaFuncAttributeMaxDynamicSharedMemorySize, GEMM_SMEM);
  launch(k1_kernel, 128, 384, GEMM_SMEM, false, mx, mqkv, mm, (const __nv_bfloat16*)d_in[7], (const uint8_t*)d_in[1], (const uint4*)d_in[2]);
  launch(k2_kernel, 132, 512, ATT_SMEM, true, (const uint8_t*)d_in[0], (const uint8_t*)d_in[4], (const uint8_t*)d_in[5], (const uint8_t*)d_in[6],
         (const __nv_bfloat16*)d_in[7], (const __nv_bfloat16*)d_in[8]);
  launch(k3_kernel, 128, 320, K3_SMEM, true, x);
  launch(k4_kernel, 128, 384, GEMM_SMEM, true, mg, mu, md, (__nv_bfloat16*)d_out);
}
```

```cpp
#include <cuda_runtime.h>
#include <cuda_bf16.h>
#include <cuda.h>
#include <stdint.h>

#define SEQ 2048
#define DM 576
#define NH 32
#define FF 4608

__device__ uint4 g_ll[36 * 4 * 2];
__device__ uint4 g_tab2[36 * 4];
__device__ __align__(16) __nv_bfloat16 g_ga[DM];
__device__ __align__(16) __nv_bfloat16 g_gb[DM];
__device__ float2 g_stat2[SEQ * 8];
__device__ __align__(1024) uint8_t g_qkv[96 * 98304];
__device__ float g_kmax[NH * 16];
__device__ __align__(1024) uint8_t g_o[SEQ * DM * 2];
__device__ __align__(1024) uint8_t g_x1[SEQ * DM * 2];
__device__ __align__(1024) uint4 g_wo[DM * DM / 8];
__device__ __align__(1024) uint8_t g_part[8 * 16 * 5 * 2 * 16384];
__device__ unsigned int g_cnt[16 * 5];

#define TS(k, i)
#define TSS(i)
#define TSDUMP(k)
__device__ __forceinline__ uint32_t s2u(const void* p) { return (uint32_t)__cvta_generic_to_shared(p); }
__device__ __forceinline__ void mbar_init(uint32_t b, int c) { asm volatile("mbarrier.init.shared::cta.b64 [%0],%1;" ::"r"(b), "r"(c)); }
__device__ __forceinline__ void mbar_expect(uint32_t b, uint32_t n) { asm volatile("mbarrier.arrive.expect_tx.shared::cta.b64 _,[%0],%1;" ::"r"(b), "r"(n) : "memory"); }
__device__ __forceinline__ void mbar_arrive(uint32_t b) { asm volatile("mbarrier.arrive.shared::cta.b64 _,[%0];" ::"r"(b) : "memory"); }
__device__ __forceinline__ void mbar_wait(uint32_t b, uint32_t ph) {
  asm volatile(
      "{.reg .pred p; .reg .u32 n;\n"
      "mbarrier.try_wait.parity.shared::cta.b64 p,[%0],%1;\n"
      "@p bra D;\n"
      "mov.u32 n,0;\n"
      "W: mbarrier.try_wait.parity.shared::cta.b64 p,[%0],%1;\n"
      "@p bra D;\n"
      "add.u32 n,n,1; setp.lt.u32 p,n,4000000; @p bra W;\n"
      "trap;\n"
      "D: }" ::"r"(b), "r"(ph) : "memory");
}
__device__ __forceinline__ void tma2d(uint32_t dst, const CUtensorMap* m, int c0, int c1, uint32_t bar) {
  asm volatile("cp.async.bulk.tensor.2d.shared::cluster.global.mbarrier::complete_tx::bytes [%0],[%1,{%3,%4}],[%2];"
               ::"r"(dst), "l"(m), "r"(bar), "r"(c0), "r"(c1) : "memory");
}
__device__ __forceinline__ void bulk_g2s(uint32_t dst, const void* src, uint32_t bytes, uint32_t bar) {
  asm volatile("cp.async.bulk.shared::cluster.global.mbarrier::complete_tx::bytes [%0],[%1],%2,[%3];"
               ::"r"(dst), "l"(src), "r"(bytes), "r"(bar) : "memory");
}
__device__ __forceinline__ void bulk_s2g(void* dst, uint32_t src, uint32_t bytes) {
  asm volatile("cp.async.bulk.global.shared::cta.bulk_group [%0],[%1],%2;" ::"l"(dst), "r"(src), "r"(bytes) : "memory");
}
__device__ __forceinline__ void bulk_commit() { asm volatile("cp.async.bulk.commit_group;" ::: "memory"); }
__device__ __forceinline__ void bulk_wait0() { asm volatile("cp.async.bulk.wait_group 0;" ::: "memory"); }
__device__ __forceinline__ void prefetch_map(const CUtensorMap* m) { asm volatile("prefetch.tensormap [%0];" ::"l"(m) : "memory"); }
__device__ __forceinline__ void fence_async_smem() { asm volatile("fence.proxy.async.shared::cta;" ::: "memory"); }
__device__ __forceinline__ void bulk_g2s_mc(uint32_t dst, const void* src, uint32_t bytes, uint32_t bar) {
  asm volatile("cp.async.bulk.shared::cluster.global.mbarrier::complete_tx::bytes.multicast::cluster [%0],[%1],%2,[%3],%4;"
               ::"r"(dst), "l"(src), "r"(bytes), "r"(bar), "h"((uint16_t)3) : "memory");
}
__device__ __forceinline__ void tma2d_mc(uint32_t dst, const CUtensorMap* m, int c0, int c1, uint32_t bar) {
  asm volatile("cp.async.bulk.tensor.2d.shared::cluster.global.mbarrier::complete_tx::bytes.multicast::cluster [%0],[%1,{%3,%4}],[%2],%5;"
               ::"r"(dst), "l"(m), "r"(bar), "r"(c0), "r"(c1), "h"((uint16_t)3) : "memory");
}
__device__ __forceinline__ void pair_sync() { asm volatile("barrier.cluster.arrive.relaxed.aligned;\nbarrier.cluster.wait.acquire.aligned;" ::: "memory"); }
#define MC 3
#define CL1 __cluster_dims__(2, 1, 1)
#define CL3 __cluster_dims__(2, 1, 1)
#define CL4
__device__ __forceinline__ void fence_bar_init() { asm volatile("fence.mbarrier_init.release.cluster;" ::: "memory"); }
__device__ __forceinline__ void pdl_wait() { asm volatile("griddepcontrol.wait;" ::: "memory"); }
__device__ __forceinline__ void pdl_launch() { asm volatile("griddepcontrol.launch_dependents;" ::: "memory"); }
__device__ __forceinline__ void bar_sync(int id, int n) { asm volatile("bar.sync %0,%1;" ::"r"(id), "r"(n) : "memory"); }
__device__ __forceinline__ void bar_arrive(int id, int n) { asm volatile("bar.arrive %0,%1;" ::"r"(id), "r"(n) : "memory"); }
#define WG_FENCE() asm volatile("wgmma.fence.sync.aligned;" ::: "memory")
#define WG_COMMIT() asm volatile("wgmma.commit_group.sync.aligned;" ::: "memory")
#define WG_WAIT(n) asm volatile("wgmma.wait_group.sync.aligned " #n ";" ::: "memory")
template <int N> __device__ __forceinline__ void fence_regs(float* r) {
#pragma unroll
  for (int i = 0; i < N; i++) asm volatile("" : "+f"(r[i])::"memory");
}
#define REG_INC(n) asm volatile("setmaxnreg.inc.sync.aligned.u32 " #n ";")
#define REG_DEC(n) asm volatile("setmaxnreg.dec.sync.aligned.u32 " #n ";")
__device__ __forceinline__ uint64_t mkdesc(uint32_t addr, uint32_t lbo, uint32_t sbo, int sw) {
  return (uint64_t)((addr & 0x3FFFF) >> 4) | ((uint64_t)(lbo >> 4) << 16) | ((uint64_t)(sbo >> 4) << 32) | ((uint64_t)sw << 62);
}
__device__ __forceinline__ void ldsm4(uint32_t* r, uint32_t addr) {
  asm volatile("ldmatrix.sync.aligned.m8n8.x4.shared.b16 {%0,%1,%2,%3},[%4];" : "=r"(r[0]), "=r"(r[1]), "=r"(r[2]), "=r"(r[3]) : "r"(addr) : "memory");
}
__device__ __forceinline__ void stsm4(uint32_t addr, uint32_t r0, uint32_t r1, uint32_t r2, uint32_t r3) {
  asm volatile("stmatrix.sync.aligned.m8n8.x4.shared.b16 [%0],{%1,%2,%3,%4};" ::"r"(addr), "r"(r0), "r"(r1), "r"(r2), "r"(r3) : "memory");
}
__device__ __forceinline__ uint32_t pack_bf16(float lo, float hi) {
  uint32_t r;
  asm("cvt.rn.bf16x2.f32 %0,%1,%2;" : "=r"(r) : "f"(hi), "f"(lo));
  return r;
}
__device__ __forceinline__ float bf_lo(uint32_t v) { return __uint_as_float(v << 16); }
__device__ __forceinline__ float bf_hi(uint32_t v) { return __uint_as_float(v & 0xFFFF0000u); }
__device__ __forceinline__ float sq2(uint32_t v) { return bf_lo(v) * bf_lo(v) + bf_hi(v) * bf_hi(v); }
__device__ __forceinline__ float rbf(float x) { return __bfloat162float(__float2bfloat16_rn(x)); }
__device__ __forceinline__ uint32_t hfma2(uint32_t a, uint32_t b, uint32_t c) {
  uint32_t r;
  asm("fma.rn.bf16x2 %0,%1,%2,%3;" : "=r"(r) : "r"(a), "r"(b), "r"(c));
  return r;
}
__device__ __forceinline__ uint32_t hadd2(uint32_t a, uint32_t b) {
  uint32_t r;
  asm("add.rn.bf16x2 %0,%1,%2;" : "=r"(r) : "r"(a), "r"(b));
  return r;
}
__device__ __forceinline__ uint32_t hmul2(uint32_t a, uint32_t b) {
  uint32_t r;
  asm("mul.rn.bf16x2 %0,%1,%2;" : "=r"(r) : "r"(a), "r"(b));
  return r;
}
__device__ __forceinline__ uint32_t hneg2(uint32_t a) {
  uint32_t r;
  asm("neg.bf16x2 %0,%1;" : "=r"(r) : "r"(a));
  return r;
}
__device__ __forceinline__ float ex2f(float x) {
  float r;
  asm("ex2.approx.ftz.f32 %0,%1;" : "=f"(r) : "f"(x));
  return r;
}
__device__ __forceinline__ float sqrt_fast(float x) {
  float r;
  asm("sqrt.approx.f32 %0,%1;" : "=f"(r) : "f"(x));
  return r;
}
__device__ __forceinline__ float rcp_fast(float x) {
  float r;
  asm("rcp.approx.f32 %0,%1;" : "=f"(r) : "f"(x));
  return r;
}
__device__ __forceinline__ float tanhf_fast(float x) {
  float r;
  asm("tanh.approx.f32 %0,%1;" : "=f"(r) : "f"(x));
  return r;
}
__device__ __forceinline__ uint4 ln_consts(float mean, float var) {
  float m = rbf(mean), v = rbf(var);
  float s = rbf(sqrtf(rbf(v + 1e-5f)));
  float r = 1.0f / s;
  float rh = rbf(r), rl = r - rh;
  return make_uint4(pack_bf16(-m, -m), pack_bf16(rh, rh), pack_bf16(rl, rl), 0u);
}
__device__ __forceinline__ uint32_t ln_apply(uint32_t x, const uint4& st, uint32_t a, uint32_t s) {
  uint32_t d = hadd2(x, st.x);
  uint32_t n = hfma2(d, st.y, hmul2(d, st.z));
  return hfma2(n, a, s);
}

__device__ __forceinline__ uint4 lds128(uint32_t a) {
  uint4 v;
  asm volatile("ld.shared.v4.b32 {%0,%1,%2,%3},[%4];" : "=r"(v.x), "=r"(v.y), "=r"(v.z), "=r"(v.w) : "r"(a) : "memory");
  return v;
}
__device__ __forceinline__ void sts128(uint32_t a, const uint4& v) {
  asm volatile("st.shared.v4.b32 [%0],{%1,%2,%3,%4};" ::"r"(a), "r"(v.x), "r"(v.y), "r"(v.z), "r"(v.w) : "memory");
}
__device__ __forceinline__ void hmma(float* c, const uint32_t* a, uint32_t b0, uint32_t b1) {
  asm volatile("mma.sync.aligned.m16n8k16.row.col.f32.bf16.bf16.f32 {%0,%1,%2,%3},{%4,%5,%6,%7},{%8,%9},{%0,%1,%2,%3};"
               : "+f"(c[0]), "+f"(c[1]), "+f"(c[2]), "+f"(c[3]) : "r"(a[0]), "r"(a[1]), "r"(a[2]), "r"(a[3]), "r"(b0), "r"(b1));
}
struct RowStat {
  float s[4], q0[4], q1[4];
  __device__ __forceinline__ void init() {
#pragma unroll
    for (int i = 0; i < 4; i++) s[i] = q0[i] = q1[i] = 0.f;
  }
  __device__ __forceinline__ void add(const uint32_t* a) {
    hmma(s, a, 0x3F803F80u, 0x3F803F80u);
    hmma(q0, a, a[0], a[2]);
    hmma(q1, a, a[1], a[3]);
  }
  __device__ __forceinline__ void merge(const RowStat& o) {
#pragma unroll
    for (int i = 0; i < 4; i++) { s[i] += o.s[i]; q0[i] += o.q0[i]; q1[i] += o.q1[i]; }
  }
  __device__ __forceinline__ void finish(int lane, uint4& c0, uint4& c1) {
    const int g = lane >> 2, src = (lane & ~3) | (g >> 1);
    const float a0 = __shfl_sync(~0u, (g & 1) ? q0[1] : q0[0], src), a1 = __shfl_sync(~0u, (g & 1) ? q1[3] : q1[2], src);
    const float m0 = s[0] * (1.0f / DM), m1 = s[2] * (1.0f / DM);
    c0 = ln_consts(m0, fmaxf(a0 * (1.0f / DM) - m0 * m0, 0.f));
    c1 = ln_consts(m1, fmaxf(a1 * (1.0f / DM) - m1 * m1, 0.f));
  }
};
#define LN_CHUNK(c, LOAD)                                                       \
  LOAD(&a[(c) * 4], R + (c) * 16384, warp * 16, lane);                          \
  _Pragma("unroll") for (int k = (c) * 4; k < (c) * 4 + 4; k++) {               \
    const uint4 t = lds128(TAB + (k * 4 + (lane & 3)) * 16);                    \
    a[k][0] = ln_apply(a[k][0], s0, t.x, t.y);                                  \
    a[k][1] = ln_apply(a[k][1], s1, t.x, t.y);                                  \
    a[k][2] = ln_apply(a[k][2], s0, t.z, t.w);                                  \
    a[k][3] = ln_apply(a[k][3], s1, t.z, t.w);                                  \
  }

__device__ __forceinline__ void wg_ss_n72_t1(float* d, uint64_t da, uint64_t db, int sc) {
  asm volatile("{.reg .pred p; setp.ne.b32 p,%38,0; wgmma.mma_async.sync.aligned.m64n72k16.f32.bf16.bf16 {%0,%1,%2,%3,%4,%5,%6,%7,%8,%9,%10,%11,%12,%13,%14,%15,%16,%17,%18,%19,%20,%21,%22,%23,%24,%25,%26,%27,%28,%29,%30,%31,%32,%33,%34,%35}, %36, %37, p,1,1,0,1;}"
  : "+f"(d[0]),"+f"(d[1]),"+f"(d[2]),"+f"(d[3]),"+f"(d[4]),"+f"(d[5]),"+f"(d[6]),"+f"(d[7]),"+f"(d[8]),"+f"(d[9]),"+f"(d[10]),"+f"(d[11]),"+f"(d[12]),"+f"(d[13]),"+f"(d[14]),"+f"(d[15]),"+f"(d[16]),"+f"(d[17]),"+f"(d[18]),"+f"(d[19]),"+f"(d[20]),"+f"(d[21]),"+f"(d[22]),"+f"(d[23]),"+f"(d[24]),"+f"(d[25]),"+f"(d[26]),"+f"(d[27]),"+f"(d[28]),"+f"(d[29]),"+f"(d[30]),"+f"(d[31]),"+f"(d[32]),"+f"(d[33]),"+f"(d[34]),"+f"(d[35]) : "l"(da),"l"(db),"r"(sc));
}
template <int SC> __device__ __forceinline__ void wl_rs_n128_t1(float* d, const uint32_t* a, uint64_t e) {
  if (SC) asm volatile("wgmma.mma_async.sync.aligned.m64n128k16.f32.bf16.bf16 {%0,%1,%2,%3,%4,%5,%6,%7,%8,%9,%10,%11,%12,%13,%14,%15,%16,%17,%18,%19,%20,%21,%22,%23,%24,%25,%26,%27,%28,%29,%30,%31,%32,%33,%34,%35,%36,%37,%38,%39,%40,%41,%42,%43,%44,%45,%46,%47,%48,%49,%50,%51,%52,%53,%54,%55,%56,%57,%58,%59,%60,%61,%62,%63}, {%64,%65,%66,%67}, %68, 1,1,1,1;"
  : "+f"(d[0]),"+f"(d[1]),"+f"(d[2]),"+f"(d[3]),"+f"(d[4]),"+f"(d[5]),"+f"(d[6]),"+f"(d[7]),"+f"(d[8]),"+f"(d[9]),"+f"(d[10]),"+f"(d[11]),"+f"(d[12]),"+f"(d[13]),"+f"(d[14]),"+f"(d[15]),"+f"(d[16]),"+f"(d[17]),"+f"(d[18]),"+f"(d[19]),"+f"(d[20]),"+f"(d[21]),"+f"(d[22]),"+f"(d[23]),"+f"(d[24]),"+f"(d[25]),"+f"(d[26]),"+f"(d[27]),"+f"(d[28]),"+f"(d[29]),"+f"(d[30]),"+f"(d[31]),"+f"(d[32]),"+f"(d[33]),"+f"(d[34]),"+f"(d[35]),"+f"(d[36]),"+f"(d[37]),"+f"(d[38]),"+f"(d[39]),"+f"(d[40]),"+f"(d[41]),"+f"(d[42]),"+f"(d[43]),"+f"(d[44]),"+f"(d[45]),"+f"(d[46]),"+f"(d[47]),"+f"(d[48]),"+f"(d[49]),"+f"(d[50]),"+f"(d[51]),"+f"(d[52]),"+f"(d[53]),"+f"(d[54]),"+f"(d[55]),"+f"(d[56]),"+f"(d[57]),"+f"(d[58]),"+f"(d[59]),"+f"(d[60]),"+f"(d[61]),"+f"(d[62]),"+f"(d[63]) : "r"(a[0]),"r"(a[1]),"r"(a[2]),"r"(a[3]),"l"(e));
  else asm volatile("wgmma.mma_async.sync.aligned.m64n128k16.f32.bf16.bf16 {%0,%1,%2,%3,%4,%5,%6,%7,%8,%9,%10,%11,%12,%13,%14,%15,%16,%17,%18,%19,%20,%21,%22,%23,%24,%25,%26,%27,%28,%29,%30,%31,%32,%33,%34,%35,%36,%37,%38,%39,%40,%41,%42,%43,%44,%45,%46,%47,%48,%49,%50,%51,%52,%53,%54,%55,%56,%57,%58,%59,%60,%61,%62,%63}, {%64,%65,%66,%67}, %68, 0,1,1,1;"
  : "=f"(d[0]),"=f"(d[1]),"=f"(d[2]),"=f"(d[3]),"=f"(d[4]),"=f"(d[5]),"=f"(d[6]),"=f"(d[7]),"=f"(d[8]),"=f"(d[9]),"=f"(d[10]),"=f"(d[11]),"=f"(d[12]),"=f"(d[13]),"=f"(d[14]),"=f"(d[15]),"=f"(d[16]),"=f"(d[17]),"=f"(d[18]),"=f"(d[19]),"=f"(d[20]),"=f"(d[21]),"=f"(d[22]),"=f"(d[23]),"=f"(d[24]),"=f"(d[25]),"=f"(d[26]),"=f"(d[27]),"=f"(d[28]),"=f"(d[29]),"=f"(d[30]),"=f"(d[31]),"=f"(d[32]),"=f"(d[33]),"=f"(d[34]),"=f"(d[35]),"=f"(d[36]),"=f"(d[37]),"=f"(d[38]),"=f"(d[39]),"=f"(d[40]),"=f"(d[41]),"=f"(d[42]),"=f"(d[43]),"=f"(d[44]),"=f"(d[45]),"=f"(d[46]),"=f"(d[47]),"=f"(d[48]),"=f"(d[49]),"=f"(d[50]),"=f"(d[51]),"=f"(d[52]),"=f"(d[53]),"=f"(d[54]),"=f"(d[55]),"=f"(d[56]),"=f"(d[57]),"=f"(d[58]),"=f"(d[59]),"=f"(d[60]),"=f"(d[61]),"=f"(d[62]),"=f"(d[63]) : "r"(a[0]),"r"(a[1]),"r"(a[2]),"r"(a[3]),"l"(e));
}
template <int SC> __device__ __forceinline__ void wl_rs_n24_t1(float* d, const uint32_t* a, uint64_t e) {
  if (SC) asm volatile("wgmma.mma_async.sync.aligned.m64n24k16.f32.bf16.bf16 {%0,%1,%2,%3,%4,%5,%6,%7,%8,%9,%10,%11}, {%12,%13,%14,%15}, %16, 1,1,1,1;"
  : "+f"(d[0]),"+f"(d[1]),"+f"(d[2]),"+f"(d[3]),"+f"(d[4]),"+f"(d[5]),"+f"(d[6]),"+f"(d[7]),"+f"(d[8]),"+f"(d[9]),"+f"(d[10]),"+f"(d[11]) : "r"(a[0]),"r"(a[1]),"r"(a[2]),"r"(a[3]),"l"(e));
  else asm volatile("wgmma.mma_async.sync.aligned.m64n24k16.f32.bf16.bf16 {%0,%1,%2,%3,%4,%5,%6,%7,%8,%9,%10,%11}, {%12,%13,%14,%15}, %16, 0,1,1,1;"
  : "=f"(d[0]),"=f"(d[1]),"=f"(d[2]),"=f"(d[3]),"=f"(d[4]),"=f"(d[5]),"=f"(d[6]),"=f"(d[7]),"=f"(d[8]),"=f"(d[9]),"=f"(d[10]),"=f"(d[11]) : "r"(a[0]),"r"(a[1]),"r"(a[2]),"r"(a[3]),"l"(e));
}
template <int SC> __device__ __forceinline__ void wl_rs_n64_t0(float* d, const uint32_t* a, uint64_t e) {
  if (SC) asm volatile("wgmma.mma_async.sync.aligned.m64n64k16.f32.bf16.bf16 {%0,%1,%2,%3,%4,%5,%6,%7,%8,%9,%10,%11,%12,%13,%14,%15,%16,%17,%18,%19,%20,%21,%22,%23,%24,%25,%26,%27,%28,%29,%30,%31}, {%32,%33,%34,%35}, %36, 1,1,1,0;"
  : "+f"(d[0]),"+f"(d[1]),"+f"(d[2]),"+f"(d[3]),"+f"(d[4]),"+f"(d[5]),"+f"(d[6]),"+f"(d[7]),"+f"(d[8]),"+f"(d[9]),"+f"(d[10]),"+f"(d[11]),"+f"(d[12]),"+f"(d[13]),"+f"(d[14]),"+f"(d[15]),"+f"(d[16]),"+f"(d[17]),"+f"(d[18]),"+f"(d[19]),"+f"(d[20]),"+f"(d[21]),"+f"(d[22]),"+f"(d[23]),"+f"(d[24]),"+f"(d[25]),"+f"(d[26]),"+f"(d[27]),"+f"(d[28]),"+f"(d[29]),"+f"(d[30]),"+f"(d[31]) : "r"(a[0]),"r"(a[1]),"r"(a[2]),"r"(a[3]),"l"(e));
  else asm volatile("wgmma.mma_async.sync.aligned.m64n64k16.f32.bf16.bf16 {%0,%1,%2,%3,%4,%5,%6,%7,%8,%9,%10,%11,%12,%13,%14,%15,%16,%17,%18,%19,%20,%21,%22,%23,%24,%25,%26,%27,%28,%29,%30,%31}, {%32,%33,%34,%35}, %36, 0,1,1,0;"
  : "=f"(d[0]),"=f"(d[1]),"=f"(d[2]),"=f"(d[3]),"=f"(d[4]),"=f"(d[5]),"=f"(d[6]),"=f"(d[7]),"=f"(d[8]),"=f"(d[9]),"=f"(d[10]),"=f"(d[11]),"=f"(d[12]),"=f"(d[13]),"=f"(d[14]),"=f"(d[15]),"=f"(d[16]),"=f"(d[17]),"=f"(d[18]),"=f"(d[19]),"=f"(d[20]),"=f"(d[21]),"=f"(d[22]),"=f"(d[23]),"=f"(d[24]),"=f"(d[25]),"=f"(d[26]),"=f"(d[27]),"=f"(d[28]),"=f"(d[29]),"=f"(d[30]),"=f"(d[31]) : "r"(a[0]),"r"(a[1]),"r"(a[2]),"r"(a[3]),"l"(e));
}
template <int SC> __device__ __forceinline__ void wl_rs_n64_t1(float* d, const uint32_t* a, uint64_t e) {
  if (SC) asm volatile("wgmma.mma_async.sync.aligned.m64n64k16.f32.bf16.bf16 {%0,%1,%2,%3,%4,%5,%6,%7,%8,%9,%10,%11,%12,%13,%14,%15,%16,%17,%18,%19,%20,%21,%22,%23,%24,%25,%26,%27,%28,%29,%30,%31}, {%32,%33,%34,%35}, %36, 1,1,1,1;"
  : "+f"(d[0]),"+f"(d[1]),"+f"(d[2]),"+f"(d[3]),"+f"(d[4]),"+f"(d[5]),"+f"(d[6]),"+f"(d[7]),"+f"(d[8]),"+f"(d[9]),"+f"(d[10]),"+f"(d[11]),"+f"(d[12]),"+f"(d[13]),"+f"(d[14]),"+f"(d[15]),"+f"(d[16]),"+f"(d[17]),"+f"(d[18]),"+f"(d[19]),"+f"(d[20]),"+f"(d[21]),"+f"(d[22]),"+f"(d[23]),"+f"(d[24]),"+f"(d[25]),"+f"(d[26]),"+f"(d[27]),"+f"(d[28]),"+f"(d[29]),"+f"(d[30]),"+f"(d[31]) : "r"(a[0]),"r"(a[1]),"r"(a[2]),"r"(a[3]),"l"(e));
  else asm volatile("wgmma.mma_async.sync.aligned.m64n64k16.f32.bf16.bf16 {%0,%1,%2,%3,%4,%5,%6,%7,%8,%9,%10,%11,%12,%13,%14,%15,%16,%17,%18,%19,%20,%21,%22,%23,%24,%25,%26,%27,%28,%29,%30,%31}, {%32,%33,%34,%35}, %36, 0,1,1,1;"
  : "=f"(d[0]),"=f"(d[1]),"=f"(d[2]),"=f"(d[3]),"=f"(d[4]),"=f"(d[5]),"=f"(d[6]),"=f"(d[7]),"=f"(d[8]),"=f"(d[9]),"=f"(d[10]),"=f"(d[11]),"=f"(d[12]),"=f"(d[13]),"=f"(d[14]),"=f"(d[15]),"=f"(d[16]),"=f"(d[17]),"=f"(d[18]),"=f"(d[19]),"=f"(d[20]),"=f"(d[21]),"=f"(d[22]),"=f"(d[23]),"=f"(d[24]),"=f"(d[25]),"=f"(d[26]),"=f"(d[27]),"=f"(d[28]),"=f"(d[29]),"=f"(d[30]),"=f"(d[31]) : "r"(a[0]),"r"(a[1]),"r"(a[2]),"r"(a[3]),"l"(e));
}
template <int SC> __device__ __forceinline__ void wl_rs_n88_t1(float* d, const uint32_t* a, uint64_t e) {
  if (SC) asm volatile("wgmma.mma_async.sync.aligned.m64n88k16.f32.bf16.bf16 {%0,%1,%2,%3,%4,%5,%6,%7,%8,%9,%10,%11,%12,%13,%14,%15,%16,%17,%18,%19,%20,%21,%22,%23,%24,%25,%26,%27,%28,%29,%30,%31,%32,%33,%34,%35,%36,%37,%38,%39,%40,%41,%42,%43}, {%44,%45,%46,%47}, %48, 1,1,1,1;"
  : "+f"(d[0]),"+f"(d[1]),"+f"(d[2]),"+f"(d[3]),"+f"(d[4]),"+f"(d[5]),"+f"(d[6]),"+f"(d[7]),"+f"(d[8]),"+f"(d[9]),"+f"(d[10]),"+f"(d[11]),"+f"(d[12]),"+f"(d[13]),"+f"(d[14]),"+f"(d[15]),"+f"(d[16]),"+f"(d[17]),"+f"(d[18]),"+f"(d[19]),"+f"(d[20]),"+f"(d[21]),"+f"(d[22]),"+f"(d[23]),"+f"(d[24]),"+f"(d[25]),"+f"(d[26]),"+f"(d[27]),"+f"(d[28]),"+f"(d[29]),"+f"(d[30]),"+f"(d[31]),"+f"(d[32]),"+f"(d[33]),"+f"(d[34]),"+f"(d[35]),"+f"(d[36]),"+f"(d[37]),"+f"(d[38]),"+f"(d[39]),"+f"(d[40]),"+f"(d[41]),"+f"(d[42]),"+f"(d[43]) : "r"(a[0]),"r"(a[1]),"r"(a[2]),"r"(a[3]),"l"(e));
  else asm volatile("wgmma.mma_async.sync.aligned.m64n88k16.f32.bf16.bf16 {%0,%1,%2,%3,%4,%5,%6,%7,%8,%9,%10,%11,%12,%13,%14,%15,%16,%17,%18,%19,%20,%21,%22,%23,%24,%25,%26,%27,%28,%29,%30,%31,%32,%33,%34,%35,%36,%37,%38,%39,%40,%41,%42,%43}, {%44,%45,%46,%47}, %48, 0,1,1,1;"
  : "=f"(d[0]),"=f"(d[1]),"=f"(d[2]),"=f"(d[3]),"=f"(d[4]),"=f"(d[5]),"=f"(d[6]),"=f"(d[7]),"=f"(d[8]),"=f"(d[9]),"=f"(d[10]),"=f"(d[11]),"=f"(d[12]),"=f"(d[13]),"=f"(d[14]),"=f"(d[15]),"=f"(d[16]),"=f"(d[17]),"=f"(d[18]),"=f"(d[19]),"=f"(d[20]),"=f"(d[21]),"=f"(d[22]),"=f"(d[23]),"=f"(d[24]),"=f"(d[25]),"=f"(d[26]),"=f"(d[27]),"=f"(d[28]),"=f"(d[29]),"=f"(d[30]),"=f"(d[31]),"=f"(d[32]),"=f"(d[33]),"=f"(d[34]),"=f"(d[35]),"=f"(d[36]),"=f"(d[37]),"=f"(d[38]),"=f"(d[39]),"=f"(d[40]),"=f"(d[41]),"=f"(d[42]),"=f"(d[43]) : "r"(a[0]),"r"(a[1]),"r"(a[2]),"r"(a[3]),"l"(e));
}

#define POLY_MASK 0xB5u
#define PFX 9
#define PACE3 330
#define PACE4 400
#define PACEB 250
#define XL -1
#define ALIAS 0
#define P4W 1
#define PFD 0
#define QSCALE (0.23570226039551584f * 1.4426950408889634f)

#define NSTG 6
#define STG_BYTES 16384
#define R_BYTES (8 * 16384)
#define GEMM_SMEM (R_BYTES + NSTG * STG_BYTES + 3072)

__device__ __forceinline__ void load_a_chunk(uint32_t (*a)[4], uint32_t chunk_base, int row_in_tile, int lane) {
  const int r = row_in_tile + (lane & 7) + ((lane >> 3) & 1) * 8;
  const uint32_t rb = chunk_base + r * 128;
#pragma unroll
  for (int k = 0; k < 4; k++) ldsm4(a[k], rb + (((k * 2 + (lane >> 4)) ^ (r & 7)) << 4));
}

__device__ __forceinline__ void load_a_core(uint32_t (*a)[4], uint32_t chunk_base, int row_in_tile, int lane) {
  const uint32_t rb = chunk_base + (row_in_tile >> 6) * 8192 + ((row_in_tile & 63) + (lane & 15)) * 16 + (lane >> 4) * 1024;
#pragma unroll
  for (int k = 0; k < 4; k++) ldsm4(a[k], rb + k * 2048);
}

#define MMA_TILE(FN, ODD, pj) MMA_TILE_(FN, ODD, pj, )
#define MMA_TILE_(FN, ODD, pj, PRE)                                             \
  {                                                                             \
    uint32_t rb_ = (RING & 0x3FFFF) >> 4;                                                 \
    asm volatile("" : "+r"(rb_));                                               \
    const uint64_t db = mkdesc(0, 8192, 1024, 1) + (uint32_t)__shfl_sync(~0u, rb_, 0); \
    _Pragma("unroll") for (int s = 0; s < 9; s++) {                             \
      const int g_ = 1 + (ODD) * 9 + s, st_ = g_ % NSTG;                        \
      PRE;                                                                      \
      mbar_wait(full + st_ * 8, (pj) ^ ((g_ / NSTG) & 1));                      \
      WG_FENCE();                                                               \
      if (s == 0) FN<0>(acc, a[0], db + st_ * 1024); else FN<1>(acc, a[s * 4], db + st_ * 1024); \
      _Pragma("unroll") for (int k = 1; k < 4; k++) FN<1>(acc, a[s * 4 + k], db + st_ * 1024 + k * 128); \
      WG_COMMIT();                                                              \
      if (s > 0) { WG_WAIT(1); if (lane == 0) mbar_arrive(empty + ((g_ - 1) % NSTG) * 8); } \
    }                                                                           \
    WG_WAIT(0);                                                                 \
    if (lane == 0) mbar_arrive(empty + ((9 + (ODD) * 9) % NSTG) * 8);           \
  }

template <int NG, int G0>
__device__ __forceinline__ void qkv_stage(const float* acc, uint32_t stg, int rowl, int cq, int nb) {
  const float vs0 = ((POLY_MASK >> ((rowl >> 3) & 7)) & 1) ? 0.5f : 1.0f, vs1 = ((POLY_MASK >> (((rowl >> 3) + 1) & 7)) & 1) ? 0.5f : 1.0f;
  const uint32_t base = stg + (rowl >> 3) * 384 + (rowl & 7) * 16;
#pragma unroll
  for (int j = 0; j < 9; j++) {
    const int cc = j * 8 + cq * 2, slot = (cc * 3641) >> 16, d = cc - slot * 18;
    const uint32_t ad = base + slot * 6144 + (d >> 3) * 128 + (d & 7) * 2;
#pragma unroll
    for (int per = 0; per < 3; per++) {
      const int i = per * 9 + j - G0, type = (nb * 3 + per) >> 3;
      if (i < 0 || i >= NG) continue;
      const float sc0 = type == 0 ? QSCALE : (type == 1 ? vs0 : 1.0f), sc1 = type == 0 ? QSCALE : (type == 1 ? vs1 : 1.0f);
      asm volatile("st.shared.b32 [%0],%1;" ::"r"(ad + per * 24576), "r"(pack_bf16(acc[4 * i] * sc0, acc[4 * i + 1] * sc0)) : "memory");
      asm volatile("st.shared.b32 [%0],%1;" ::"r"(ad + per * 24576 + 384), "r"(pack_bf16(acc[4 * i + 2] * sc1, acc[4 * i + 3] * sc1)) : "memory");
    }
  }
}

__device__ __forceinline__ float silu_f(float v) { return rbf(__fdividef(v, 1.0f + fminf(__expf(-v), 1e37f))); }
__device__ __forceinline__ float silu_bf(__nv_bfloat16 c) { return silu_f(__bfloat162float(c)); }
__device__ __forceinline__ void fma8(float* acc, float sv, const uint4& w) {
  acc[0] += sv * bf_lo(w.x); acc[1] += sv * bf_hi(w.x); acc[2] += sv * bf_lo(w.y); acc[3] += sv * bf_hi(w.y);
  acc[4] += sv * bf_lo(w.z); acc[5] += sv * bf_hi(w.z); acc[6] += sv * bf_lo(w.w); acc[7] += sv * bf_hi(w.w);
}
__device__ __forceinline__ int tab_pos(int col, int shift) {
  return (((col >> 4) * 4 + ((col & 7) >> 1)) * 4 + ((col >> 3) & 1) * 2 + shift) * 2 + (col & 1);
}
__device__ __forceinline__ float knorm_row(uint32_t slot, int row) {
  const uint32_t ad = slot + (row >> 3) * 384 + (row & 7) * 16;
  const uint4 u = lds128(ad), v = lds128(ad + 128);
  uint32_t w;
  asm volatile("ld.shared.b32 %0,[%1];" : "=r"(w) : "r"(ad + 256) : "memory");
  float q = sq2(u.x) + sq2(u.y) + sq2(u.z) + sq2(u.w) + sq2(v.x) + sq2(v.y) + sq2(v.z) + sq2(v.w) + sq2(w);
  if ((POLY_MASK >> ((row >> 3) & 7)) & 1) q *= 4.0f;
  return q == q ? q : __int_as_float(0x7f800000);
}

__global__ void CL1 __launch_bounds__(384, 1) k1_kernel(const __grid_constant__ CUtensorMap mx, const __grid_constant__ CUtensorMap mw,
                                                    const __grid_constant__ CUtensorMap mm, const __nv_bfloat16* __restrict__ cvec,
                                                    const uint8_t* __restrict__ wqkv, const uint4* __restrict__ wo) {
  extern __shared__ __align__(1024) uint8_t smem_raw[];
  const uint32_t sb = s2u(smem_raw);
  const uint32_t R = sb, RING = sb + R_BYTES, BAR = RING + NSTG * STG_BYTES, TAB = BAR + 512;
  const uint32_t full = BAR, empty = BAR + 64, xfull = BAR + 128;
  const int tid = threadIdx.x, lane = tid & 31, warp = tid >> 5;
  const int mb = blockIdx.x >> 3, nb = blockIdx.x & 7;
  if (tid == 0) TS(1, 0);
  if (tid == 288) { prefetch_map(&mx); prefetch_map(&mw); }
  if (tid == 256) {
    if (sb & 1023) __trap();
    for (int i = 0; i < NSTG; i++) { mbar_init(full + i * 8, 1); mbar_init(empty + i * 8, 8); }
    for (int i = 0; i < 9; i++) mbar_init(xfull + i * 8, 1);
    if (MC & 1) { for (int i = 0; i < 8; i++) mbar_expect(xfull + i * 8, 16384); mbar_expect(full, 16384); }
    fence_bar_init();
    if (blockIdx.x < 72) {
      mbar_expect(xfull + 64, 18432);
      for (int i = 0; i < 3; i++) tma2d(RING + 4 * STG_BYTES + i * 6144, &mm, blockIdx.x * 16, i * 192, xfull + 64);
    }
  }
  if (MC & 1) pair_sync(); else __syncthreads();
  pdl_launch();
  if (MC & 1) {
    if (lane == 0 && warp < 8 && (warp & 1) == (nb & 1)) tma2d_mc(R + warp * 16384, &mx, warp * 64, mb * 128, xfull + warp * 8);
    if (lane == 0 && warp == 1 && !(nb & 1)) tma2d_mc(RING, &mx, 512, mb * 128, full);
  } else if (lane == 0) {
    if (warp < 8) { mbar_expect(xfull + warp * 8, 16384); tma2d(R + warp * 16384, &mx, warp * 64, mb * 128, xfull + warp * 8); }
    if (warp == 1) { mbar_expect(full, 16384); tma2d(RING, &mx, 512, mb * 128, full); }
  }
  __syncwarp();
#define W_FIRST() { asm volatile("cp.async.bulk.prefetch.L2.global [%0],%1;" ::"l"(wqkv + blockIdx.x * 15552), "r"(15552) : "memory"); \
      for (int st = 1; st < 4; st++) { \
        mbar_expect(full + st * 8, 16384); \
        tma2d(RING + st * STG_BYTES, &mw, nb * 216, st * 64 - 64, full + st * 8); \
        tma2d(RING + st * STG_BYTES + 8192, &mw, nb * 216 + 64, st * 64 - 64, full + st * 8); } }
  if (warp >= 8) {
    REG_DEC(24);
    const int pt = tid - 256;
    if (PFD < 0 && pt == 0) W_FIRST();
    if (blockIdx.x < 72) {
      float* sf = (float*)(smem_raw + R_BYTES + 4 * STG_BYTES + 18432);
      if (pt < 72) {
        const uint4 cv = __ldg((const uint4*)cvec + pt);
        const uint32_t cw[4] = {cv.x, cv.y, cv.z, cv.w};
#pragma unroll
        for (int i = 0; i < 4; i++) { sf[pt * 8 + 2 * i] = silu_f(bf_lo(cw[i])); sf[pt * 8 + 2 * i + 1] = silu_f(bf_hi(cw[i])); }
      }
      bar_sync(3, 128);
      mbar_wait(xfull + 64, 0);
      float acc[8] = {0, 0, 0, 0, 0, 0, 0, 0};
#pragma unroll 1
      for (int i = 0; i < 9; i++) fma8(acc, sf[(pt >> 1) + 64 * i], lds128(RING + 4 * STG_BYTES + i * 2048 + pt * 16));
#pragma unroll
      for (int j = 0; j < 8; j++)
#pragma unroll
        for (int o = 2; o < 32; o *= 2) acc[j] += __shfl_xor_sync(~0u, acc[j], o);
      if (lane < 2) {
#pragma unroll
        for (int j = 0; j < 8; j++) sf[DM + (warp - 8) * 16 + lane * 8 + j] = acc[j];
      }
      bar_sync(3, 128);
      if (pt < 16) {
        const float v = rbf(sf[DM + pt] + sf[DM + 16 + pt] + sf[DM + 32 + pt] + sf[DM + 48 + pt]);
        const int n = blockIdx.x * 16 + pt, shift = n < DM;
        const uint32_t word = pack_bf16(shift ? v : 1.0f + v, 1.0f);
        asm volatile("st.relaxed.gpu.global.u32 [%0],%1;" ::"l"((uint32_t*)g_ll + tab_pos(shift ? n : n - DM, shift)), "r"(word) : "memory");
      }
      fence_async_smem();
      __syncwarp();
      if (pt == 0) TS(0, 1);
    }
    if (warp == 8) {
      if (lane == 0) {
        int st = 4; uint32_t ph = 0;
        for (int it = 3; it < 18; it++) {
          const int t = it / 9, s = it - t * 9;
          mbar_wait(empty + st * 8, ph ^ 1);
          mbar_expect(full + st * 8, 16384);
          tma2d(RING + st * STG_BYTES, &mw, nb * 216 + t * 128, s * 64, full + st * 8);
          tma2d(RING + st * STG_BYTES + 8192, &mw, nb * 216 + t * 128 + 64, s * 64, full + st * 8);
          if (++st == NSTG) { st = 0; ph ^= 1; }
        }
      }
    } else {
      const int ht = tid - 288;
      mbar_wait(full, 0);
#pragma unroll 2
      for (int j = ht; j < 324; j += 96) {
        const int i = blockIdx.x * 324 + j, k = i / 72, n8 = i - k * 72;
        g_wo[(n8 / 9) * 5184 + (k >> 3) * 72 + (n8 % 9) * 8 + (k & 7)] = __ldg(wo + i);
      }
      bar_sync(1, 352);
      for (int i = ht; i < 12 * 128; i += 96) {
        const int slot = i >> 7, row = i & 127, type = (nb * 12 + slot) >> 5;
        uint32_t v = 0;
        if (type == 1) v = ((POLY_MASK >> ((row >> 3) & 7)) & 1) ? 0x43403F00u : 0x40253F80u;
        if (type == 2) v = 0x3F80u;
        const uint32_t ad = R + slot * 6144 + (row >> 3) * 384 + 256 + (row & 7) * 16;
        asm volatile("st.shared.b32 [%0],%1;" ::"r"(ad + 4), "r"(v) : "memory");
        asm volatile("st.shared.v2.b32 [%0],{%1,%1};" ::"r"(ad + 8), "r"(0) : "memory");
      }
      fence_async_smem();
      bar_sync(2, 352);
      if (ht == 0) {
        for (int s = 0; s < 7; s++) bulk_s2g(g_qkv + (size_t)(nb * 12 + s) * 98304 + mb * 6144, R + s * 6144, 6144);
        bulk_commit();
      }
      for (int s = warp - 9; s < 7; s += 3) {
        const int gs = nb * 12 + s;
        if ((gs >> 5) != 1) continue;
        float mx2 = 0;
#pragma unroll 1
        for (int row = lane; row < 128; row += 32) mx2 = fmaxf(mx2, knorm_row(R + s * 6144, row));
#pragma unroll
        for (int o = 16; o; o >>= 1) mx2 = fmaxf(mx2, __shfl_xor_sync(~0u, mx2, o));
        if (lane == 0) g_kmax[(gs & 31) * 16 + mb] = mx2;
      }
      if (ht == 0) bulk_wait0();
    }
  } else {
    REG_INC(240);
    TSS(0);
    const int rowl = warp * 16;
    uint4 s0, s1;
    {
      RowStat rs, rt;
      rs.init(); rt.init();
      uint32_t f[4][4];
#pragma unroll 1
      for (int c = 0; c < 9; c++) {
        mbar_wait(c < 8 ? xfull + c * 8 : full, 0);
        if (c == PFD && tid == 224) W_FIRST();
        __syncwarp();
        load_a_chunk(f, R + c * 16384, rowl, lane);
        rs.add(f[0]); rt.add(f[1]); rs.add(f[2]); rt.add(f[3]);
      }
      rs.merge(rt);
      rs.finish(lane, s0, s1);
    }
    TSS(1);
    if (tid < 144) {
      uint4 u, v;
      int n = 0;
      do {
        asm volatile("ld.relaxed.gpu.global.v4.u32 {%0,%1,%2,%3},[%4];" : "=r"(u.x), "=r"(u.y), "=r"(u.z), "=r"(u.w) : "l"(g_ll + tid * 2) : "memory");
        asm volatile("ld.relaxed.gpu.global.v4.u32 {%0,%1,%2,%3},[%4];" : "=r"(v.x), "=r"(v.y), "=r"(v.z), "=r"(v.w) : "l"(g_ll + tid * 2 + 1) : "memory");
        if (++n > 4000000) __trap();
      } while (((u.x & u.y & u.z & u.w & v.x & v.y & v.z & v.w) >> 16) != 0x3F80u);
      sts128(TAB + tid * 16, make_uint4(__byte_perm(u.x, u.y, 0x5410), __byte_perm(u.z, u.w, 0x5410), __byte_perm(v.x, v.y, 0x5410), __byte_perm(v.z, v.w, 0x5410)));
    }
    bar_sync(4, 256);
    TSS(2);
    uint32_t a[36][4];
    float acc[64];
    MMA_TILE_(wl_rs_n128_t1, 0, 0, if (s < 8) { LN_CHUNK(s, load_a_chunk) } if (s == 1) { LN_CHUNK(8, load_a_chunk) if (lane == 0) mbar_arrive(empty); } if (s == 5) bar_arrive(1, 352));
    TSS(3);
    bar_sync(4, 256);
    int t2 = threadIdx.x;
    asm volatile("" : "+r"(t2));
    qkv_stage<16, 0>(acc, R, (t2 >> 5) * 16 + ((t2 & 31) >> 2), t2 & 3, nb);
    fence_async_smem();
    bar_arrive(2, 352);
    TSS(4);
    MMA_TILE(wl_rs_n88_t1, 1, 0);
    asm volatile("" : "+r"(t2));
    qkv_stage<11, 16>(acc, R, (t2 >> 5) * 16 + ((t2 & 31) >> 2), t2 & 3, nb);
    fence_async_smem();
    bar_sync(4, 256);
    TSS(5);
    if (tid == 0) {
      for (int s = 7; s < 12; s++) bulk_s2g(g_qkv + (size_t)(nb * 12 + s) * 98304 + mb * 6144, R + s * 6144, 6144);
      bulk_commit();
    }
    if (warp >= 3 && ((nb * 12 + 4 + warp) >> 5) == 1) {
      float mx2 = 0;
#pragma unroll
      for (int i = 0; i < 4; i++) mx2 = fmaxf(mx2, knorm_row(R + (4 + warp) * 6144, lane + 32 * i));
#pragma unroll
      for (int o = 16; o; o >>= 1) mx2 = fmaxf(mx2, __shfl_xor_sync(~0u, mx2, o));
      if (lane == 0) g_kmax[((nb * 12 + 4 + warp) & 31) * 16 + mb] = mx2;
    }
    if (tid == 0) bulk_wait0();
    TSS(6);
    TSDUMP(1);
  }
}

#define ATT_SMEM (2 * 98304 + 1024 + 256)

__device__ __forceinline__ uint32_t exp2_pair_fma(float t0, float t1) {
  uint32_t y;
  asm("prmt.b32 %0,%1,%2,0x6521;" : "=r"(y) : "r"(__float_as_uint(t0)), "r"(__float_as_uint(t1)));
  return hfma2(y, y | 0x3F803F80u, y | 0x007F007Fu);
}

__device__ __forceinline__ void softmax_fast(const float* s, uint32_t* p) {
#pragma unroll
  for (int i = 0; i < 8; i++) {
    if ((POLY_MASK >> i) & 1) {
      p[2 * i] = exp2_pair_fma(s[4 * i], s[4 * i + 1]);
      p[2 * i + 1] = exp2_pair_fma(s[4 * i + 2], s[4 * i + 3]);
    } else {
      p[2 * i] = pack_bf16(ex2f(s[4 * i]), ex2f(s[4 * i + 1]));
      p[2 * i + 1] = pack_bf16(ex2f(s[4 * i + 2]), ex2f(s[4 * i + 3]));
    }
  }
}
#define QK_MMA(S, kd)                                                           \
  wl_rs_n64_t0<0>(S, q, (kd));                                                  \
  wl_rs_n64_t0<1>(S, q + 4, (kd) + 16 - (8ull << 16));
#define PV_MMA(P, vd)                                                           \
  _Pragma("unroll") for (int t = 0; t < 4; t++) wl_rs_n24_t1<1>(o, P + 4 * t, (vd) + t * 48);

__device__ __forceinline__ void att_store(const float* o, int row0, int head, int lane) {
  const int cq = lane & 3;
  const float l0 = __shfl_sync(~0u, o[8], (lane & ~3) | 1), l1 = __shfl_sync(~0u, o[10], (lane & ~3) | 1);
  const float i0 = rcp_fast(l0), i1 = rcp_fast(l1);
  const int col = head * 18 + cq * 2;
  uint32_t* og = (uint32_t*)(g_o + (row0 >> 6) * 73728 + (col >> 3) * 1024 + (row0 & 63) * 16 + (col & 7) * 2);
  og[0] = pack_bf16(o[0] * i0, o[1] * i0);
  og[256] = pack_bf16(o[4] * i0, o[5] * i0);
  og[32] = pack_bf16(o[2] * i1, o[3] * i1);
  og[256 + 32] = pack_bf16(o[6] * i1, o[7] * i1);
  if (cq == 0) {
    og[512] = pack_bf16(o[8] * i0, o[9] * i0);
    og[512 + 32] = pack_bf16(o[10] * i1, o[11] * i1);
  }
}

__global__ void __launch_bounds__(512, 1) k2_kernel(const uint8_t* __restrict__ xin, const uint8_t* __restrict__ wg_, const uint8_t* __restrict__ wu,
                                                    const uint8_t* __restrict__ wd, const __nv_bfloat16* __restrict__ cvec,
                                                    const __nv_bfloat16* __restrict__ wmod) {
  extern __shared__ __align__(1024) uint8_t smem_raw[];
  const uint32_t sb = (s2u(smem_raw) + 1023) & ~1023u;
  const uint32_t KS = sb, VS = sb + 98304, BAR = sb + 2 * 98304;
  const int tid = threadIdx.x, lane = tid & 31, warp = tid >> 5, wg = tid >> 7;
  if (blockIdx.x < 4) {
    float* sf = (float*)smem_raw;
    const int part = blockIdx.x + 2;
    for (int i = tid; i < DM; i += 512) sf[i] = silu_bf(cvec[i]);
    if (part == 2 && tid < 80) g_cnt[tid] = 0;
    __nanosleep(4000);
    __syncthreads();
    if (tid < 432) {
      const int cg = tid % 72, rg = tid / 72;
      const __nv_bfloat16* w = wmod + (size_t)rg * 96 * 3456 + part * DM + cg * 8;
      float acc[8] = {0, 0, 0, 0, 0, 0, 0, 0};
#pragma unroll 1
      for (int r = 0; r < 96; r += 12) {
        uint4 v[12];
#pragma unroll
        for (int i = 0; i < 12; i++) v[i] = __ldg((const uint4*)(w + (size_t)(r + i) * 3456));
#pragma unroll
        for (int i = 0; i < 12; i++) fma8(acc, sf[rg * 96 + r + i], v[i]);
      }
#pragma unroll
      for (int j = 0; j < 8; j++) sf[DM + rg * DM + cg * 8 + j] = acc[j];
    }
    __syncthreads();
    for (int col = tid; col < DM; col += 512) {
      float v = 0;
#pragma unroll
      for (int j = 1; j < 7; j++) v += sf[j * DM + col];
      v = rbf(v);
      if (part == 2) g_ga[col] = __float2bfloat16_rn(v);
      else if (part == 5) g_gb[col] = __float2bfloat16_rn(v);
      else ((__nv_bfloat16*)g_tab2)[tab_pos(col, part == 3)] = __float2bfloat16_rn(0.5f * (part == 3 ? v : rbf(1.0f + v)));
    }
    pdl_wait();
    if (part == 2 && tid < 288) g_ll[tid] = make_uint4(0, 0, 0, 0);
    if (tid == 0) TS(0, 0);
    return;
  }
  const int bid = blockIdx.x - 4, head = bid >> 2, qb = bid & 3;
  if (tid == 0) {
    TS(2, 0);
    for (int i = 0; i < 16; i++) mbar_init(BAR + i * 8, 1);
    fence_bar_init();
  }
  __syncthreads();
  const int g = lane >> 2, cq = lane & 3;
  const int row0 = qb * 512 + wg * 128 + (warp & 3) * 16 + g;
  const uint8_t* qg = g_qkv + (size_t)head * 98304 + (row0 >> 3) * 384 + (row0 & 7) * 16 + cq * 4;
  pdl_wait();
  pdl_launch();
  if (tid == 0) TS(2, 1);
  const uint8_t* kg = g_qkv + (size_t)(32 + head) * 98304;
#define KV_LOAD(c) { mbar_expect(BAR + (c) * 8, 12288); bulk_g2s(KS + (c) * 6144, kg + (c) * 6144, 6144, BAR + (c) * 8); \
                     bulk_g2s(VS + (c) * 6144, kg + 32 * 98304 + (c) * 6144, 6144, BAR + (c) * 8); }
  if (lane == 0 && warp < 2) KV_LOAD(warp);
  __syncwarp();
  uint32_t q[8], q2[6];
  float kmax2 = __ldcg(g_kmax + head * 16 + (lane & 15));
#pragma unroll
  for (int i = 0; i < 6; i++) {
    q[i] = __ldcg((const uint32_t*)(qg + (i & 1) * 384 + (i >> 1) * 128));
    q2[i] = __ldcg((const uint32_t*)(qg + 3072 + (i & 1) * 384 + (i >> 1) * 128));
  }
  q[6] = __ldcg((const uint32_t*)(qg + 256 + 12 - cq * 4)); q[7] = __ldcg((const uint32_t*)(qg + 256 + 8 - cq * 4));
  const uint64_t dk = mkdesc(KS, 128, 384, 0), dv = mkdesc(VS, 384, 128, 0);
#pragma unroll
  for (int o = 8; o; o >>= 1) kmax2 = fmaxf(kmax2, __shfl_xor_sync(~0u, kmax2, o));
  float bd[4] = {sq2(q[0]) + sq2(q[2]) + sq2(q[4]), sq2(q[1]) + sq2(q[3]) + sq2(q[5]),
                 sq2(q2[0]) + sq2(q2[2]) + sq2(q2[4]), sq2(q2[1]) + sq2(q2[3]) + sq2(q2[5])};
  int ok = 1;
  if (tid == 0 && bd[0] + bd[3] + kmax2 != 1.2345f) TS(2, 5);
#pragma unroll
  for (int i = 0; i < 4; i++) {
    bd[i] += __shfl_xor_sync(~0u, bd[i], 1); bd[i] += __shfl_xor_sync(~0u, bd[i], 2);
    bd[i] = sqrt_fast(bd[i] * kmax2) * 1.01f + 1.0f;
    ok = ok && (bd[i] <= 62.0f);
  }
  {
    uint32_t all;
    asm volatile("{.reg .pred p,q; setp.ne.b32 p,%1,0; barrier.red.and.pred q,1,512,p; selp.u32 %0,1,0,q;}"
                 : "=r"(all) : "r"(ok) : "memory");
    ok = __all_sync(~0u, all);
  }
  float o[12];
#pragma unroll
  for (int i = 0; i < 12; i++) { o[i] = 0.f; asm volatile("" : "+f"(o[i])); }
  float s[32];
  uint32_t p[16];
  if (tid == 0) TS(2, 2);
  if (ok) {
    if (cq == 1) {
      q[4] = pack_bf16(-bd[0], 1.0f); q[5] = pack_bf16(-bd[1], 1.0f);
      q2[4] = pack_bf16(-bd[2], 1.0f); q2[5] = pack_bf16(-bd[3], 1.0f);
    }
    if (lane == 0 && (warp & 3) == wg && wg) KV_LOAD(1 + wg);
    __syncwarp();
    mbar_wait(BAR, 0);
    WG_FENCE();
    QK_MMA(s, dk);
    WG_COMMIT();
#pragma unroll 1
    for (int tile = 0; tile < 2; tile++) {
#pragma unroll 1
      for (int jj = 0; jj < 8; jj++) {
        const uint64_t kd = dk + (uint32_t)(jj * 768), vd = dv + (uint32_t)(jj * 768), kn = dk + (uint32_t)(((jj + 1) & 7) * 768);
        if (tile == 0) {
          if (lane == 0 && (warp == 9 || warp == 14) && 2 * jj + 3 + wg < 16) KV_LOAD(2 * jj + 3 + wg);
          if (lane == 0 && (warp == 3 || warp == 4 || warp == 7))
            asm volatile("cp.async.bulk.prefetch.L2.global [%0],%1;" ::"l"((warp == 4 ? wg_ : warp == 3 ? wu : wd) + (bid * 8 + jj) * 5184), "r"(5184) : "memory");
          __syncwarp();
          mbar_wait(BAR + jj * 16 + 8, 0); if (tid == 0) TS(2, 8 + jj);
        } else if (jj == PFX) {
          if (tid == 96) asm volatile("cp.async.bulk.prefetch.L2.global [%0],%1;" ::"l"(xin + bid * 18432), "r"(18432) : "memory");
          if (tid == 160) asm volatile("cp.async.bulk.prefetch.L2.global [%0],%1;" ::"l"(g_wo + bid * 324), "r"(5184) : "memory");
          __syncwarp();
        }
#pragma unroll
        for (int u = 0; u < 4; u++) {
          WG_WAIT(0);
          fence_regs<32>(s);
          softmax_fast(s, p);
          if (u == 3 && tile == 0) mbar_wait(BAR + ((jj * 16 + 16) & 127), 0);
          if (u == 3 && jj == 7) {
#pragma unroll
            for (int i = 0; i < 6; i++) q[i] = q2[i];
          }
          WG_FENCE();
          PV_MMA(p, vd + u * 192);
          QK_MMA(s, u < 3 ? kd + u * 192 + 192 : kn);
          WG_COMMIT();
        }
      }
      WG_WAIT(0);
      fence_regs<12>(o);
      att_store(o, row0 + tile * 64, head, lane);
#pragma unroll
      for (int i = 0; i < 12; i++) o[i] = 0.f;
      fence_regs<12>(o);
      if (tid == 0 && tile == 0) TS(2, 3);
    }
  } else {
    if (lane == 0 && warp >= 2) KV_LOAD(warp);
    __syncwarp();
#pragma unroll 1
    for (int tile = 0; tile < 2; tile++) {
      float m0 = -INFINITY, m1 = -INFINITY;
#pragma unroll 1
      for (int j = 0; j < 32; j++) {
        mbar_wait(BAR + (j >> 1) * 8, 0);
        WG_FENCE();
        QK_MMA(s, dk + (uint32_t)(j * 192));
        WG_COMMIT();
        WG_WAIT(0);
        fence_regs<32>(s);
#pragma unroll
        for (int i = 0; i < 32; i++) if ((POLY_MASK >> (i >> 2)) & 1) s[i] *= 2.0f;
        float x0 = m0, x1 = m1;
#pragma unroll
        for (int i = 0; i < 8; i++) {
          x0 = fmaxf(x0, fmaxf(s[4 * i], s[4 * i + 1]));
          x1 = fmaxf(x1, fmaxf(s[4 * i + 2], s[4 * i + 3]));
        }
        x0 = fmaxf(x0, __shfl_xor_sync(~0u, x0, 1)); x0 = fmaxf(x0, __shfl_xor_sync(~0u, x0, 2));
        x1 = fmaxf(x1, __shfl_xor_sync(~0u, x1, 1)); x1 = fmaxf(x1, __shfl_xor_sync(~0u, x1, 2));
        const float c0 = ex2f(m0 - x0), c1 = ex2f(m1 - x1);
        m0 = x0; m1 = x1;
#pragma unroll
        for (int i = 0; i < 3; i++) { o[4 * i] *= c0; o[4 * i + 1] *= c0; o[4 * i + 2] *= c1; o[4 * i + 3] *= c1; }
#pragma unroll
        for (int i = 0; i < 8; i++) {
          p[2 * i] = pack_bf16(ex2f(s[4 * i] - x0), ex2f(s[4 * i + 1] - x0));
          p[2 * i + 1] = pack_bf16(ex2f(s[4 * i + 2] - x1), ex2f(s[4 * i + 3] - x1));
        }
        WG_FENCE();
        PV_MMA(p, dv + (uint32_t)(j * 192));
        WG_COMMIT();
        WG_WAIT(0);
        fence_regs<12>(o);
      }
      att_store(o, row0 + tile * 64, head, lane);
#pragma unroll
      for (int i = 0; i < 12; i++) o[i] = 0.f;
#pragma unroll
      for (int i = 0; i < 6; i++) q[i] = q2[i];
    }
  }
  if (tid == 0) TS(2, 4);
}

#define K3_SMEM (9 * 16384 + 9 * 9216 + 256)
__device__ __forceinline__ uint32_t res_pair(uint32_t x, uint32_t g, float s0, float s1) { return hadd2(x, hmul2(g, pack_bf16(s0, s1))); }
__global__ void CL3 __launch_bounds__(320, 1) k3_kernel(const __nv_bfloat16* __restrict__ x) {
  extern __shared__ __align__(1024) uint8_t smem_raw[];
  const uint32_t sb = s2u(smem_raw);
  const uint32_t A = sb, B = sb + 9 * 16384, BAR = B + 9 * 9216;
  const int tid = threadIdx.x, lane = tid & 31, warp = tid >> 5;
  const int mb = blockIdx.x >> 3, nb = blockIdx.x & 7;
  if (tid == 0) {
    TS(3, 0);
    if (sb & 1023) __trap();
    for (int i = 0; i < 9; i++) { mbar_init(BAR + i * 8, 1); mbar_expect(BAR + i * 8, 9216 + 16384 + (i == 8 ? 144 : 0)); }
    fence_bar_init();
  }
  if (MC & 2) pair_sync(); else __syncthreads();
  if (warp >= 8) {
    if (tid == 256) {
      const uint32_t t0 = clock();
      for (int s = 0; s < 9; s++) {
        while ((uint32_t)clock() - t0 < (uint32_t)(s * PACEB)) {}
        bulk_g2s(B + s * 9216, g_wo + nb * 5184 + s * 576, 9216, BAR + s * 8);
      }
      TS(0, 2);
    }
    if (tid == 288) {
      pdl_wait();
      pdl_launch();
      TS(0, 3);
      const uint32_t t0 = clock();
      for (int c = nb & 1; c < 18; c += 2) {
        while ((uint32_t)clock() - t0 < (uint32_t)((c >> 1) * PACE3)) {}
        bulk_g2s_mc(A + c * 8192, g_o + (mb * 2 + (c & 1)) * 73728 + (c >> 1) * 8192, 8192, BAR + (c >> 1) * 8);
      }
      bulk_g2s(BAR + 96, g_ga + nb * 72, 144, BAR + 64);
    }
  } else {
    const int g = lane >> 2, cq = lane & 3, wg = warp >> 2;
    const int row = mb * 128 + warp * 16 + g, col = nb * 72 + cq * 2;
    uint32_t xv[20], ga[9];
#define X_LOAD() _Pragma("unroll") for (int i = 0; i < 9; i++) { \
      xv[2 * i] = __ldg((const uint32_t*)(x + (size_t)row * DM + col + 8 * i)); \
      xv[2 * i + 1] = __ldg((const uint32_t*)(x + (size_t)(row + 8) * DM + col + 8 * i)); }
    if (XL < 0) { X_LOAD() }
    float acc[36];
    const uint64_t da = mkdesc(A + wg * 8192, 1024, 128, 0), db = mkdesc(B, 1152, 128, 0);
#pragma unroll 1
    for (int s = 0; s < 9; s++) {
      mbar_wait(BAR + s * 8, 0);
      if (tid == 0) TS(0, 4 + s);
      WG_FENCE();
#pragma unroll
      for (int k = 0; k < 4; k++) wg_ss_n72_t1(acc, da + s * 1024 + k * 128, db + s * 576 + k * 144, s | k);
      WG_COMMIT();
      if (s == XL) { X_LOAD() }
    }
    pdl_launch();
#pragma unroll
    for (int i = 0; i < 9; i++) asm volatile("ld.shared.b32 %0,[%1];" : "=r"(ga[i]) : "r"(BAR + 96 + cq * 4 + i * 16));
    WG_WAIT(0);
    fence_regs<36>(acc);
    if (tid == 0) TS(3, 2);
    bar_sync(1, 256);
    const uint32_t stg = A + wg * 9216 + ((warp & 3) * 16 + g) * 16 + cq * 4;
#pragma unroll
    for (int i = 0; i < 9; i++) {
      xv[2 * i] = res_pair(xv[2 * i], ga[i], acc[4 * i], acc[4 * i + 1]);
      xv[2 * i + 1] = res_pair(xv[2 * i + 1], ga[i], acc[4 * i + 2], acc[4 * i + 3]);
      asm volatile("st.shared.b32 [%0],%1;" ::"r"(stg + i * 1024), "r"(xv[2 * i]) : "memory");
      asm volatile("st.shared.b32 [%0],%1;" ::"r"(stg + i * 1024 + 128), "r"(xv[2 * i + 1]) : "memory");
    }
    fence_async_smem();
    bar_sync(2 + wg, 128);
    if ((tid & 127) == 0) {
      bulk_s2g(g_x1 + (mb * 2 + wg) * 73728 + nb * 9216, A + wg * 9216, 9216);
      bulk_commit();
    }
    xv[18] = xv[19] = 0;
    RowStat rs;
    rs.init();
#pragma unroll
    for (int i = 0; i < 5; i++) rs.add(&xv[4 * i]);
    if (cq == (g >> 1)) {
      g_stat2[row * 8 + nb] = make_float2(rs.s[0], (g & 1) ? rs.q0[1] : rs.q0[0]);
      g_stat2[(row + 8) * 8 + nb] = make_float2(rs.s[2], (g & 1) ? rs.q1[3] : rs.q1[2]);
    }
    if ((tid & 127) == 0) bulk_wait0();
    if (tid == 0) TS(3, 3);
  }
}

__device__ __forceinline__ uint4 ln2_consts(int row, int cq) {
  const float4 p = __ldcg((const float4*)(g_stat2 + row * 8 + cq * 2));
  float s = p.x + p.z, q = p.y + p.w;
  s += __shfl_xor_sync(~0u, s, 1); q += __shfl_xor_sync(~0u, q, 1);
  s += __shfl_xor_sync(~0u, s, 2); q += __shfl_xor_sync(~0u, q, 2);
  const float mean = s * (1.0f / DM);
  return ln_consts(mean, fmaxf(q * (1.0f / DM) - mean * mean, 0.f));
}
__device__ __forceinline__ uint8_t* part_ptr(int f, int mb, int p) {
  const int i = f * 16 + mb;
  if (ALIAS && p == 4) return g_o + i * 16384;
  if (ALIAS && (p >> 1) == ALIAS - 1) return g_qkv + (size_t)(i * 2 + (p & 1)) * 32768;
  return g_part + (size_t)(i * 5 + p) * 32768;
}
__device__ __forceinline__ uint32_t glu_pair(float g0, float g1, float u0, float u1) {
  return pack_bf16(fmaf(tanhf_fast(g0), u0, u0), fmaf(tanhf_fast(g1), u1, u1));
}
template <int NG>
__device__ __forceinline__ void stage_part(const float* acc, uint32_t stg, int lane) {
  const int r = (lane & 7) + ((lane >> 3) & 1) * 8;
#pragma unroll
  for (int i = 0; i < NG; i += 2) {
    const int ch = i + (lane >> 4);
    stsm4(stg + r * (NG * 16) + ((ch ^ (r & 7)) << 4), pack_bf16(acc[4 * i], acc[4 * i + 1]), pack_bf16(acc[4 * i + 2], acc[4 * i + 3]),
          pack_bf16(acc[4 * i + 4], acc[4 * i + 5]), pack_bf16(acc[4 * i + 6], acc[4 * i + 7]));
  }
}
__global__ void CL4 __launch_bounds__(384, 1) k4_kernel(const __grid_constant__ CUtensorMap mg,
                                                    const __grid_constant__ CUtensorMap mu, const __grid_constant__ CUtensorMap md,
                                                    __nv_bfloat16* __restrict__ out) {
  extern __shared__ __align__(1024) uint8_t smem_raw[];
  const uint32_t sb = s2u(smem_raw);
  const uint32_t R = sb, RING = sb + R_BYTES, BAR = RING + NSTG * STG_BYTES, TAB = BAR + 512;
  const uint32_t full = BAR, empty = BAR + 64, xfull = BAR + 128, gfull = BAR + 272, sfull = BAR + 320;
  const int tid = threadIdx.x, lane = tid & 31, warp = tid >> 5;
  const int mb = blockIdx.x >> 3, fb = blockIdx.x & 7;
  if (tid == 0) {
    TS(4, 0);
    if (sb & 1023) __trap();
    for (int i = 0; i < 10; i++) mbar_init(sfull + i * 8, 4);
    for (int i = 0; i < NSTG; i++) { mbar_init(full + i * 8, 1); mbar_init(empty + i * 8, 8); }
    for (int i = 0; i < 9; i++) mbar_init(xfull + i * 8, 1);
    for (int i = 0; i < 5; i++) mbar_init(gfull + i * 8, 1);
    mbar_arrive(full);
    for (int i = 0; i < 9; i++) mbar_expect(xfull + i * 8, 16384);
    fence_bar_init();
  }
  if (MC & 4) pair_sync(); else __syncthreads();
  if (warp >= 8) {
    REG_DEC(24);
    if (lane == 0) {
      if (warp == 8) {
        int st = 1; uint32_t ph = 0;
        for (int it = 0; it < 126; it++) {
          const int t = it / 9, s = it - t * 9;
          const uint32_t dst = RING + st * STG_BYTES, fb_ = full + st * 8;
          mbar_wait(empty + st * 8, ph ^ 1);
          if (t < 9) {
            mbar_expect(fb_, 16384);
            tma2d(dst, &mg, fb * 576 + t * 64, s * 64, fb_);
            tma2d(dst + 8192, &mu, fb * 576 + t * 64, s * 64, fb_);
          } else {
            mbar_expect(fb_, t < 13 ? 16384 : 8192);
            tma2d(dst, &md, (t - 9) * 128, fb * 576 + s * 64, fb_);
            if (t < 13) tma2d(dst + 8192, &md, (t - 9) * 128 + 64, fb * 576 + s * 64, fb_);
          }
          if (++st == NSTG) { st = 0; ph ^= 1; }
        }
      }
#define GATHER(p)                                                               \
  { unsigned int v; int n = 0;                                                  \
    do { asm volatile("ld.acquire.gpu.global.u32 %0,[%1];" : "=r"(v) : "l"(g_cnt + mb * 5 + (p)) : "memory"); } while (v < 8 && ++n < 20000000); \
    if (v < 8) __trap();                                                        \
    asm volatile("fence.proxy.async.global;" ::: "memory");                     \
    TS(3, 9 + (p));                                                             \
    const uint32_t sz = (p) < 4 ? 4096 : 2048;                                  \
    mbar_expect(gfull + (p) * 8, sz * 8);                                       \
    _Pragma("unroll 1") for (int f = 0; f < 8; f++)                             \
      bulk_g2s((p) < 4 ? R + (p) * 32768 + f * 4096 : RING + (2 + (f >> 2)) * STG_BYTES + 8192 + (f & 3) * 2048, \
               part_ptr(f, mb, p) + fb * sz, sz, gfull + (p) * 8); }
      if (warp < 11) {
#pragma unroll 1
        for (int p = warp == 8 ? 4 : warp - 9; p < 5 - (warp != 8); p += 2) {
          uint8_t* dst = part_ptr(fb, mb, p);
#pragma unroll 1
          for (int wg = 0; wg < 2; wg++) {
            mbar_wait(sfull + (p * 2 + wg) * 8, 0);
            if (p < 4) {
              bulk_s2g(dst + wg * 16384, R + p * 32768 + wg * 8192, 8192);
              bulk_s2g(dst + wg * 16384 + 8192, R + p * 32768 + 16384 + wg * 8192, 8192);
            } else {
              bulk_s2g(dst + wg * 8192, RING + wg * STG_BYTES + 8192, 8192);
            }
          }
          bulk_commit();
          if (p >= 3) TS(3, 11 + p);
          bulk_wait0();
          TS(3, 4 + p);
          asm volatile("fence.proxy.async.global;" ::: "memory");
          asm volatile("red.release.gpu.global.add.u32 [%0],1;" ::"l"(g_cnt + mb * 5 + p) : "memory");
          GATHER(p);
        }
      } else {
        pdl_wait();
        const uint32_t t0 = clock();
        for (int c = 0; c < 9; c++) {
          while ((uint32_t)clock() - t0 < (uint32_t)(c * PACE4)) {}
          const int k = c < 2 ? c : (c == 2 ? 8 : c - 1);
          if (MC & 4) { bulk_g2s_mc(R + k * 16384 + (fb & 1) * 8192, g_x1 + (mb * 2 + (fb & 1)) * 73728 + k * 8192, 8192, xfull + c * 8); continue; }
          bulk_g2s(R + k * 16384, g_x1 + mb * 2 * 73728 + k * 8192, 8192, xfull + c * 8);
          bulk_g2s(R + k * 16384 + 8192, g_x1 + (mb * 2 + 1) * 73728 + k * 8192, 8192, xfull + c * 8);
        }
      }
    }
  } else {
    REG_INC(240);
    uint32_t a[36][4];
    const int wg = warp >> 2, wl = warp & 3;
    if (tid < 144) sts128(TAB + tid * 16, g_tab2[tid]);
    bar_sync(1, 256);
    pdl_wait();
    TSS(0);
    float acc[64];
    const uint32_t hsp = R + wg * 8192 + (wl * 16 + (lane & 15)) * 16 + (lane >> 4) * 1024;
#define GLU_SPILL(t)                                                            \
  _Pragma("unroll") for (int j = 0; j < 4; j++) {                               \
    uint32_t h[4];                                                              \
    _Pragma("unroll") for (int e = 0; e < 4; e++)                               \
      h[e] = glu_pair(acc[8 * j + 2 * e], acc[8 * j + 2 * e + 1], acc[32 + 8 * j + 2 * e], acc[32 + 8 * j + 2 * e + 1]); \
    asm volatile("st.shared.v4.b32 [%0],{%1,%2,%3,%4};" ::"r"(hsp + (t) * 16384 + j * 2048), "r"(h[0]), "r"(h[1]), "r"(h[2]), "r"(h[3]) : "memory"); \
  }
    {
      const uint4 s0 = ln2_consts(mb * 128 + warp * 16 + (lane >> 2), lane & 3), s1 = ln2_consts(mb * 128 + warp * 16 + (lane >> 2) + 8, lane & 3);
      TSS(1);
      MMA_TILE_(wl_rs_n128_t1, 0, 0,
                if (s < 8) { mbar_wait(xfull + (s + (s > 1)) * 8, 0); LN_CHUNK(s, load_a_core) }
                if (s == 1) { mbar_wait(xfull + 16, 0); LN_CHUNK(8, load_a_core) if (lane == 0) mbar_arrive(empty); });
    }
    GLU_SPILL(0);
#pragma unroll 1
    for (int t = 0; t < 3; t++) {
      MMA_TILE(wl_rs_n128_t1, 1, t & 1);
      GLU_SPILL(2 * t + 1);
      MMA_TILE(wl_rs_n128_t1, 0, (t & 1) ^ 1);
      GLU_SPILL(2 * t + 2);
    }
    MMA_TILE(wl_rs_n128_t1, 1, 1);
    GLU_SPILL(7);
    MMA_TILE(wl_rs_n128_t1, 0, 0);
#pragma unroll
    for (int j = 0; j < 4; j++)
#pragma unroll
      for (int e = 0; e < 4; e++)
        a[32 + j][e] = glu_pair(acc[8 * j + 2 * e], acc[8 * j + 2 * e + 1], acc[32 + 8 * j + 2 * e], acc[32 + 8 * j + 2 * e + 1]);
#pragma unroll
    for (int k = 0; k < 32; k++)
      asm volatile("ld.shared.v4.b32 {%0,%1,%2,%3},[%4];" : "=r"(a[k][0]), "=r"(a[k][1]), "=r"(a[k][2]), "=r"(a[k][3]) : "r"(hsp + (k >> 2) * 16384 + (k & 3) * 2048) : "memory");
    TSS(2);
    const uint32_t stg = R + (wl >> 1) * 16384 + wg * 8192 + (wl & 1) * 4096;
#define PART_OUT(p)                                                             \
  stage_part<16>(acc, stg + (p) * 32768, lane);                                 \
  fence_async_smem();                                                           \
  __syncwarp();                                                                 \
  if (lane == 0) mbar_arrive(sfull + ((p) * 2 + wg) * 8);
    bar_sync(2 + wg, 128);
#pragma unroll 1
    for (int p = 0; p < 2; p++) {
      MMA_TILE(wl_rs_n128_t1, 1, p);
      PART_OUT(2 * p);
      MMA_TILE(wl_rs_n128_t1, 0, p ^ 1);
      PART_OUT(2 * p + 1);
    }
    MMA_TILE(wl_rs_n64_t1, 1, 0);
    stage_part<8>(acc, RING + wg * STG_BYTES + 8192 + wl * 2048, lane);
    fence_async_smem();
    __syncwarp();
    if (lane == 0) mbar_arrive(sfull + (8 + wg) * 8);
    TSS(3);
    const int rl = tid >> 4, ch = tid & 15;
    const size_t off = (size_t)(mb * 128 + fb * 16 + rl) * DM + ch * 8;
    uint4 xv[5], gv[5];
#pragma unroll
    for (int p = 0; p < 5; p++)
      if (p < 4 || ch < 8) { xv[p] = __ldcg((const uint4*)(g_x1 + (mb * 2 + (fb >> 2)) * 73728 + (p * 16 + ch) * 1024 + ((fb & 3) * 16 + rl) * 16)); gv[p] = __ldcg((const uint4*)(g_gb + p * 128 + ch * 8)); }
#pragma unroll
    for (int p = 0; p < 5; p++) {
      if (p == 4 && ch >= 8) break;
      mbar_wait(gfull + p * 8, 0);
      float r8[8] = {0, 0, 0, 0, 0, 0, 0, 0};
#pragma unroll
      for (int f = 0; f < 8; f++) {
        const uint4 v = lds128((p < 4 ? R + p * 32768 + f * 4096 + rl * 256 : RING + (2 + (f >> 2)) * STG_BYTES + 8192 + (f & 3) * 2048 + rl * 128) +
                               ((ch ^ (rl & 7)) << 4));
        r8[0] += bf_lo(v.x); r8[1] += bf_hi(v.x); r8[2] += bf_lo(v.y); r8[3] += bf_hi(v.y);
        r8[4] += bf_lo(v.z); r8[5] += bf_hi(v.z); r8[6] += bf_lo(v.w); r8[7] += bf_hi(v.w);
      }
      uint4 r;
      r.x = res_pair(xv[p].x, gv[p].x, r8[0], r8[1]);
      r.y = res_pair(xv[p].y, gv[p].y, r8[2], r8[3]);
      r.z = res_pair(xv[p].z, gv[p].z, r8[4], r8[5]);
      r.w = res_pair(xv[p].w, gv[p].w, r8[6], r8[7]);
      *(uint4*)(out + off + p * 128) = r;
      if (p >= 2) TSS(2 + p);
    }
    TSDUMP(4);
  }
}

typedef CUresult (*EncodeFn)(CUtensorMap*, CUtensorMapDataType, cuuint32_t, void*, const cuuint64_t*, const cuuint64_t*,
                             const cuuint32_t*, const cuuint32_t*, CUtensorMapInterleave, CUtensorMapSwizzle,
                             CUtensorMapL2promotion, CUtensorMapFloatOOBfill);
static void make_map(EncodeFn fn, CUtensorMap* m, const void* p, int rows, int cols, int box_rows, int box_cols = 64) {
  cuuint64_t dims[2] = {(cuuint64_t)cols, (cuuint64_t)rows};
  cuuint64_t strides[1] = {(cuuint64_t)cols * 2};
  cuuint32_t box[2] = {(cuuint32_t)box_cols, (cuuint32_t)box_rows};
  cuuint32_t es[2] = {1, 1};
  fn(m, CU_TENSOR_MAP_DATA_TYPE_BFLOAT16, 2, (void*)p, dims, strides, box, es, CU_TENSOR_MAP_INTERLEAVE_NONE,
     box_cols == 64 ? CU_TENSOR_MAP_SWIZZLE_128B : CU_TENSOR_MAP_SWIZZLE_NONE,
     box_cols == 64 ? CU_TENSOR_MAP_L2_PROMOTION_L2_256B : CU_TENSOR_MAP_L2_PROMOTION_NONE, CU_TENSOR_MAP_FLOAT_OOB_FILL_NONE);
}
template <typename... KA, typename... A>
static void launch(void (*k)(KA...), int grid, int block, int smem, bool pdl, A... args) {
  cudaLaunchConfig_t cfg = {};
  cfg.gridDim = dim3(grid); cfg.blockDim = dim3(block); cfg.dynamicSmemBytes = smem; cfg.stream = cudaStreamPerThread;
  cudaLaunchAttribute at;
  at.id = cudaLaunchAttributeProgrammaticStreamSerialization;
  at.val.programmaticStreamSerializationAllowed = 1;
  cfg.attrs = &at; cfg.numAttrs = pdl ? 1 : 0;
  cudaLaunchKernelEx(&cfg, k, KA(args)...);
}

extern "C" void kernel_launch(void* const* d_in, const int* in_sizes, int n_in, void* d_out, int out_size) {
  const __nv_bfloat16* x = (const __nv_bfloat16*)d_in[0];
  void* fnp = nullptr;
  cudaDriverEntryPointQueryResult qr;
  cudaGetDriverEntryPoint("cuTensorMapEncodeTiled", &fnp, cudaEnableDefault, &qr);
  EncodeFn fn = (EncodeFn)fnp;
  CUtensorMap mm, mx, mqkv, mg, mu, md;
  make_map(fn, &mm, d_in[8], DM, 6 * DM, 192, 16);
  make_map(fn, &mx, x, SEQ, DM, 128);
  make_map(fn, &mqkv, d_in[1], DM, 3 * DM, 64);
  make_map(fn, &mg, d_in[4], DM, FF, 64);
  make_map(fn, &mu, d_in[5], DM, FF, 64);
  make_map(fn, &md, d_in[6], FF, DM, 64);
  cudaFuncSetAttribute(k1_kernel, cudaFuncAttributeMaxDynamicSharedMemorySize, GEMM_SMEM);
  cudaFuncSetAttribute(k2_kernel, cudaFuncAttributeMaxDynamicSharedMemorySize, ATT_SMEM);
  cudaFuncSetAttribute(k3_kernel, cudaFuncAttributeMaxDynamicSharedMemorySize, K3_SMEM);
  cudaFuncSetAttribute(k4_kernel, cudaFuncAttributeMaxDynamicSharedMemorySize, GEMM_SMEM);
  launch(k1_kernel, 128, 384, GEMM_SMEM, false, mx, mqkv, mm, (const __nv_bfloat16*)d_in[7], (const uint8_t*)d_in[1], (const uint4*)d_in[2]);
  launch(k2_kernel, 132, 512, ATT_SMEM, true, (const uint8_t*)d_in[0], (const uint8_t*)d_in[4], (const uint8_t*)d_in[5], (const uint8_t*)d_in[6],
         (const __nv_bfloat16*)d_in[7], (const __nv_bfloat16*)d_in[8]);
  launch(k3_kernel, 128, 320, K3_SMEM, true, x);
  launch(k4_kernel, 128, 384, GEMM_SMEM, true, mg, mu, md, (__nv_bfloat16*)d_out);
}
```
